```python
import torch

def _softmax(x, axis=-1):
    return torch.softmax(x, dim=axis)
def _gelu(x):
    return torch.nn.functional.gelu(x, approximate="tanh")
def _silu(x):
    return torch.nn.functional.silu(x)
def _sigmoid(x):
    return torch.sigmoid(x)
def _layernorm(x, axis=-1, eps=1e-5):
    m = x.mean(dim=axis, keepdim=True)
    v = x.var(dim=axis, keepdim=True, unbiased=False)
    return (x - m) / torch.sqrt(v + eps)
def _scatter_add(tgt, idx, src, axis=0):
    return tgt.clone().index_add_(axis, idx, src)
def _segment_sum(src, seg, n):
    out = torch.zeros((n,) + src.shape[1:], dtype=src.dtype)
    return out.index_add_(0, seg, src)
def _pad(x, pw):
    flat = tuple(v for pair in reversed(pw) for v in pair)
    return torch.nn.functional.pad(x, flat)

kernel_name = 'standalone__modern_conv_block_slak__vision'

def setup_inputs():

    _w = (lambda a: (lambda t: t.to(torch.bfloat16) if t.is_floating_point() else t)(torch.as_tensor(a)))
    H = W = 384
    C = 384
    K = 1
    return {
        "x": _w((lambda *s: torch.randn(*s, dtype=torch.bfloat16) * 0.05)(1, H, W, C)),
        "dw": _w((lambda *s: torch.randn(*s, dtype=torch.bfloat16) * 0.05)(K, K, C)),
        "w1": _w((lambda *s: torch.randn(*s, dtype=torch.bfloat16) * 0.05)(C, 4 * C)),
        "w2": _w((lambda *s: torch.randn(*s, dtype=torch.bfloat16) * 0.05)(4 * C, C)),
        "grn_g": _w((lambda *s: torch.randn(*s, dtype=torch.bfloat16) * 0.05)(4 * C)),
        "grn_b": _w((lambda *s: torch.randn(*s, dtype=torch.bfloat16) * 0.05)(4 * C)),
    }

def reference(x, dw, w1, w2, grn_g, grn_b):
    B, H, W, C = x.shape
    K = dw.shape[0]
    pad = K // 2
    xp = _pad(x, ((0,0),(pad,pad),(pad,pad),(0,0)))
    out = torch.zeros_like(x)
    for i in range(K):
        for j in range(K):
            out = out + xp[:, i:i+H, j:j+W, :] * dw[i, j][None, None, None, :]
    h = _layernorm(out, axis=-1)
    h = _gelu(h @ w1)
    gx = torch.sqrt((h * h).sum(axis=(1, 2), keepdims=True) + 1e-6)
    nx = gx / (gx.mean(axis=-1, keepdims=True) + 1e-6)
    h = grn_g[None, None, None, :] * (h * nx) + grn_b[None, None, None, :] + h
    return x + h @ w2
```

```cpp
#include <cuda.h>
#include <cuda_runtime.h>
#include <cuda_bf16.h>
#include <stdint.h>
#include <stdio.h>

namespace {

constexpr int M_TOTAL = 384 * 384;
constexpr int C_DIM   = 384;
constexpr int HID     = 1536;
constexpr int NT128   = M_TOTAL / 128;
constexpr int NUM_CTAS = 132;

constexpr int NGRP = 11, GRP_CTAS = 12;
constexpr int LN_STEP = NUM_CTAS / 4, LN_RING = 2 * LN_STEP;
constexpr int NT_RING = NT128 - NGRP;
constexpr int LN_TILE = 128 * C_DIM * 2;
constexpr int H_TILE = 64 * HID * 3 / 2;
constexpr int H_HALF = 3072, H_STEP = 6144;

__device__ __align__(1024) uint4 g_h[(size_t)M_TOTAL * HID * 3 / 32];
__device__ __align__(1024) uint4 g_ln[LN_RING * LN_TILE / 16];
__device__ __align__(1024) uint4 g_w2img[HID * C_DIM * 2 / 16];
__device__ __align__(16) float g_sums[2][HID + 512];
__device__ unsigned g_ex[HID];
__device__ unsigned g_epoch;
__device__ __align__(128) unsigned g_prog;
__device__ __align__(128) unsigned g_half[32][2];
__device__ unsigned g_flag[LN_RING + 3][2][8];
#define TSTAMP(k, i)
#define TRACE(wg, pos, i)
#define TRACEW(pos, i)

#define TR2(i)
__host__ __device__ __forceinline__ int perm32(int n) {
    return (n & ~31) | (((n >> 1) & 3) << 3) | (((n >> 3) & 3) << 1) | (n & 1);
}

__device__ __forceinline__ uint32_t smem_u32(const void* p) { return (uint32_t)__cvta_generic_to_shared(p); }

__device__ __forceinline__ void mbar_init(uint32_t bar, uint32_t count) {
    asm volatile("mbarrier.init.shared::cta.b64 [%0], %1;\n" ::"r"(bar), "r"(count) : "memory");
}
__device__ __forceinline__ void mbar_expect_tx(uint32_t bar, uint32_t bytes) {
    asm volatile("mbarrier.arrive.expect_tx.shared::cta.b64 _, [%0], %1;\n" ::"r"(bar), "r"(bytes) : "memory");
}
__device__ __forceinline__ void mbar_arrive(uint32_t bar) {
    asm volatile("mbarrier.arrive.shared::cta.b64 _, [%0];\n" ::"r"(bar) : "memory");
}
__device__ __forceinline__ void mbar_arrive_cluster(uint32_t bar_cluster_addr) {
    asm volatile("mbarrier.arrive.shared::cluster.b64 _, [%0];\n" ::"r"(bar_cluster_addr) : "memory");
}
#define SAFE_BREAK
__device__ __forceinline__ void mbar_wait(uint32_t bar, uint32_t parity) {
    asm volatile(
        "{\n"
        ".reg .pred p;\n"
        "LAB_WAIT:\n"
        "mbarrier.try_wait.parity.shared::cta.b64 p, [%0], %1;\n"
        "@!p bra LAB_WAIT;\n"
        "}\n" ::"r"(bar), "r"(parity) : "memory");
}
__device__ __forceinline__ bool mbar_test(uint32_t bar, uint32_t parity) {
    uint32_t ok;
    asm volatile("{\n.reg .pred p;\n"
                 "mbarrier.test_wait.parity.shared::cta.b64 p, [%1], %2;\n"
                 "selp.u32 %0, 1, 0, p;\n}\n" : "=r"(ok) : "r"(bar), "r"(parity) : "memory");
    return ok != 0;
}
__device__ __forceinline__ uint32_t mapa(uint32_t addr, uint32_t rank) {
    uint32_t r;
    asm volatile("mapa.shared::cluster.u32 %0, %1, %2;\n" : "=r"(r) : "r"(addr), "r"(rank));
    return r;
}
__device__ __forceinline__ void bulk_g2s(uint32_t dst, const void* src, uint32_t bytes, uint32_t bar) {
    asm volatile("cp.async.bulk.shared::cluster.global.mbarrier::complete_tx::bytes [%0], [%1], %2, [%3];\n"
                 ::"r"(dst), "l"(src), "r"(bytes), "r"(bar) : "memory");
}
__device__ __forceinline__ void bulk_g2s_mc(uint32_t dst, const void* src, uint32_t bytes, uint32_t bar, uint16_t mask) {
    asm volatile("cp.async.bulk.shared::cluster.global.mbarrier::complete_tx::bytes.multicast::cluster [%0], [%1], %2, [%3], %4;\n"
                 ::"r"(dst), "l"(src), "r"(bytes), "r"(bar), "h"(mask) : "memory");
}
__device__ __forceinline__ void tma2(uint32_t dst, const CUtensorMap* map, int c0, int c1, uint32_t bar) {
    asm volatile("cp.async.bulk.tensor.2d.shared::cluster.global.tile.mbarrier::complete_tx::bytes [%0], [%1, {%2, %3}], [%4];\n"
                 ::"r"(dst), "l"(map), "r"(c0), "r"(c1), "r"(bar) : "memory");
}
template <bool ACQ>
__device__ __forceinline__ uint32_t flag_wait(const unsigned* p, unsigned target) {
    unsigned v, n = 0;
    do {
        if (ACQ) asm volatile("ld.acquire.gpu.global.u32 %0, [%1];\n" : "=r"(v) : "l"(p) : "memory");
        else asm volatile("ld.relaxed.gpu.global.u32 %0, [%1];\n" : "=r"(v) : "l"(p) : "memory");
        n++;
    } while (v < target);
    return n == 1;
}
__device__ __forceinline__ void ldsm4t(uint32_t (&r)[4], uint32_t addr) {
    asm volatile("ldmatrix.sync.aligned.m8n8.x4.trans.shared.b16 {%0,%1,%2,%3}, [%4];\n"
                 : "=r"(r[0]), "=r"(r[1]), "=r"(r[2]), "=r"(r[3]) : "r"(addr) : "memory");
}
__device__ __forceinline__ void bulk_s2g(void* dst, uint32_t src, uint32_t bytes) {
    asm volatile("cp.async.bulk.global.shared::cta.bulk_group [%0], [%1], %2;\n" ::"l"(dst), "r"(src), "r"(bytes) : "memory");
}
__device__ __forceinline__ void cluster_sync() {
    asm volatile("barrier.cluster.arrive.aligned;\nbarrier.cluster.wait.aligned;\n" ::: "memory");
}
__device__ __forceinline__ void cluster_sync_relaxed() {
    asm volatile("barrier.cluster.arrive.relaxed.aligned;\nbarrier.cluster.wait.aligned;\n" ::: "memory");
}
__device__ __forceinline__ void gdc_wait() { asm volatile("griddepcontrol.wait;\n" ::: "memory"); }
__device__ __forceinline__ void gdc_launch() { asm volatile("griddepcontrol.launch_dependents;\n" ::: "memory"); }
__device__ __forceinline__ uint32_t cluster_rank() {
    uint32_t r;
    asm volatile("mov.u32 %0, %%cluster_ctarank;\n" : "=r"(r));
    return r;
}
__device__ __forceinline__ bool elect_one() {
    uint32_t pred;
    asm volatile("{\n.reg .pred p;\nelect.sync _|p, 0xffffffff;\nselp.u32 %0, 1, 0, p;\n}\n" : "=r"(pred));
    return pred != 0;
}
__device__ __forceinline__ void wg_fence() { asm volatile("wgmma.fence.sync.aligned;\n" ::: "memory"); }
__device__ __forceinline__ void wg_commit() { asm volatile("wgmma.commit_group.sync.aligned;\n" ::: "memory"); }
template <int N> __device__ __forceinline__ void wg_wait() {
    asm volatile("wgmma.wait_group.sync.aligned %0;\n" ::"n"(N) : "memory");
}
template <int R> __device__ __forceinline__ void reg_inc() { asm volatile("setmaxnreg.inc.sync.aligned.u32 %0;\n" ::"n"(R)); }
template <int R> __device__ __forceinline__ void reg_dec() { asm volatile("setmaxnreg.dec.sync.aligned.u32 %0;\n" ::"n"(R)); }
__device__ __forceinline__ void bar_sync(int id, int n) { asm volatile("bar.sync %0, %1;\n" ::"r"(id), "r"(n) : "memory"); }
__device__ __forceinline__ void bar_arrive(int id, int n) { asm volatile("bar.arrive %0, %1;\n" ::"r"(id), "r"(n) : "memory"); }

__device__ __forceinline__ uint64_t make_desc(uint32_t saddr, uint32_t lbo, uint32_t sbo) {
    return (uint64_t)((saddr & 0x3FFFF) >> 4) | ((uint64_t)(lbo >> 4) << 16) | ((uint64_t)(sbo >> 4) << 32);
}

__device__ __forceinline__ void stg128_cs(void* p, uint32_t a, uint32_t b, uint32_t c, uint32_t d) {
    asm volatile("st.global.cs.v4.u32 [%0], {%1,%2,%3,%4};\n" ::"l"(p), "r"(a), "r"(b), "r"(c), "r"(d) : "memory");
}
__device__ __forceinline__ uint32_t pack_bf16(float lo, float hi) {
    uint32_t r;
    asm("cvt.rn.bf16x2.f32 %0, %1, %2;\n" : "=r"(r) : "f"(hi), "f"(lo));
    return r;
}
__device__ __forceinline__ float bf_lo(uint32_t v) { return __uint_as_float(v << 16); }
__device__ __forceinline__ float bf_hi(uint32_t v) { return __uint_as_float(v & 0xffff0000u); }
__device__ __forceinline__ uint32_t bf2_mul(uint32_t a, uint32_t b) {
    uint32_t r;
    asm("mul.rn.bf16x2 %0, %1, %2;\n" : "=r"(r) : "r"(a), "r"(b));
    return r;
}
__device__ __forceinline__ uint32_t bf2_fma(uint32_t a, uint32_t b, uint32_t c) {
    uint32_t r;
    asm("fma.rn.bf16x2 %0, %1, %2, %3;\n" : "=r"(r) : "r"(a), "r"(b), "r"(c));
    return r;
}
__device__ __forceinline__ uint32_t bf2_add(uint32_t a, uint32_t b) {
    uint32_t r;
    asm("add.rn.bf16x2 %0, %1, %2;\n" : "=r"(r) : "r"(a), "r"(b));
    return r;
}
constexpr float KAPPA = 0.3292034911525734f;
constexpr float GELU_C = 2.423681954311584f;
constexpr float HSCALE = 1.0f / (2.0f * KAPPA);
__device__ __forceinline__ void sched_break(int zero) {
    asm volatile("{\n.reg .pred p;\nsetp.ne.s32 p, %0, 0;\nSB_LOOP:\n@p nanosleep.u32 1;\n@p bra SB_LOOP;\n}\n" ::"r"(zero));
}

#define ACC8(d, o) "+f"(d[o + 0]), "+f"(d[o + 1]), "+f"(d[o + 2]), "+f"(d[o + 3]), "+f"(d[o + 4]), "+f"(d[o + 5]), "+f"(d[o + 6]), "+f"(d[o + 7])

#define ACCR8(d, o) "+r"(d[o + 0]), "+r"(d[o + 1]), "+r"(d[o + 2]), "+r"(d[o + 3]), "+r"(d[o + 4]), "+r"(d[o + 5]), "+r"(d[o + 6]), "+r"(d[o + 7])
__device__ __forceinline__ void mma_rs_n128(uint32_t (&d)[32], const uint32_t (&a)[4], uint64_t desc, int scale_d) {
    asm volatile(
        "{\n.reg .pred p;\nsetp.ne.b32 p, %37, 0;\n"
        "wgmma.mma_async.sync.aligned.m64n128k16.f16.f16.f16 "
        "{%0,%1,%2,%3,%4,%5,%6,%7,%8,%9,%10,%11,%12,%13,%14,%15,"
        "%16,%17,%18,%19,%20,%21,%22,%23,%24,%25,%26,%27,%28,%29,%30,%31},"
        "{%32,%33,%34,%35}, %36, p, 1, 1, 0;\n}\n"
        : ACCR8(d, 0), ACCR8(d, 8), ACCR8(d, 16), ACCR8(d, 24)
        : "r"(a[0]), "r"(a[1]), "r"(a[2]), "r"(a[3]), "l"(desc), "r"(scale_d));
}
__device__ __forceinline__ uint32_t bf2_to_h2(uint32_t v) {
    v = bf2_mul(v, 0x07800780u);
    return (v & 0x0fff0fffu) * 7u + v;
}
__device__ __forceinline__ float h_lo(uint32_t v) {
    float r;
    asm("{\n.reg .b16 l, h;\nmov.b32 {l, h}, %1;\ncvt.f32.f16 %0, l;\n}\n" : "=f"(r) : "r"(v));
    return r;
}
__device__ __forceinline__ float h_hi(uint32_t v) {
    float r;
    asm("{\n.reg .b16 l, h;\nmov.b32 {l, h}, %1;\ncvt.f32.f16 %0, h;\n}\n" : "=f"(r) : "r"(v));
    return r;
}

__device__ __forceinline__ void mma_rs_n192(uint32_t (&d)[48], const uint4& a, uint64_t db) {
    asm volatile(
        "{\n.reg .pred p;\nsetp.ne.b32 p, %53, 0;\n"
        "wgmma.mma_async.sync.aligned.m64n192k16.f16.f16.f16 "
        "{%0,%1,%2,%3,%4,%5,%6,%7,%8,%9,%10,%11,%12,%13,%14,%15,"
        "%16,%17,%18,%19,%20,%21,%22,%23,%24,%25,%26,%27,%28,%29,%30,%31,"
        "%32,%33,%34,%35,%36,%37,%38,%39,%40,%41,%42,%43,%44,%45,%46,%47},"
        "{%48,%49,%50,%51}, %52, p, 1, 1, 0;\n}\n"
        : ACCR8(d, 0), ACCR8(d, 8), ACCR8(d, 16), ACCR8(d, 24), ACCR8(d, 32), ACCR8(d, 40)
        : "r"(a.x), "r"(a.y), "r"(a.z), "r"(a.w), "l"(db), "r"(1));
}

__device__ __forceinline__ void mma_ss_n192_init(uint32_t (&d)[48], uint64_t da, uint64_t db) {
    asm volatile(
        "{\n.reg .pred p;\nsetp.ne.b32 p, %50, 0;\n"
        "wgmma.mma_async.sync.aligned.m64n192k16.f16.f16.f16 "
        "{%0,%1,%2,%3,%4,%5,%6,%7,%8,%9,%10,%11,%12,%13,%14,%15,"
        "%16,%17,%18,%19,%20,%21,%22,%23,%24,%25,%26,%27,%28,%29,%30,%31,"
        "%32,%33,%34,%35,%36,%37,%38,%39,%40,%41,%42,%43,%44,%45,%46,%47},"
        "%48, %49, p, 1, 1, 0, 0;\n}\n"
        : ACCR8(d, 0), ACCR8(d, 8), ACCR8(d, 16), ACCR8(d, 24), ACCR8(d, 32), ACCR8(d, 40)
        : "l"(da), "l"(db), "r"(0));
}
__device__ __forceinline__ uint32_t pack_f16(float lo, float hi) {
    uint32_t r;
    asm("cvt.rn.f16x2.f32 %0, %1, %2;\n" : "=r"(r) : "f"(hi), "f"(lo));
    return r;
}

#define P1_ARR 23
#define P1_PACE true
constexpr int P1_SLOT = LN_TILE / 2, P1_NST = 4;
constexpr int P1_X = 32 * C_DIM * 2;
constexpr int P1_OFF_X = P1_SLOT * P1_NST;
constexpr int P1_OFF_BAR = P1_OFF_X + P1_X;
constexpr int P1_OFF_TILE = P1_OFF_BAR + (2 * P1_NST + 2 + 4 + 4) * 8;
constexpr int P1_OFF_RAW = P1_OFF_TILE + 64;
constexpr int P1_SMEM = P1_OFF_RAW + 16;

__device__ __forceinline__ float rsqrt_fast(float x) {
    float r;
    asm("rsqrt.approx.ftz.f32 %0, %1;\n" : "=f"(r) : "f"(x));
    return r;
}
__device__ __forceinline__ float row_sum(const uint32_t (&c)[4]) {
    const uint32_t u = bf2_add(bf2_add(c[0], c[1]), bf2_add(c[2], c[3]));
    float s = bf_lo(u) + bf_hi(u);
#pragma unroll
    for (int o = 1; o < 8; o <<= 1) s += __shfl_xor_sync(0xffffffffu, s, o);
    return s;
}
__device__ __forceinline__ uint32_t pace(uint32_t bar, uint32_t off, uint32_t val, uint32_t after, int zero) {
    asm volatile(
        "{\n.reg .pred p;\n.reg .b32 par;\n"
        "lop3.b32 par, %4, %2, %3, 0xea;\n"
        "mbarrier.test_wait.parity.shared::cta.b64 p, [%1], par;\n"
        "selp.u32 par, 1, 0, p;\n"
        "mbarrier.try_wait.parity.shared::cta.b64 p, [%1], par, 1000;\n"
        "@p or.b32 %0, %0, %2;\n"
        "}\n" : "+r"(val) : "r"(bar), "r"(zero), "r"(off), "r"(after));
    return val;
}
template <bool PACE>
__device__ __forceinline__ void ln_row(uint32_t (&v)[6][4], const uint32_t (&d)[6][4], uint32_t bar, uint32_t off, int zero,
                                       uint32_t bar_read) {
    uint32_t c[4];
#pragma unroll
    for (int i = 0; i < 6; i++)
#pragma unroll
        for (int k = 0; k < 4; k++) c[k] = bf2_fma(v[i][k], d[i][k], i ? c[k] : 0);
    const float inv = 1.0f / C_DIM;
    const float m = row_sum(c) * inv;
    uint32_t nm = pack_bf16(-m, -m);
    const float e = m + bf_lo(nm);
    if (bar_read) mbar_arrive(bar_read + (nm & zero));
    if (PACE) nm = pace(bar, off, nm, nm, zero);
#pragma unroll
    for (int i = 0; i < 6; i++) {
#pragma unroll
        for (int k = 0; k < 4; k++) {
            v[i][k] = bf2_fma(v[i][k], d[i][k], nm);
            c[k] = i ? bf2_fma(v[i][k], v[i][k], c[k]) : bf2_mul(v[i][k], v[i][k]);
        }
    }
    const float r = KAPPA * rsqrt_fast(fmaxf(fmaf(-e, e, row_sum(c) * inv), 0.f) + 1e-5f);
    uint32_t rs = pack_bf16(r, r);
    const uint32_t sh = pack_bf16(-e * r, -e * r);
    if (PACE) rs = pace(bar, off, rs, sh, zero);
#pragma unroll
    for (int i = 0; i < 6; i++)
#pragma unroll
        for (int k = 0; k < 4; k++) v[i][k] = bf2_to_h2(bf2_fma(v[i][k], rs, sh));
}

__device__ __forceinline__ float gelu_s(float y) {
    float u = y * fmaf(y, y, GELU_C);
    float t;
    asm volatile("tanh.approx.f32 %0, %1;\n" : "=f"(t) : "f"(u));
    return fmaf(y, t, y);
}
__device__ __forceinline__ constexpr int p1_reg(int c, int u) { return 16 * (c >> 1) + 4 * (u >> 1) + 2 * (c & 1) + (u & 1); }
template <bool BIG>
__device__ __forceinline__ void p1_pack(int c, uint32_t (&p)[4], uint32_t (&dd)[4], uint32_t (&sq)[4], uint32_t sc2) {
    uint32_t& s = sq[(c >> 2) * 2 + (c & 1)];
    s = (c & 2) ? bf2_fma(p[0], p[0], s) : bf2_mul(p[0], p[0]);
    s = bf2_fma(p[3], p[3], bf2_fma(p[2], p[2], bf2_fma(p[1], p[1], s)));
#pragma unroll
    for (int u = 0; u < 4; u++) {
        uint32_t v;
        if (c & 1) asm("{\n.reg .b16 l, h;\n.reg .b32 f;\nmov.b32 {l, h}, %2;\nmov.b32 f, {h, h};\nmul.rn.bf16x2 %0, %1, f;\n}\n" : "=r"(v) : "r"(p[u]), "r"(sc2));
        else asm("{\n.reg .b16 l, h;\n.reg .b32 f;\nmov.b32 {l, h}, %2;\nmov.b32 f, {l, l};\nmul.rn.bf16x2 %0, %1, f;\n}\n" : "=r"(v) : "r"(p[u]), "r"(sc2));
        if (BIG) v = bf2_mul(v, 0x07800780u);
        if ((c & 3) == 0) dd[u] = v;
        else {
            uint32_t n = dd[u];
            if ((c & 3) == 1) { n <<= 4; dd[u] = __byte_perm(dd[u], 0, 0x2301); }
            if ((c & 3) == 2) dd[u] <<= 4;
            asm("lop3.b32 %0, %1, %2, 0x78007800, 0xd8;\n" : "=r"(p[u]) : "r"(v), "r"(n));
        }
    }
}
__device__ __forceinline__ void p1_store(int c, const uint32_t (&p)[4], uint8_t* hptr) {
    if (c & 3) stg128_cs(hptr + (c >> 2) * H_HALF + ((c & 3) - 1) * 512, p[0], p[1], p[2], p[3]);
}

__device__ __forceinline__ uint32_t p1_parity(uint32_t sbase) {
    uint32_t v;
    asm volatile("ld.shared.u32 %0, [%1];\n" : "=r"(v) : "r"(sbase + P1_OFF_TILE - 4) : "memory");
    return v;
}
template <bool GEN>
__device__ __forceinline__ uint32_t gelu2(uint32_t y, float fs) {
    if (GEN) return pack_bf16(gelu_s(h_lo(y) * fs), gelu_s(h_hi(y) * fs));
    uint32_t g;
    asm("{\n.reg .b32 w;\n"
        "fma.rn.f16x2 w, %1, %1, %2;\n"
        "mul.rn.f16x2 w, w, %1;\n"
        "tanh.approx.f16x2 w, w;\n"
        "fma.rn.f16x2 %0, %1, w, %1;\n}\n" : "=r"(g) : "r"(y), "r"(0x40d940d9u));
    return pack_bf16(h_lo(g), h_hi(g));
}
template <int WG, bool GEN>
__device__ __forceinline__ void p1_consumer(const uint32_t (&a)[24][4], uint32_t sc2, const float (&fs)[2], uint32_t sbase, int w, int lane, int zero) {
    const uint32_t bar_full = sbase + P1_OFF_BAR, bar_empty = bar_full + P1_NST * 8;
    const uint32_t empty_remote = mapa(bar_empty, lane & 1) + (WG == 0 ? (lane & 2) * 4 : 0);
    const uint32_t bar_pace = bar_empty + P1_NST * 8 + 16 + w * 8;
    const int g = lane >> 2, q = lane & 3, cb = (blockIdx.x % GRP_CTAS) * 2 + WG;
    float ssq[2] = {0.f, 0.f};
    uint32_t acc[32], sq[4], dd[4];
    TSTAMP(0, 1);

    uint8_t* hp = reinterpret_cast<uint8_t*>(g_h) + (size_t)(blockIdx.x / GRP_CTAS) * (2 * H_TILE) + ((cb * 2 + (w >> 1)) * H_STEP + (w & 1) * 1536) + g * 64 + (q ^ (g >> 1)) * 16;
    const uint64_t desc_base = make_desc(sbase, 16, 1024) | (1ull << 62);
#pragma unroll 1
    for (int i = 0;; i++) {
        const int s0 = (i & 1) * 16, par = (i >> 1) & 1;
        const uint64_t d0 = desc_base + (uint64_t)((i & 1) * (LN_TILE / 16));
        TRACE(WG, i, 0);
        if (WG == 0) mbar_wait(bar_full + s0, par);
        bar_sync(1 + WG, 256);
        TRACE(WG, i, 1);
        uint32_t step, more;
        wg_fence();
#pragma unroll
        for (int k = 0; k < 24; k++) {
            if (WG == 0 && k == 12) mbar_wait(bar_full + s0 + 8, par);
            mma_rs_n128(acc, a[k], d0 + (uint64_t)((k >> 2) * 1024 + (k & 3) * 2), k != 0);
            if (k == P1_ARR) bar_arrive(2 - WG, 256);
            if (k % 6 == 5) wg_commit();
        }
        asm volatile("ld.shared.v2.u32 {%0, %1}, [%2];\n" : "=r"(step), "=r"(more) : "r"(sbase + P1_OFF_TILE + (i & 3) * 16) : "memory");
        TRACE(WG, i, 2);
        if (WG == 1) {
            wg_wait<2>();
            if (lane < 2) mbar_arrive_cluster(empty_remote + s0);
        }
        hp += step;
        TRACE(WG, i, 3);
        wg_wait<0>();
        TRACE(WG, i, 4);
        if (lane < (WG == 0 ? 4 : 2)) mbar_arrive_cluster(empty_remote + s0 + WG * 8);
#pragma unroll
        for (int c = 0; c < 8; c++) {
            uint32_t p[4];
#pragma unroll
            for (int u = 0; u < 4; u++) p[u] = gelu2<GEN>(acc[8 * (c >> 1) + 2 * u + (c & 1)], fs[c & 1]);
            p1_pack<GEN>(c, p, dd, sq, sc2);
            p1_store(c, p, hp);
        }
#pragma unroll
        for (int r = 0; r < 2; r++) {
            const uint32_t u = bf2_add(sq[r], sq[2 + r]);
            ssq[r] += bf_lo(u) + bf_hi(u);
        }
        if (lane == 0) mbar_arrive(bar_pace);
        if (!more) break;
    }
    TSTAMP(0, 21);
    if (WG == 0) bar_sync(1, 256);
#pragma unroll
    for (int r = 0; r < 2; r++) {
        ssq[r] += __shfl_xor_sync(0xffffffffu, ssq[r], 1);
        ssq[r] += __shfl_xor_sync(0xffffffffu, ssq[r], 2);
        if (q == 0) atomicAdd(&g_sums[p1_parity(sbase)][cb * 64 + w * 16 + r * 8 + g], ssq[r]);
    }
}

__global__ void __cluster_dims__(2, 1, 1) __launch_bounds__(512, 1)
pass1_kernel(const __grid_constant__ CUtensorMap wmap, const __nv_bfloat16* __restrict__ x, const __nv_bfloat16* __restrict__ dw,
             const __nv_bfloat16* __restrict__ w2, const __nv_bfloat16* __restrict__ grn_b, int zero) {
    extern __shared__ __align__(1024) uint8_t smem[];
    const uint32_t sbase = smem_u32(smem);
    const uint32_t bar_full = sbase + P1_OFF_BAR, bar_empty = bar_full + P1_NST * 8, bar_w = bar_empty + P1_NST * 8;
    const int tid = threadIdx.x;
    const int warp = __shfl_sync(0xffffffffu, tid >> 5, 0), lane = tid & 31;
    const uint32_t rank = cluster_rank();
    const int cig = blockIdx.x % GRP_CTAS;
    uint8_t* const ring = reinterpret_cast<uint8_t*>(g_ln);

    TSTAMP(0, 0);
    TRACEW(110 + warp, 0);
    const uint32_t bar_pace = bar_w + 16, bar_xfull = bar_pace + 32, bar_xempty = bar_xfull + 8, bar_done = bar_xfull + 16;
    const uint32_t bar_raw = sbase + P1_OFF_RAW;
    const int ln0 = blockIdx.x >> 2, first = blockIdx.x / GRP_CTAS;
    const uint8_t* xsrc = reinterpret_cast<const uint8_t*>(x) + (size_t)(NGRP * 4 + blockIdx.x) * P1_X;

    if (warp >= 12) {
        reg_dec<24>();
        asm volatile("barrier.cluster.arrive.relaxed.aligned;\n" ::: "memory");
        asm volatile("barrier.cluster.wait.aligned;\n" ::: "memory");
        if (warp == 12) {
            int prev = first - NGRP, t = first, next = t + NGRP;
            const uint32_t rbase = mapa(sbase, lane & 1);
#pragma unroll 1
            for (int i = 1; t < NT_RING; i++) {
                const int s0 = (i & 1) * 2, par = ((i + 1) >> 1 & 1) ^ 1;
                const int round = t / LN_RING, slot = t - round * LN_RING;
                const uint8_t* src = ring + slot * LN_TILE + rank * (P1_SLOT / 2);
                int draw = 0;
                if (rank == 0 && lane == 0) draw = atomicAdd(&g_flag[LN_RING + (cig >> 2)][(cig >> 1) & 1][0], 1u);
                flag_wait<true>(&g_flag[slot][0][0], 4 * round + 4);
                TRACEW(i, 2);
                asm volatile("fence.proxy.async.global;\n" ::: "memory");
                draw = 2 * NGRP + __shfl_sync(0xffffffffu, draw, 0);
#pragma unroll
                for (int h = 0; h < 2; h++) {
                    mbar_wait(bar_empty + (s0 + h) * 8, par);
                    TRACEW(i, 4 + h);
                    if (elect_one()) {
                        mbar_expect_tx(bar_full + (s0 + h) * 8, P1_SLOT + 16 - 16 * h);
                        bulk_g2s_mc(sbase + (s0 + h) * P1_SLOT + rank * (P1_SLOT / 2), src + h * P1_SLOT, P1_SLOT / 2, bar_full + (s0 + h) * 8, (uint16_t)3);
                    }
                    __syncwarp();
                    if (h == 0 && rank == 0 && lane < 2)
                        asm volatile("st.async.shared::cluster.mbarrier::complete_tx::bytes.v4.u32 [%0], {%1, %2, %3, %3}, [%4];\n"
                                     ::"r"(rbase + P1_OFF_TILE + (i & 3) * 16), "r"((t - prev) * (2 * H_TILE)), "r"((int)(next < NT_RING)), "r"(draw),
                                       "r"(rbase + P1_OFF_BAR + s0 * 8) : "memory");
                }
                prev = t;
                t = next;
                next = draw;
                if (rank != 0) {
                    mbar_wait(bar_full + (s0 ^ 2) * 8, ((i - 1) >> 1) & 1);
                    asm volatile("ld.shared.u32 %0, [%1];\n" : "=r"(t) : "r"(sbase + P1_OFF_TILE + ((i - 1) & 3) * 16 + 8) : "memory");
                }
            }
        } else if (warp == 13) {
            int ph = 0;
            unsigned target = 0;
#pragma unroll 1
            for (int i = ln0 + LN_STEP; i < NT_RING; i += LN_STEP, ph ^= 1) {
                target += ph * (GRP_CTAS / 2);
                xsrc += (size_t)NUM_CTAS * P1_X;
                mbar_wait(bar_xempty, ph);
                if (elect_one()) {
                    mbar_expect_tx(bar_xfull, P1_X);
                    bulk_g2s(sbase + P1_OFF_X, xsrc, P1_X, bar_xfull);
                }
                __syncwarp();
                const uint32_t off = flag_wait<false>(&g_flag[ln0 + (ph ^ 1) * LN_STEP][1][0], target);
                mbar_wait(bar_done, ph);
                if (elect_one()) {
                    asm volatile("st.shared.u32 [%0], %1;\n" ::"r"(bar_done + 8), "r"(off) : "memory");
                    mbar_arrive(bar_xfull);
                }
                __syncwarp();
            }
        } else if (warp == 15) {
            if (rank == 1 && lane < 2) mbar_arrive(bar_empty + (2 + lane) * 8);
            const uint32_t par = g_epoch & 1;
            asm volatile("st.shared.u32 [%0], %1;\n" ::"r"(sbase + P1_OFF_TILE - 4), "r"(par) : "memory");
            if (blockIdx.x < 16) reinterpret_cast<float4*>(g_sums[par ^ 1])[blockIdx.x * 32 + lane] = make_float4(0.f, 0.f, 0.f, 0.f);
            bar_arrive(3, 160);
            {
                bar_sync(4, 288);
                mbar_wait(bar_raw + 8, 0);
                const uint32_t o = lane * 16384 + rank * 8192, peer = mapa(sbase, rank ^ 1);
                if (lane < 6)
                    asm volatile("cp.async.bulk.shared::cluster.shared::cta.mbarrier::complete_tx::bytes [%0], [%1], 8192, [%2];\n"
                                 ::"r"(peer + o), "r"(sbase + o), "r"(peer + P1_OFF_BAR + (lane >= 3 ? 8 : 0)) : "memory");
                __syncwarp();
            }
            int t = first, next = t + NGRP;
            if (rank == 1) {
                mbar_wait(bar_full, 0);
                mbar_wait(bar_full + 8, 0);
                if (lane < 2) mbar_arrive(bar_empty + lane * 8);
            }
#pragma unroll 1
            for (int i = 1; rank == 1 && t < NT_RING; i++) {
                const int s0 = (i & 1) * 16;
                mbar_wait(bar_full + s0, (i >> 1) & 1);
                mbar_wait(bar_full + s0 + 8, (i >> 1) & 1);
                if (lane == 0) asm volatile("red.relaxed.gpu.global.add.u32 [%0], 1;\n" ::"l"(&g_flag[t % LN_RING][1][0]) : "memory");
                t = next;
                asm volatile("ld.shared.u32 %0, [%1];\n" : "=r"(next) : "r"(sbase + P1_OFF_TILE + (i & 3) * 16 + 8) : "memory");
                if (lane < 2) mbar_arrive(bar_empty + s0 + lane * 8);
                TRACEW(i, 3);
            }
        } else if (warp == 14) {
            int ph = 0;
#pragma unroll 1
            for (int i = ln0; i < NT_RING; i += LN_STEP, ph ^= 1) {
                mbar_wait(bar_done, ph);
                TRACEW(i / LN_STEP, 0);
                asm volatile("fence.proxy.async.global;\n" ::: "memory");
                if (elect_one()) asm volatile("red.release.gpu.global.add.u32 [%0], 1;\n" ::"l"(&g_flag[ln0 + ph * LN_STEP][0][0]) : "memory");
                __syncwarp();
                TRACEW(i / LN_STEP, 1);
            }
        }
        __syncwarp();
        cluster_sync();
    } else if (warp >= 8) {
        reg_dec<88>();
        asm volatile("barrier.cluster.arrive.relaxed.aligned;\n" ::: "memory");
        {
            const int l8 = lane & 7, row = (warp - 8) * 4 + (lane >> 3), px = (blockIdx.x & 3) * 32 + row;
            uint32_t d[6][4];
#pragma unroll
            for (int j = 0; j < 6; j++) {
                const uint4 t = reinterpret_cast<const uint4*>(dw)[j * 8 + l8];
                d[j][0] = t.x; d[j][1] = t.y; d[j][2] = t.z; d[j][3] = t.w;
            }
            const int n = (px & 64) + perm32(2 * row + ((px >> 5) & 1));
            uint8_t* const dst0 = ring + ln0 * LN_TILE + n * 128 + ((l8 ^ (n & 7)) << 4);
            const uint32_t src = sbase + P1_OFF_X + ((warp - 8) * 8 + (lane >> 3)) * (C_DIM * 2) + l8 * 16;
            int ph = 0;
            asm volatile("barrier.cluster.wait.aligned;\n" ::: "memory");
#pragma unroll 1
            for (int i = ln0; i < NT_RING; i += LN_STEP, ph ^= 1) {
                TRACE(2, i / LN_STEP, 0);
                mbar_wait(bar_xfull, ph);
                uint32_t off;
                asm volatile("ld.shared.u32 %0, [%1];\n" : "=r"(off) : "r"(bar_done + 8) : "memory");
                TRACE(2, i / LN_STEP, 1);
#pragma unroll 1
                for (int ps = 0; ps < 2; ps++) {
                    uint32_t v[6][4];
#pragma unroll
                    for (int j = 0; j < 6; j++)
                        asm volatile("ld.shared.v4.u32 {%0,%1,%2,%3}, [%4];\n"
                                     : "=r"(v[j][0]), "=r"(v[j][1]), "=r"(v[j][2]), "=r"(v[j][3]) : "r"(src + ps * (4 * C_DIM * 2) + j * 128) : "memory");
                    ln_row<P1_PACE>(v, d, bar_pace + (warp - 8) * 8, off, zero, ps == 1 && lane == 0 ? bar_xempty : 0);
                    uint8_t* dst = dst0 + ph * (LN_STEP * LN_TILE) + ps * 4096;
#pragma unroll
                    for (int j = 0; j < 6; j++) *reinterpret_cast<uint4*>(dst + j * 16384) = make_uint4(v[j][0], v[j][1], v[j][2], v[j][3]);
                    TRACE(2, i / LN_STEP, 3 + ps);
                }
                asm volatile("fence.proxy.async.global;\nfence.acq_rel.cta;\n" ::: "memory");
                __syncwarp();
                if (lane == 0) mbar_arrive(bar_done);
                TRACE(2, i / LN_STEP, 5);
                TRACE(2, i / LN_STEP, 2);
            }
        }
        const int gw = (warp - 8) * NUM_CTAS + blockIdx.x;
        bar_sync(3, 160);
        if (gw < 288) {
            const int np = (gw % 12) * 32 + lane, kb = gw / 12;
            const __nv_bfloat16* wc = w2 + (size_t)kb * 64 * C_DIM + perm32(np);
            float bsum = 0.f;
#pragma unroll 2
            for (int c = 0; c < 8; c++) {
                float f[8];
#pragma unroll
                for (int e = 0; e < 8; e++) {
                    f[e] = __bfloat162float(wc[(c * 8 + e) * C_DIM]);
                    bsum = fmaf(__bfloat162float(grn_b[kb * 64 + c * 8 + e]), f[e], bsum);
                    f[e] *= __uint_as_float(__ldcg(&g_ex[kb * 64 + c * 8 + e]) << 23);
                }
                g_w2img[(((kb * 4 + (c >> 1)) * 48 + (np >> 3)) * 2 + (c & 1)) * 8 + (np & 7)] =
                    make_uint4(pack_f16(f[0], f[1]), pack_f16(f[2], f[3]), pack_f16(f[4], f[5]), pack_f16(f[6], f[7]));
            }
            atomicAdd(&g_sums[p1_parity(sbase)][HID + np], bsum);
        }
        __syncwarp();
        cluster_sync();
    } else {
        uint32_t d[6][4];
#pragma unroll
        for (int j = 0; j < 6; j++)
            asm volatile("ld.global.nc.v4.u32 {%0,%1,%2,%3}, [%4];\n" : "=r"(d[j][0]), "=r"(d[j][1]), "=r"(d[j][2]), "=r"(d[j][3])
                         : "l"(reinterpret_cast<const uint4*>(dw) + j * 8 + (lane & 7)) : "memory");
        if (tid == 0) {
            mbar_init(bar_raw, 1);
            mbar_init(bar_raw + 8, 8);
            asm volatile("fence.mbarrier_init.release.cluster;\n" ::: "memory");
            mbar_expect_tx(bar_raw, P1_SLOT);
            for (int i = 0; i < 6; i++)
                bulk_g2s(sbase + i * 16384 + (rank ^ 1) * 8192, x + (size_t)(first * 128 + rank * 64) * C_DIM + i * 4096, 8192, bar_raw);
        }
        if (tid == 32) {
            mbar_init(bar_xfull, 2);
            mbar_init(bar_xempty, 4);
            mbar_init(bar_done, 4);
            asm volatile("fence.mbarrier_init.release.cluster;\n" ::: "memory");
            mbar_expect_tx(bar_xfull, P1_X);
            bulk_g2s(sbase + P1_OFF_X, xsrc, P1_X, bar_xfull);
            asm volatile("st.shared.u32 [%0], 1;\n" ::"r"(bar_done + 8) : "memory");
            mbar_arrive(bar_xfull);
        }
        if (tid == 64) {
            asm volatile("st.shared.v4.u32 [%0], {0, 1, %1, %1};\n" ::"r"(sbase + P1_OFF_TILE), "r"(first + NGRP) : "memory");
            for (int i = 0; i < P1_NST; i++) {
                mbar_init(bar_full + i * 8, 1);
                mbar_init(bar_empty + i * 8, 16 + rank);
                mbar_init(bar_pace + i * 8, 1);
                if (i < 2) mbar_expect_tx(bar_full + i * 8, P1_SLOT / 2);
            }
            asm volatile("fence.mbarrier_init.release.cluster;\n" ::: "memory");
            if (blockIdx.x < 64) (&g_half[0][0])[blockIdx.x] = 0;
            else if (blockIdx.x == 64) g_prog = 0;
        }
        if (tid == 96) {
            for (int i = 0; i < 2; i++) mbar_init(bar_w + i * 8, 1);
            asm volatile("fence.mbarrier_init.release.cluster;\n" ::: "memory");
        }
        __syncwarp();
        asm volatile("barrier.cluster.arrive.relaxed.aligned;\n" ::: "memory");
        if (tid == 96)
            for (int i = 0; i < 2; i++) {
                mbar_expect_tx(bar_w + i * 8, P1_SLOT);
                tma2(sbase + (2 + i) * P1_SLOT, &wmap, cig * 128 + i * 64, 0, bar_w + i * 8);
                tma2(sbase + (2 + i) * P1_SLOT + P1_SLOT / 2, &wmap, cig * 128 + i * 64, 192, bar_w + i * 8);
            }
        __syncwarp();
        reg_inc<200>();
        TRACEW(110 + warp, 1);
        const int wg = warp >> 2, w = warp & 3;
        uint32_t a[24][4];
        {
            const int n = warp * 8 + (lane >> 3), px = (n & 1) * 32 + (n >> 5) * 4 + ((n >> 1) & 1) * 8 + ((n >> 3) & 3);
            if (wg == 1) bar_arrive(1, 256);
            gdc_launch();
            asm volatile("barrier.cluster.wait.aligned;\n" ::: "memory");
#pragma unroll 1
            for (int ps = -1; ps < 2; ps++) {
                if (ps == 0) mbar_wait(bar_raw, 0);
                TRACEW(110 + warp, 2 + (ps == 0));
                uint32_t v[6][4];
#pragma unroll
                for (int j = 0; j < 6; j++) {
                    const uint32_t o = (px + (ps & 1) * 16) * (C_DIM * 2) + j * 128;
                    asm volatile("ld.shared.v4.u32 {%0,%1,%2,%3}, [%4];\n" : "=r"(v[j][0]), "=r"(v[j][1]), "=r"(v[j][2]), "=r"(v[j][3])
                                 : "r"(sbase + (rank ^ 1) * 8192 + (lane & 7) * 16 + o + (o & ~8191u)) : "memory");
                }
                ln_row<false>(v, d, 0, 0, zero, 0);
                const uint32_t p = sbase + (rank * 64 + n + (ps & 1) * 4) * 128 + (((lane ^ n ^ (ps & 1) * 4) & 7) << 4);
#pragma unroll
                for (int j = 0; j < 6; j++)
                    asm volatile("st.shared.v4.u32 [%4], {%0,%1,%2,%3};\n"
                                 ::"r"(v[j][0]), "r"(v[j][1]), "r"(v[j][2]), "r"(v[j][3]), "r"(p + j * 16384) : "memory");
            }
            asm volatile("fence.proxy.async.shared::cta;\n" ::: "memory");
            __syncwarp();
            if (lane == 0) mbar_arrive_cluster(mapa(bar_raw + 8, rank ^ 1));
            bar_arrive(4, 288);
            TRACEW(110 + warp, 4);
            const uint32_t src = sbase + (2 + wg) * P1_SLOT + ((lane >> 4) * 8 + (lane & 7)) * 128 + (((2 * w + ((lane >> 3) & 1)) ^ (lane & 7)) << 4);
            mbar_wait(bar_w + wg * 8, 0);
            TRACEW(110 + warp, 5);
            uint32_t dep = 0;
#pragma unroll
            for (int k = 0; k < 24; k++) {
                ldsm4t(a[k], src + k * 2048);
                dep |= a[k][0];
            }
            __syncwarp();
            if (lane < 4) mbar_arrive_cluster(mapa(bar_empty, lane & 1) + (2 + (lane >> 1)) * 8 + (dep & zero));
        }
        uint32_t ex[2];
#pragma unroll
        for (int r = 0; r < 2; r++) {
            float t = 0.f;
#pragma unroll
            for (int j = 0; j < 6; j++) {
                uint32_t c = bf2_mul(a[4 * j][r], a[4 * j][r]);
#pragma unroll
                for (int k = 1; k < 8; k++) c = bf2_fma(a[4 * j + k / 2][r + (k & 1) * 2], a[4 * j + k / 2][r + (k & 1) * 2], c);
                t += bf_lo(c) + bf_hi(c);
            }
            t += __shfl_xor_sync(0xffffffffu, t, 1);
            t += __shfl_xor_sync(0xffffffffu, t, 2);
            ex[r] = min(max(__float_as_uint(13.9f * __fsqrt_rn(t)) >> 23, 72u), 198u);
            if ((lane & 3) == 0) g_ex[cig * 128 + wg * 64 + w * 16 + r * 8 + (lane >> 2)] = ex[r];
        }
        const uint32_t sc2 = 0x47004700u - ((ex[0] | ex[1] << 16) << 7);
        uint32_t big;
        asm volatile("{\n.reg .pred p;\nsetp.gt.u32 p, %1, 16;\nbar.red.or.pred p, 5, 256, p;\nselp.u32 %0, 1, 0, p;\n}\n"
                     : "=r"(big) : "r"(max(ex[0] - 125u, ex[1] - 125u)) : "memory");
        float fs[2] = {1.f, 1.f};
        if (!__shfl_sync(0xffffffffu, big, 0)) {
#pragma unroll
            for (int k = 0; k < 24; k++)
#pragma unroll
                for (int j = 0; j < 4; j++) a[k][j] = bf2_to_h2(a[k][j]);
            if (warp < 4) p1_consumer<0, false>(a, sc2, fs, sbase, w, lane, zero);
            else p1_consumer<1, false>(a, sc2, fs, sbase, w, lane, zero);
        } else {
#pragma unroll
            for (int r = 0; r < 2; r++) fs[r] = __uint_as_float((268u - ex[r]) << 23);
#pragma unroll
            for (int k = 0; k < 24; k++)
#pragma unroll
                for (int j = 0; j < 4; j++)
                    asm("cvt.rn.f16x2.f32 %0, %1, %2;\n" : "=r"(a[k][j]) : "f"(bf_hi(a[k][j]) * fs[j & 1]), "f"(bf_lo(a[k][j]) * fs[j & 1]));
#pragma unroll
            for (int r = 0; r < 2; r++) fs[r] = __uint_as_float((ex[r] - 14u) << 23);
            if (warp < 4) p1_consumer<0, true>(a, sc2 + 0x38003800u, fs, sbase, w, lane, zero);
            else p1_consumer<1, true>(a, sc2 + 0x38003800u, fs, sbase, w, lane, zero);
        }
        cluster_sync();
        TSTAMP(0, 30);
    }
}

#define P2_NB_ 5
#define P2_NA_ 5
#define P2_DELTA_ 7
#define P2_EXTRA 0
#define P2_HSLEEP 64
#define P2_T0 5
#define P2_TS 11
constexpr int P2_B = 24576, P2_NB = P2_NB_;
constexpr int P2_A = 3072, P2_NA = P2_NA_;
constexpr int P2_XROW = C_DIM * 2;
constexpr int P2_OFF_A = P2_B * P2_NB;
constexpr int P2_OFF_X = P2_OFF_A + 3 * P2_NA * P2_A;
constexpr int P2_XHALF = 32 * P2_XROW + 64;
constexpr int P2_OFF_BIAS = P2_OFF_X + 64 * P2_XROW + 128;
constexpr int P2_OFF_ONES = P2_OFF_BIAS + 48 * 128;
constexpr int P2_OFF_BAR = P2_OFF_ONES + 256;
constexpr int P2_SMEM = P2_OFF_BAR + (2 * P2_NB + 6 * P2_NA + 3) * 8;
constexpr int P2_LAG = 16;
constexpr int P2_NCL = NUM_CTAS / 2, P2_ITEMS = NT128 / P2_NCL, P2_SHARED = NT128 - P2_ITEMS * P2_NCL;
constexpr int P2_POS = P2_LAG * (P2_ITEMS + 2);
constexpr int P2_XC = 8 * P2_XROW;
constexpr uint32_t ACC_UP = 0x3fc23fc2u;
constexpr float ACC_UPF = 1.515625f;
constexpr int P2_DELTA = P2_DELTA_;
__device__ __forceinline__ int p2_tile(int cl, int n) {
    return n == 0 ? NT128 - 1 - cl : n < 0 || n == P2_ITEMS ? NT128 - 1 - P2_NCL - (cl >> 1) : cl + P2_NCL * (n - 1);
}

#define P2_EG 2
__device__ __forceinline__ void p2_epilogue(const uint32_t (&acc0)[48], const uint32_t (&acc1)[48], uint32_t sx, int zero) {
    uint32_t v[2][P2_EG][4];
    auto load = [&](int c, uint32_t a) {
#pragma unroll
        for (int j = 0; j < P2_EG; j++) {
            const int u = c * P2_EG + j;
            asm volatile("ld.shared.v4.u32 {%0,%1,%2,%3}, [%4];\n" : "=r"(v[c & 1][j][0]), "=r"(v[c & 1][j][1]), "=r"(v[c & 1][j][2]), "=r"(v[c & 1][j][3])
                         : "r"(a + (u >> 1) * 64 + (u & 1) * 4 * P2_XROW) : "memory");
        }
    };
    load(0, sx);
#pragma unroll
    for (int c = 0; c < 24 / P2_EG; c++) {
        if (c + 1 < 24 / P2_EG) load(c + 1, sx + (v[c & 1][P2_EG - 1][0] & zero));
#pragma unroll
        for (int j = 0; j < P2_EG; j++) {
            const int u = c * P2_EG + j, i = 8 * ((u >> 1) % 6) + (u & 1);
            const uint32_t (&acc)[48] = u < 12 ? acc0 : acc1;
            uint32_t (&w)[4] = v[c & 1][j];
#pragma unroll
            for (int e = 0; e < 4; e++) w[e] = bf2_fma(pack_bf16(h_lo(acc[i + 2 * e]), h_hi(acc[i + 2 * e])), ACC_UP, w[e]);
            asm volatile("st.shared.v4.u32 [%4], {%0,%1,%2,%3};\n" ::"r"(w[0]), "r"(w[1]), "r"(w[2]), "r"(w[3]),
                         "r"(sx + (u >> 1) * 64 + (u & 1) * 4 * P2_XROW) : "memory");
        }
    }
}

__device__ __forceinline__ void p2_unpack(uint32_t (&u)[4], uint32_t o1, uint32_t o2, uint32_t o3) {
    u[2] = o1 & 0x87ff87ffu;
    u[1] = o2 & 0x87ff87ffu;
    u[3] = o3 & 0x87ff87ffu;
    u[0] = __byte_perm((o2 & 0x78007800u) | ((o3 >> 4) & 0x07800780u), 0, 0x2301) | ((o1 >> 4) & 0x07800780u);
}
__device__ __forceinline__ void p2_epilogue_add(const uint32_t (&acc)[48], uint8_t* o) {
    auto up = [&](int i) { return pack_bf16(h_lo(acc[i / 2]) * ACC_UPF, h_hi(acc[i / 2]) * ACC_UPF); };
#pragma unroll
    for (int t = 0; t < 6; t++)
#pragma unroll
        for (int r = 0; r < 2; r++)
            asm volatile("red.global.add.noftz.v4.bf16x2 [%0], {%1,%2,%3,%4};\n" ::"l"(o + t * 64 + r * 4 * P2_XROW),
                         "r"(up(16 * t + 2 * r)), "r"(up(16 * t + 2 * r + 4)), "r"(up(16 * t + 2 * r + 8)), "r"(up(16 * t + 2 * r + 12)) : "memory");
}

__global__ void __cluster_dims__(2, 1, 1) __launch_bounds__(512, 1)
pass2_kernel(const __nv_bfloat16* __restrict__ x, const __nv_bfloat16* __restrict__ grn_g, __nv_bfloat16* __restrict__ out, int zero) {
    extern __shared__ __align__(1024) uint8_t smem[];
    const uint32_t sbase = smem_u32(smem);
    const uint32_t bar_bfull = sbase + P2_OFF_BAR, bar_bempty = bar_bfull + P2_NB * 8;
    const uint32_t bar_afull = bar_bempty + P2_NB * 8, bar_aempty = bar_afull + 3 * P2_NA * 8;
    const uint32_t bar_xfull = bar_aempty + 3 * P2_NA * 8, bar_oready = bar_xfull + 8, s_pos = bar_xfull + 16;
    int tid;
    asm volatile("mov.u32 %0, %%tid.x;\n" : "=r"(tid));
    const int warp = __shfl_sync(0xffffffffu, tid >> 5, 0), lane = tid & 31;
    const uint32_t rank = cluster_rank();
    const int cl = blockIdx.x >> 1, pair = cl >> 1;
    const int k0 = (4 * pair + (cl & 1) * 32) % 48;
    const int head = pair < P2_SHARED && !(cl & 1), tail = pair < P2_SHARED && (cl & 1);

    TSTAMP(1, 0);
    if (tid == 384) {
        for (int i = 0; i < P2_NB; i++) {
            mbar_init(bar_bfull + i * 8, 1);
            mbar_init(bar_bempty + i * 8, 24);
        }
        for (int i = 0; i < 3 * P2_NA; i++) {
            mbar_init(bar_afull + i * 8, 1);
            mbar_init(bar_aempty + i * 8, 4);
        }
        mbar_init(bar_xfull, 2);
        mbar_init(bar_oready, 4);
        asm volatile("st.shared.u32 [%0], 0;\n" ::"r"(s_pos) : "memory");
        asm volatile("fence.mbarrier_init.release.cluster;\n" ::: "memory");
    }
    __syncthreads();
    cluster_sync_relaxed();

    if (warp >= 12) {
        reg_dec<32>();
        if (warp == 12) {
            const uint8_t* wsrc = reinterpret_cast<const uint8_t*>(g_w2img) + rank * (P2_B / 2);
            int st = 0, ph = 1, kb = k0;
            gdc_wait();
#pragma unroll 1
            for (int p = 0; p < P2_POS; p++) {
                mbar_wait(bar_bempty + st * 8, ph);
                if (elect_one()) {
                    mbar_expect_tx(bar_bfull + st * 8, P2_B);
                    bulk_g2s_mc(sbase + st * P2_B + rank * (P2_B / 2), wsrc + kb * P2_B, P2_B / 2, bar_bfull + st * 8, (uint16_t)3);
                    asm volatile("st.volatile.shared.u32 [%0], %1;\n" ::"r"(s_pos), "r"(p) : "memory");
                    if (rank == 0) asm volatile("red.relaxed.gpu.global.add.u32 [%0], 1;\n" ::"l"(&g_prog) : "memory");
                }
                __syncwarp();
                if (++st == P2_NB) { st = 0; ph ^= 1; }
                if (++kb == 48) kb = 0;
            }
            mbar_wait(bar_bempty + st * 8, ph);
            if (lane == 0) mbar_arrive(bar_bfull + st * 8);
        } else if (warp == 13) {
            const uint8_t* src[3];
            int n[3], left[3], wrap[3];
            uint32_t st[3];
            auto item = [&](int w) {
                int u = k0 + (n[w] < 0 ? 0 : n[w] == P2_ITEMS ? 40 : w * P2_LAG);
                if (u >= 48) u -= 48;
                left[w] = n[w] < 0 || n[w] == P2_ITEMS ? 24 : 48;
                wrap[w] = left[w] - (48 - u);
                src[w] = reinterpret_cast<const uint8_t*>(g_h) + (size_t)p2_tile(cl, n[w]) * (2 * H_TILE) + rank * H_HALF + u * H_STEP;
            };
#pragma unroll
            for (int w = 0; w < 3; w++) {
                n[w] = w == 2 && head ? -1 : w;
                st[w] = 0x80000000u;
                item(w);
            }
            gdc_wait();
#pragma unroll 1
            for (int done = 0; done < 3;) {
                bool idle = true;
#pragma unroll
                for (int w = 0; w < 3; w++) {
                    const uint32_t o = (st[w] & 0xff) + w * P2_NA * 8;
                    if (left[w] >= 0 && mbar_test(bar_aempty + o, st[w] >> 31)) {
                        idle = false;
                        if (left[w] == 0) {
                            if (lane == 0) mbar_arrive(bar_afull + o);
                            left[w] = -1;
                            done++;
                        } else {
                            if (elect_one()) {
                                mbar_expect_tx(bar_afull + o, P2_A);
                                bulk_g2s(sbase + P2_OFF_A + o * (P2_A / 8), src[w], P2_A, bar_afull + o);
                            }
                            __syncwarp();
                            src[w] += H_STEP;
                            st[w] += 8;
                            if ((st[w] & 0xff) == P2_NA * 8) st[w] ^= 0x80000000u | (P2_NA * 8);
                            if (--left[w] == wrap[w]) src[w] -= 48 * H_STEP;
                            if (left[w] == 0 && (n[w] += 3) < P2_ITEMS + tail) item(w);
                        }
                    }
                }
                if (idle) __nanosleep(P2_HSLEEP);
                SAFE_BREAK
            }
        } else if (warp == 14) {
            const uint32_t sx = sbase + P2_OFF_X;
            size_t o = 0;
            auto pace = [&](int target) {
                int v;
                while (true) {
                    asm volatile("ld.volatile.shared.u32 %0, [%1];\n" : "=r"(v) : "r"(s_pos) : "memory");
                    if (v * 16 >= target) break;
                    __nanosleep(100);
                    SAFE_BREAK
                }
            };
#pragma unroll 1
            for (int n = -head; n <= P2_ITEMS; n++) {
                const size_t on = (size_t)(2 * p2_tile(cl, n) + rank) * (64 * C_DIM * 2);
                const bool st = n + head > 0, ld = n < P2_ITEMS;
                if (st) mbar_wait(bar_oready, (n - 1 + head) & 1);
                if (lane == 0) {
                    if (n == 1 && head) {
                        asm volatile("cp.async.bulk.wait_group 0;\nfence.proxy.async.global;\n" ::: "memory");
                        asm volatile("st.release.gpu.global.u32 [%0], 1;\n" ::"l"(&g_half[pair][rank]) : "memory");
                    }
                    if (ld) mbar_expect_tx(bar_xfull, 64 * C_DIM * 2);
                    int t = st && n < P2_ITEMS - 1 ? (P2_LAG * (n + 2) + P2_T0 - 1) * 16 : -1024;
#pragma unroll 1
                    for (int c = 0; st && c < 64 * P2_XROW; c += P2_XC) {
                        pace(t += P2_TS);
                        bulk_s2g(reinterpret_cast<uint8_t*>(out) + o + c, sx + c + (c >= 32 * P2_XROW ? 64 : 0), P2_XC);
                    }
                    asm volatile("cp.async.bulk.commit_group;\ncp.async.bulk.wait_group.read 0;\n" ::: "memory");
#pragma unroll 1
                    for (int c = 0; ld && c < 64 * P2_XROW; c += P2_XC) {
                        pace(t += P2_TS);
                        bulk_g2s(sx + c + (c >= 32 * P2_XROW ? 64 : 0), reinterpret_cast<const uint8_t*>(x) + on + c, P2_XC, bar_xfull);
                    }
                    if (rank == 0 && n > 0 && n < P2_ITEMS - 2)
                        flag_wait<false>(&g_prog, P2_NCL * (P2_LAG * (n + 3) + P2_EXTRA) + (tail ? P2_SHARED - P2_NCL : P2_SHARED) * P2_DELTA);
                    if (ld) mbar_arrive(bar_xfull);
                }
                __syncwarp();
                o = on;
            }
            asm volatile("cp.async.bulk.wait_group 0;\n" ::: "memory");
        }
        __syncwarp();
        cluster_sync();
    } else {
        reg_inc<160>();
        const int wg = warp >> 2, w = warp & 3, g = lane >> 2, q = lane & 3;
        const uint32_t sx = sbase + P2_OFF_X + (g & 1) * P2_XHALF + (w * 8 + (g >> 1)) * P2_XROW + q * 16;
        const uint32_t af = bar_afull + wg * P2_NA * 8, ae = bar_aempty + wg * P2_NA * 8;
        const uint32_t s_a = sbase + P2_OFF_A - bar_afull * (P2_A / 8) + (lane >> 3) * 512 + (lane & 7) * 64 +
                             ((w ^ ((lane & 7) >> 1)) << 4);
        uint32_t acc0[48], acc1[48];
        uint4 a0[2], a1[2];
        int st = 0, ph = 0;

        {
            float* s_red = reinterpret_cast<float*>(smem + P2_OFF_ONES);
            float gx[4], part = 0.f;
            __nv_bfloat16 gg[4];
#pragma unroll
            for (int i = 0; i < 4; i++) gg[i] = grn_g[tid + 384 * i];
            TSTAMP(1, 27);
            gdc_wait();
            TSTAMP(1, 1);
            if (blockIdx.x == 120 && tid < (LN_RING + 3) * 2) (&g_flag[0][0][0])[tid * 8] = 0;
            if (blockIdx.x == 121 && tid == 0) g_epoch++;
#pragma unroll
            for (int i = 0; i < 4; i++) gx[i] = __ldcg(&g_sums[0][tid + 384 * i]) + __ldcg(&g_sums[1][tid + 384 * i]);
            const float bias = (__ldcg(&g_sums[0][HID + tid]) + __ldcg(&g_sums[1][HID + tid])) * (1.0f / ACC_UPF);
#pragma unroll
            for (int i = 0; i < 4; i++) {
                gx[i] = sqrtf(gx[i] * (HSCALE * HSCALE) + 1e-6f);
                part += gx[i];
            }
#pragma unroll
            for (int o = 16; o > 0; o >>= 1) part += __shfl_xor_sync(0xffffffffu, part, o);
            TSTAMP(1, 26);
            if (lane == 0) s_red[warp] = part;
            bar_sync(1, 384);
            float tot = 0.f;
#pragma unroll
            for (int i = 0; i < 12; i++) tot += s_red[i];
            const float inv = 1.0f / (tot * (1.0f / HID) + 1e-6f);
            bar_sync(1, 384);
            *reinterpret_cast<uint2*>(smem + P2_OFF_BIAS + tid * 16) = make_uint2(pack_f16(bias, bias - h_lo(pack_f16(bias, 0.f))), 0u);
#pragma unroll
            for (int i = 0; i < 4; i++) {
                const int k = tid + 384 * i;
                *reinterpret_cast<__nv_bfloat16*>(smem + P2_OFF_BIAS + ((k >> 4) * 4 + ((k >> 1) & 3)) * 16 + 8 + ((k >> 3) & 1) * 4 + (k & 1) * 2) =
                    __float2bfloat16(fmaf(__bfloat162float(gg[i]) * (gx[i] * inv), HSCALE / ACC_UPF, HSCALE / ACC_UPF - 1.0f));
            }
            TSTAMP(1, 25);
            if (tid < 16) reinterpret_cast<uint4*>(smem + P2_OFF_ONES)[tid] = make_uint4(tid < 8 ? 0x3c003c00u : 0u, 0u, 0u, 0u);
            asm volatile("fence.proxy.async.shared::cta;\n" ::: "memory");
            bar_sync(1, 384);
        }
        TSTAMP(1, 28);
        const uint32_t s_t = sbase + P2_OFF_BIAS + q * 16 + 8;
        const int first = wg == 2 && head ? 0 : wg * P2_LAG;
        int kt = (k0 + first) % 48;

        int pos = first;
        const int who = __shfl_sync(0xffffffffu, lane == 2 ? 0 : lane < 2 ? 1 : 2, lane);
        const uint32_t rel0 = who ? mapa(bar_bempty, lane & 1) : mapa(ae, rank), rel1 = rel0 + (who ? P2_NB : P2_NA) * 8;
        uint32_t rel = rel1 - 8;
        auto next_rel = [&](bool go) {
            if (go) rel += 8;
            if (rel == rel1) rel = rel0;
        };
        auto release_b = [&]() {
            next_rel(who == 1);
            if (who == 1) mbar_arrive_cluster(rel);
        };
        auto skip = [&](int cnt) {
#pragma unroll 1
            for (int p = 0; p < cnt; p++) {
                mbar_wait(bar_bfull + st * 8, ph);
                release_b();
                if (++st == P2_NB) { st = 0; ph ^= 1; }
            }
        };
        auto publish = [&]() {
            asm volatile("fence.proxy.async.shared::cta;\n" ::: "memory");
            __syncwarp();
            if (who == 0) mbar_arrive(bar_oready);
        };
        bool ok_a, pend = false;
        uint32_t abar = af, pa = 0;
        auto fetch = [&](uint4 (&a)[2]) {
            uint32_t u0[4], u1[4];
            const uint32_t src = s_a + abar * (P2_A / 8);
            abar += 8;
            if (abar == af + P2_NA * 8) { abar = af; pa ^= 0x80000000u; }
            uint2 t0, t1;
            asm volatile("ld.shared.v2.u32 {%0,%1}, [%2];\n" : "=r"(t0.x), "=r"(t0.y) : "r"(s_t + kt * 128) : "memory");
            asm volatile("ld.shared.v2.u32 {%0,%1}, [%2];\n" : "=r"(t1.x), "=r"(t1.y) : "r"(s_t + kt * 128 + 64) : "memory");
            const bool ok_b = mbar_test(bar_bfull + st * 8, ph);
            ok_a = mbar_test(abar, pa >> 31);
            uint32_t o[6];
            asm volatile("ldmatrix.sync.aligned.m8n8.x4.trans.shared.b16 {%0,%1,%2,%3}, [%4];\n"
                         : "=r"(o[0]), "=r"(o[1]), "=r"(o[2]), "=r"(o[3]) : "r"(src) : "memory");
            asm volatile("ldmatrix.sync.aligned.m8n8.x2.trans.shared.b16 {%0,%1}, [%2];\n"
                         : "=r"(o[4]), "=r"(o[5]) : "r"(src + 2048) : "memory");
            p2_unpack(u0, o[0], o[1], o[2]);
            p2_unpack(u1, o[3], o[4], o[5]);
            auto grn = [&](uint32_t u, uint32_t t) { u = bf2_fma(u, t, u); return (u & 0x0fff0fffu) * 7u + u; };
            a[0] = make_uint4(grn(u0[0], t0.x), grn(u0[1], t0.x), grn(u0[2], t0.y), grn(u0[3], t0.y));
            a[1] = make_uint4(grn(u1[0], t1.x), grn(u1[1], t1.x), grn(u1[2], t1.y), grn(u1[3], t1.y));
            if (++kt == 48) kt = 0;
            if (!ok_b) mbar_wait(bar_bfull + st * 8, ph);
        };
        auto step = [&](const uint4 (&a)[2], uint4 (&an)[2], int thr) {
            TR2(0);
            const uint64_t db = make_desc(sbase + st * P2_B, 128, 256);
            wg_fence();
            mma_rs_n192(acc0, a[0], db);
            mma_rs_n192(acc1, a[0], db + 384);
            mma_rs_n192(acc0, a[1], db + 768);
            mma_rs_n192(acc1, a[1], db + 768 + 384);
            wg_commit();
            next_rel(who < thr);
            if (++st == P2_NB) { st = 0; ph ^= 1; }
            wg_wait<1>();
            if (!ok_a) {
                if (who < thr) mbar_arrive_cluster(rel);
                if (thr == 1 && pend) publish();
                thr = 0;
                mbar_wait(abar, pa >> 31);
            }
            if (who < thr) mbar_arrive_cluster(rel);
            fetch(an);
            pos++;
        };
        skip(first);
        mbar_wait(af, 0);
        fetch(a0);
#pragma unroll 1
        for (int n = wg == 2 && head ? -1 : wg;; n += 3) {
            TSTAMP(1, 2 + n);
            const uint64_t ones = make_desc(sbase + P2_OFF_ONES + (n == P2_ITEMS ? 128 : 0), n == P2_ITEMS ? 0 : 128, 0);
            wg_fence();
            mma_ss_n192_init(acc0, ones, make_desc(sbase + P2_OFF_BIAS, 0, 128));
            mma_ss_n192_init(acc1, ones, make_desc(sbase + P2_OFF_BIAS + 3072, 0, 128));
            wg_commit();
            const int p0 = n < 0 || n == P2_ITEMS ? 12 : 0;
            const bool more = n + 3 < P2_ITEMS + tail;
#pragma unroll 1
            for (int p = p0; p < 24; p++) {
                step(a0, a1, p == p0 ? 1 : 2);
                step(a1, a0, 2);
            }
            if (n == P2_ITEMS) {
                flag_wait<true>(&g_half[pair][rank], 1);
                wg_wait<0>();
                release_b();
                uint8_t* o = reinterpret_cast<uint8_t*>(out) + (size_t)((2 * p2_tile(cl, -1) + rank) * 64 + (g & 1) * 32 + w * 8 + (g >> 1)) * P2_XROW + q * 16;
                p2_epilogue_add(acc0, o);
                p2_epilogue_add(acc1, o + 384);
                break;
            }
            mbar_wait(bar_xfull, (n + head) & 1);
            TR2(5);
            wg_wait<0>();
            TR2(6);
            release_b();
            __syncwarp();
            p2_epilogue(acc0, acc1, sx, zero);
            if (!more) {
                publish();
                skip(P2_POS - P2_LAG * (n + 3));
                break;
            }
            pend = true;
            ok_a = false;
            if (n < 0 || n + 3 == P2_ITEMS) {
                publish();
                pend = false;
                skip(8);
                if (abar == af) { abar = af + P2_NA * 8; pa ^= 0x80000000u; }
                abar -= 8;
                kt += 7;
                if (kt >= 48) kt -= 48;
                fetch(a0);
                pos += 8;
            }
        }
        TSTAMP(1, 29);
        cluster_sync();
        TSTAMP(1, 30);
    }
}

}

extern "C" void kernel_launch(void* const* d_in, const int* in_sizes, int n_in, void* d_out, int out_size) {
    const __nv_bfloat16* x = (const __nv_bfloat16*)d_in[0];
    const __nv_bfloat16* dw = (const __nv_bfloat16*)d_in[1];
    const __nv_bfloat16* w1 = (const __nv_bfloat16*)d_in[2];
    const __nv_bfloat16* w2 = (const __nv_bfloat16*)d_in[3];
    const __nv_bfloat16* grn_g = (const __nv_bfloat16*)d_in[4];
    const __nv_bfloat16* grn_b = (const __nv_bfloat16*)d_in[5];
    __nv_bfloat16* out = (__nv_bfloat16*)d_out;

    cudaFuncSetAttribute(pass1_kernel, cudaFuncAttributeMaxDynamicSharedMemorySize, P1_SMEM);
    cudaFuncSetAttribute(pass2_kernel, cudaFuncAttributeMaxDynamicSharedMemorySize, P2_SMEM);

    typedef CUresult (*EncodeFn)(CUtensorMap*, CUtensorMapDataType, cuuint32_t, void*, const cuuint64_t*, const cuuint64_t*,
                                 const cuuint32_t*, const cuuint32_t*, CUtensorMapInterleave, CUtensorMapSwizzle,
                                 CUtensorMapL2promotion, CUtensorMapFloatOOBfill);
    static EncodeFn encode = nullptr;
    if (!encode) {
        cudaDriverEntryPointQueryResult qres;
        cudaGetDriverEntryPoint("cuTensorMapEncodeTiled", (void**)&encode, cudaEnableDefault, &qres);
    }
    CUtensorMap wmap;
    const cuuint64_t gdim[2] = {HID, C_DIM};
    const cuuint64_t gstr[1] = {HID * 2};
    const cuuint32_t box[2] = {64, 192}, estr[2] = {1, 1};
    CUresult er = encode(&wmap, CU_TENSOR_MAP_DATA_TYPE_BFLOAT16, 2, (void*)w1, gdim, gstr, box, estr, CU_TENSOR_MAP_INTERLEAVE_NONE,
           CU_TENSOR_MAP_SWIZZLE_128B, CU_TENSOR_MAP_L2_PROMOTION_L2_128B, CU_TENSOR_MAP_FLOAT_OOB_FILL_NONE);
    if (er != CUDA_SUCCESS) printf("tensor map encode failed %d\n", (int)er);

    pass1_kernel<<<NUM_CTAS, 512, P1_SMEM>>>(wmap, x, dw, w2, grn_b, 0);

    cudaLaunchAttribute attr[1];
    attr[0].id = cudaLaunchAttributeProgrammaticStreamSerialization;
    attr[0].val.programmaticStreamSerializationAllowed = 1;
    cudaLaunchConfig_t cfg = {};
    cfg.gridDim = dim3(NUM_CTAS);
    cfg.stream = 0;
    cfg.attrs = attr;
    cfg.numAttrs = 1;
    cfg.blockDim = dim3(512);
    cfg.dynamicSmemBytes = P2_SMEM;
    cudaLaunchKernelEx(&cfg, pass2_kernel, x, grn_g, out, 0);
}
```

```cpp
#include <cuda.h>
#include <cuda_runtime.h>
#include <cuda_bf16.h>
#include <stdint.h>
#include <stdio.h>

namespace {

constexpr int M_TOTAL = 384 * 384;
constexpr int C_DIM   = 384;
constexpr int HID     = 1536;
constexpr int NT128   = M_TOTAL / 128;
constexpr int NUM_CTAS = 132;

constexpr int NGRP = 11, GRP_CTAS = 12;
constexpr int LN_STEP = NUM_CTAS / 4, LN_RING = 2 * LN_STEP;
constexpr int NT_RING = NT128 - NGRP;
constexpr int LN_TILE = 128 * C_DIM * 2;
constexpr int H_TILE = 64 * HID * 3 / 2;
constexpr int H_HALF = 3072, H_STEP = 6144;

__device__ __align__(1024) uint4 g_h[(size_t)M_TOTAL * HID * 3 / 32];
__device__ __align__(1024) uint4 g_ln[LN_RING * LN_TILE / 16];
__device__ __align__(1024) uint4 g_w2img[HID * C_DIM * 2 / 16];
__device__ __align__(16) float g_sums[2][HID + 512];
__device__ unsigned g_ex[HID];
__device__ unsigned g_epoch;
__device__ __align__(128) unsigned g_prog;
__device__ __align__(128) unsigned g_half[32][2];
__device__ unsigned g_flag[LN_RING + 3][2][8];
#define TSTAMP(k, i)
#define TRACE(wg, pos, i)
#define TRACEW(pos, i)

#define TR2(i)
#define TR2P(pos, i)
__host__ __device__ __forceinline__ int perm32(int n) {
    return (n & ~31) | (((n >> 1) & 3) << 3) | (((n >> 3) & 3) << 1) | (n & 1);
}

__device__ __forceinline__ uint32_t smem_u32(const void* p) { return (uint32_t)__cvta_generic_to_shared(p); }

__device__ __forceinline__ void mbar_init(uint32_t bar, uint32_t count) {
    asm volatile("mbarrier.init.shared::cta.b64 [%0], %1;\n" ::"r"(bar), "r"(count) : "memory");
}
__device__ __forceinline__ void mbar_expect_tx(uint32_t bar, uint32_t bytes) {
    asm volatile("mbarrier.arrive.expect_tx.shared::cta.b64 _, [%0], %1;\n" ::"r"(bar), "r"(bytes) : "memory");
}
__device__ __forceinline__ void mbar_arrive(uint32_t bar) {
    asm volatile("mbarrier.arrive.shared::cta.b64 _, [%0];\n" ::"r"(bar) : "memory");
}
__device__ __forceinline__ void mbar_arrive_cluster(uint32_t bar_cluster_addr) {
    asm volatile("mbarrier.arrive.shared::cluster.b64 _, [%0];\n" ::"r"(bar_cluster_addr) : "memory");
}
#define SAFE_BREAK
__device__ __forceinline__ void mbar_wait(uint32_t bar, uint32_t parity) {
    asm volatile(
        "{\n"
        ".reg .pred p;\n"
        "LAB_WAIT:\n"
        "mbarrier.try_wait.parity.shared::cta.b64 p, [%0], %1;\n"
        "@!p bra LAB_WAIT;\n"
        "}\n" ::"r"(bar), "r"(parity) : "memory");
}
__device__ __forceinline__ bool mbar_test(uint32_t bar, uint32_t parity) {
    uint32_t ok;
    asm volatile("{\n.reg .pred p;\n"
                 "mbarrier.test_wait.parity.shared::cta.b64 p, [%1], %2;\n"
                 "selp.u32 %0, 1, 0, p;\n}\n" : "=r"(ok) : "r"(bar), "r"(parity) : "memory");
    return ok != 0;
}
__device__ __forceinline__ uint32_t mapa(uint32_t addr, uint32_t rank) {
    uint32_t r;
    asm volatile("mapa.shared::cluster.u32 %0, %1, %2;\n" : "=r"(r) : "r"(addr), "r"(rank));
    return r;
}
__device__ __forceinline__ void bulk_g2s(uint32_t dst, const void* src, uint32_t bytes, uint32_t bar) {
    asm volatile("cp.async.bulk.shared::cluster.global.mbarrier::complete_tx::bytes [%0], [%1], %2, [%3];\n"
                 ::"r"(dst), "l"(src), "r"(bytes), "r"(bar) : "memory");
}
__device__ __forceinline__ void bulk_g2s_mc(uint32_t dst, const void* src, uint32_t bytes, uint32_t bar, uint16_t mask) {
    asm volatile("cp.async.bulk.shared::cluster.global.mbarrier::complete_tx::bytes.multicast::cluster [%0], [%1], %2, [%3], %4;\n"
                 ::"r"(dst), "l"(src), "r"(bytes), "r"(bar), "h"(mask) : "memory");
}
__device__ __forceinline__ void tma2(uint32_t dst, const CUtensorMap* map, int c0, int c1, uint32_t bar) {
    asm volatile("cp.async.bulk.tensor.2d.shared::cluster.global.tile.mbarrier::complete_tx::bytes [%0], [%1, {%2, %3}], [%4];\n"
                 ::"r"(dst), "l"(map), "r"(c0), "r"(c1), "r"(bar) : "memory");
}
template <bool ACQ>
__device__ __forceinline__ uint32_t flag_wait(const unsigned* p, unsigned target) {
    unsigned v, n = 0;
    do {
        if (ACQ) asm volatile("ld.acquire.gpu.global.u32 %0, [%1];\n" : "=r"(v) : "l"(p) : "memory");
        else asm volatile("ld.relaxed.gpu.global.u32 %0, [%1];\n" : "=r"(v) : "l"(p) : "memory");
        n++;
    } while (v < target);
    return n == 1;
}
__device__ __forceinline__ void ldsm4t(uint32_t (&r)[4], uint32_t addr) {
    asm volatile("ldmatrix.sync.aligned.m8n8.x4.trans.shared.b16 {%0,%1,%2,%3}, [%4];\n"
                 : "=r"(r[0]), "=r"(r[1]), "=r"(r[2]), "=r"(r[3]) : "r"(addr) : "memory");
}
__device__ __forceinline__ void bulk_s2g(void* dst, uint32_t src, uint32_t bytes) {
    asm volatile("cp.async.bulk.global.shared::cta.bulk_group [%0], [%1], %2;\n" ::"l"(dst), "r"(src), "r"(bytes) : "memory");
}
__device__ __forceinline__ void cluster_sync() {
    asm volatile("barrier.cluster.arrive.aligned;\nbarrier.cluster.wait.aligned;\n" ::: "memory");
}
__device__ __forceinline__ void cluster_sync_relaxed() {
    asm volatile("barrier.cluster.arrive.relaxed.aligned;\nbarrier.cluster.wait.aligned;\n" ::: "memory");
}
__device__ __forceinline__ void gdc_wait() { asm volatile("griddepcontrol.wait;\n" ::: "memory"); }
__device__ __forceinline__ void gdc_launch() { asm volatile("griddepcontrol.launch_dependents;\n" ::: "memory"); }
__device__ __forceinline__ uint32_t cluster_rank() {
    uint32_t r;
    asm volatile("mov.u32 %0, %%cluster_ctarank;\n" : "=r"(r));
    return r;
}
__device__ __forceinline__ bool elect_one() {
    uint32_t pred;
    asm volatile("{\n.reg .pred p;\nelect.sync _|p, 0xffffffff;\nselp.u32 %0, 1, 0, p;\n}\n" : "=r"(pred));
    return pred != 0;
}
__device__ __forceinline__ void wg_fence() { asm volatile("wgmma.fence.sync.aligned;\n" ::: "memory"); }
__device__ __forceinline__ void wg_commit() { asm volatile("wgmma.commit_group.sync.aligned;\n" ::: "memory"); }
template <int N> __device__ __forceinline__ void wg_wait() {
    asm volatile("wgmma.wait_group.sync.aligned %0;\n" ::"n"(N) : "memory");
}
template <int R> __device__ __forceinline__ void reg_inc() { asm volatile("setmaxnreg.inc.sync.aligned.u32 %0;\n" ::"n"(R)); }
template <int R> __device__ __forceinline__ void reg_dec() { asm volatile("setmaxnreg.dec.sync.aligned.u32 %0;\n" ::"n"(R)); }
__device__ __forceinline__ void bar_sync(int id, int n) { asm volatile("bar.sync %0, %1;\n" ::"r"(id), "r"(n) : "memory"); }
__device__ __forceinline__ void bar_arrive(int id, int n) { asm volatile("bar.arrive %0, %1;\n" ::"r"(id), "r"(n) : "memory"); }

__device__ __forceinline__ uint64_t make_desc(uint32_t saddr, uint32_t lbo, uint32_t sbo) {
    return (uint64_t)((saddr & 0x3FFFF) >> 4) | ((uint64_t)(lbo >> 4) << 16) | ((uint64_t)(sbo >> 4) << 32);
}

__device__ __forceinline__ void stg128_cs(void* p, uint32_t a, uint32_t b, uint32_t c, uint32_t d) {
    asm volatile("st.global.cs.v4.u32 [%0], {%1,%2,%3,%4};\n" ::"l"(p), "r"(a), "r"(b), "r"(c), "r"(d) : "memory");
}
__device__ __forceinline__ uint32_t pack_bf16(float lo, float hi) {
    uint32_t r;
    asm("cvt.rn.bf16x2.f32 %0, %1, %2;\n" : "=r"(r) : "f"(hi), "f"(lo));
    return r;
}
__device__ __forceinline__ float bf_lo(uint32_t v) { return __uint_as_float(v << 16); }
__device__ __forceinline__ float bf_hi(uint32_t v) { return __uint_as_float(v & 0xffff0000u); }
__device__ __forceinline__ uint32_t bf2_mul(uint32_t a, uint32_t b) {
    uint32_t r;
    asm("mul.rn.bf16x2 %0, %1, %2;\n" : "=r"(r) : "r"(a), "r"(b));
    return r;
}
__device__ __forceinline__ uint32_t bf2_fma(uint32_t a, uint32_t b, uint32_t c) {
    uint32_t r;
    asm("fma.rn.bf16x2 %0, %1, %2, %3;\n" : "=r"(r) : "r"(a), "r"(b), "r"(c));
    return r;
}
__device__ __forceinline__ uint32_t bf2_add(uint32_t a, uint32_t b) {
    uint32_t r;
    asm("add.rn.bf16x2 %0, %1, %2;\n" : "=r"(r) : "r"(a), "r"(b));
    return r;
}
constexpr float KAPPA = 0.3292034911525734f;
constexpr float GELU_C = 2.423681954311584f;
constexpr float HSCALE = 1.0f / (2.0f * KAPPA);
__device__ __forceinline__ void sched_break(int zero) {
    asm volatile("{\n.reg .pred p;\nsetp.ne.s32 p, %0, 0;\nSB_LOOP:\n@p nanosleep.u32 1;\n@p bra SB_LOOP;\n}\n" ::"r"(zero));
}

#define ACC8(d, o) "+f"(d[o + 0]), "+f"(d[o + 1]), "+f"(d[o + 2]), "+f"(d[o + 3]), "+f"(d[o + 4]), "+f"(d[o + 5]), "+f"(d[o + 6]), "+f"(d[o + 7])

#define ACCR8(d, o) "+r"(d[o + 0]), "+r"(d[o + 1]), "+r"(d[o + 2]), "+r"(d[o + 3]), "+r"(d[o + 4]), "+r"(d[o + 5]), "+r"(d[o + 6]), "+r"(d[o + 7])
__device__ __forceinline__ void mma_rs_n128(uint32_t (&d)[32], const uint32_t (&a)[4], uint64_t desc, int scale_d) {
    asm volatile(
        "{\n.reg .pred p;\nsetp.ne.b32 p, %37, 0;\n"
        "wgmma.mma_async.sync.aligned.m64n128k16.f16.f16.f16 "
        "{%0,%1,%2,%3,%4,%5,%6,%7,%8,%9,%10,%11,%12,%13,%14,%15,"
        "%16,%17,%18,%19,%20,%21,%22,%23,%24,%25,%26,%27,%28,%29,%30,%31},"
        "{%32,%33,%34,%35}, %36, p, 1, 1, 0;\n}\n"
        : ACCR8(d, 0), ACCR8(d, 8), ACCR8(d, 16), ACCR8(d, 24)
        : "r"(a[0]), "r"(a[1]), "r"(a[2]), "r"(a[3]), "l"(desc), "r"(scale_d));
}
__device__ __forceinline__ uint32_t bf2_to_h2(uint32_t v) {
    v = bf2_mul(v, 0x07800780u);
    return (v & 0x0fff0fffu) * 7u + v;
}
__device__ __forceinline__ float h_lo(uint32_t v) {
    float r;
    asm("{\n.reg .b16 l, h;\nmov.b32 {l, h}, %1;\ncvt.f32.f16 %0, l;\n}\n" : "=f"(r) : "r"(v));
    return r;
}
__device__ __forceinline__ float h_hi(uint32_t v) {
    float r;
    asm("{\n.reg .b16 l, h;\nmov.b32 {l, h}, %1;\ncvt.f32.f16 %0, h;\n}\n" : "=f"(r) : "r"(v));
    return r;
}

__device__ __forceinline__ void mma_rs_n192(uint32_t (&d)[48], const uint4& a, uint64_t db) {
    asm volatile(
        "{\n.reg .pred p;\nsetp.ne.b32 p, %53, 0;\n"
        "wgmma.mma_async.sync.aligned.m64n192k16.f16.f16.f16 "
        "{%0,%1,%2,%3,%4,%5,%6,%7,%8,%9,%10,%11,%12,%13,%14,%15,"
        "%16,%17,%18,%19,%20,%21,%22,%23,%24,%25,%26,%27,%28,%29,%30,%31,"
        "%32,%33,%34,%35,%36,%37,%38,%39,%40,%41,%42,%43,%44,%45,%46,%47},"
        "{%48,%49,%50,%51}, %52, p, 1, 1, 0;\n}\n"
        : ACCR8(d, 0), ACCR8(d, 8), ACCR8(d, 16), ACCR8(d, 24), ACCR8(d, 32), ACCR8(d, 40)
        : "r"(a.x), "r"(a.y), "r"(a.z), "r"(a.w), "l"(db), "r"(1));
}

__device__ __forceinline__ void mma_ss_n192_init(uint32_t (&d)[48], uint64_t da, uint64_t db) {
    asm volatile(
        "{\n.reg .pred p;\nsetp.ne.b32 p, %50, 0;\n"
        "wgmma.mma_async.sync.aligned.m64n192k16.f16.f16.f16 "
        "{%0,%1,%2,%3,%4,%5,%6,%7,%8,%9,%10,%11,%12,%13,%14,%15,"
        "%16,%17,%18,%19,%20,%21,%22,%23,%24,%25,%26,%27,%28,%29,%30,%31,"
        "%32,%33,%34,%35,%36,%37,%38,%39,%40,%41,%42,%43,%44,%45,%46,%47},"
        "%48, %49, p, 1, 1, 0, 0;\n}\n"
        : ACCR8(d, 0), ACCR8(d, 8), ACCR8(d, 16), ACCR8(d, 24), ACCR8(d, 32), ACCR8(d, 40)
        : "l"(da), "l"(db), "r"(0));
}
__device__ __forceinline__ uint32_t pack_f16(float lo, float hi) {
    uint32_t r;
    asm("cvt.rn.f16x2.f32 %0, %1, %2;\n" : "=r"(r) : "f"(hi), "f"(lo));
    return r;
}

#define P1_ARR 23
#define P1_PACE true
constexpr int P1_SLOT = LN_TILE / 2, P1_NST = 4;
constexpr int P1_X = 32 * C_DIM * 2;
constexpr int P1_OFF_X = P1_SLOT * P1_NST;
constexpr int P1_OFF_BAR = P1_OFF_X + P1_X;
constexpr int P1_OFF_TILE = P1_OFF_BAR + (2 * P1_NST + 2 + 4 + 4) * 8;
constexpr int P1_OFF_RAW = P1_OFF_TILE + 64;
constexpr int P1_SMEM = P1_OFF_RAW + 16;

__device__ __forceinline__ float rsqrt_fast(float x) {
    float r;
    asm("rsqrt.approx.ftz.f32 %0, %1;\n" : "=f"(r) : "f"(x));
    return r;
}
__device__ __forceinline__ float row_sum(const uint32_t (&c)[4]) {
    const uint32_t u = bf2_add(bf2_add(c[0], c[1]), bf2_add(c[2], c[3]));
    float s = bf_lo(u) + bf_hi(u);
#pragma unroll
    for (int o = 1; o < 8; o <<= 1) s += __shfl_xor_sync(0xffffffffu, s, o);
    return s;
}
__device__ __forceinline__ uint32_t pace(uint32_t bar, uint32_t off, uint32_t val, uint32_t after, int zero) {
    asm volatile(
        "{\n.reg .pred p;\n.reg .b32 par;\n"
        "lop3.b32 par, %4, %2, %3, 0xea;\n"
        "mbarrier.test_wait.parity.shared::cta.b64 p, [%1], par;\n"
        "selp.u32 par, 1, 0, p;\n"
        "mbarrier.try_wait.parity.shared::cta.b64 p, [%1], par, 1000;\n"
        "@p or.b32 %0, %0, %2;\n"
        "}\n" : "+r"(val) : "r"(bar), "r"(zero), "r"(off), "r"(after));
    return val;
}
template <bool PACE>
__device__ __forceinline__ void ln_row(uint32_t (&v)[6][4], const uint32_t (&d)[6][4], uint32_t bar, uint32_t off, int zero,
                                       uint32_t bar_read) {
    uint32_t c[4];
#pragma unroll
    for (int i = 0; i < 6; i++)
#pragma unroll
        for (int k = 0; k < 4; k++) c[k] = bf2_fma(v[i][k], d[i][k], i ? c[k] : 0);
    const float inv = 1.0f / C_DIM;
    const float m = row_sum(c) * inv;
    uint32_t nm = pack_bf16(-m, -m);
    const float e = m + bf_lo(nm);
    if (bar_read) mbar_arrive(bar_read + (nm & zero));
    if (PACE) nm = pace(bar, off, nm, nm, zero);
#pragma unroll
    for (int i = 0; i < 6; i++) {
#pragma unroll
        for (int k = 0; k < 4; k++) {
            v[i][k] = bf2_fma(v[i][k], d[i][k], nm);
            c[k] = i ? bf2_fma(v[i][k], v[i][k], c[k]) : bf2_mul(v[i][k], v[i][k]);
        }
    }
    const float r = KAPPA * rsqrt_fast(fmaxf(fmaf(-e, e, row_sum(c) * inv), 0.f) + 1e-5f);
    uint32_t rs = pack_bf16(r, r);
    const uint32_t sh = pack_bf16(-e * r, -e * r);
    if (PACE) rs = pace(bar, off, rs, sh, zero);
#pragma unroll
    for (int i = 0; i < 6; i++)
#pragma unroll
        for (int k = 0; k < 4; k++) v[i][k] = bf2_to_h2(bf2_fma(v[i][k], rs, sh));
}

__device__ __forceinline__ float gelu_s(float y) {
    float u = y * fmaf(y, y, GELU_C);
    float t;
    asm volatile("tanh.approx.f32 %0, %1;\n" : "=f"(t) : "f"(u));
    return fmaf(y, t, y);
}
__device__ __forceinline__ constexpr int p1_reg(int c, int u) { return 16 * (c >> 1) + 4 * (u >> 1) + 2 * (c & 1) + (u & 1); }
template <bool BIG>
__device__ __forceinline__ void p1_pack(int c, uint32_t (&p)[4], uint32_t (&dd)[4], uint32_t (&sq)[4], uint32_t sc2) {
    uint32_t& s = sq[(c >> 2) * 2 + (c & 1)];
    s = (c & 2) ? bf2_fma(p[0], p[0], s) : bf2_mul(p[0], p[0]);
    s = bf2_fma(p[3], p[3], bf2_fma(p[2], p[2], bf2_fma(p[1], p[1], s)));
#pragma unroll
    for (int u = 0; u < 4; u++) {
        uint32_t v;
        if (c & 1) asm("{\n.reg .b16 l, h;\n.reg .b32 f;\nmov.b32 {l, h}, %2;\nmov.b32 f, {h, h};\nmul.rn.bf16x2 %0, %1, f;\n}\n" : "=r"(v) : "r"(p[u]), "r"(sc2));
        else asm("{\n.reg .b16 l, h;\n.reg .b32 f;\nmov.b32 {l, h}, %2;\nmov.b32 f, {l, l};\nmul.rn.bf16x2 %0, %1, f;\n}\n" : "=r"(v) : "r"(p[u]), "r"(sc2));
        if (BIG) v = bf2_mul(v, 0x07800780u);
        if ((c & 3) == 0) dd[u] = v;
        else {
            uint32_t n = dd[u];
            if ((c & 3) == 1) { n <<= 4; dd[u] = __byte_perm(dd[u], 0, 0x2301); }
            if ((c & 3) == 2) dd[u] <<= 4;
            asm("lop3.b32 %0, %1, %2, 0x78007800, 0xd8;\n" : "=r"(p[u]) : "r"(v), "r"(n));
        }
    }
}
__device__ __forceinline__ void p1_store(int c, const uint32_t (&p)[4], uint8_t* hptr) {
    if (c & 3) stg128_cs(hptr + (c >> 2) * H_HALF + ((c & 3) - 1) * 512, p[0], p[1], p[2], p[3]);
}

__device__ __forceinline__ uint32_t p1_parity(uint32_t sbase) {
    uint32_t v;
    asm volatile("ld.shared.u32 %0, [%1];\n" : "=r"(v) : "r"(sbase + P1_OFF_TILE - 4) : "memory");
    return v;
}
template <bool GEN>
__device__ __forceinline__ uint32_t gelu2(uint32_t y, float fs) {
    if (GEN) return pack_bf16(gelu_s(h_lo(y) * fs), gelu_s(h_hi(y) * fs));
    uint32_t g;
    asm("{\n.reg .b32 w;\n"
        "fma.rn.f16x2 w, %1, %1, %2;\n"
        "mul.rn.f16x2 w, w, %1;\n"
        "tanh.approx.f16x2 w, w;\n"
        "fma.rn.f16x2 %0, %1, w, %1;\n}\n" : "=r"(g) : "r"(y), "r"(0x40d940d9u));
    return pack_bf16(h_lo(g), h_hi(g));
}
template <int WG, bool GEN>
__device__ __forceinline__ void p1_consumer(const uint32_t (&a)[24][4], uint32_t sc2, const float (&fs)[2], uint32_t sbase, int w, int lane, int zero) {
    const uint32_t bar_full = sbase + P1_OFF_BAR, bar_empty = bar_full + P1_NST * 8;
    const uint32_t empty_remote = mapa(bar_empty, lane & 1) + (WG == 0 ? (lane & 2) * 4 : 0);
    const uint32_t bar_pace = bar_empty + P1_NST * 8 + 16 + w * 8;
    const int g = lane >> 2, q = lane & 3, cb = (blockIdx.x % GRP_CTAS) * 2 + WG;
    float ssq[2] = {0.f, 0.f};
    uint32_t acc[32], sq[4], dd[4];
    TSTAMP(0, 1);

    uint8_t* hp = reinterpret_cast<uint8_t*>(g_h) + (size_t)(blockIdx.x / GRP_CTAS) * (2 * H_TILE) + ((cb * 2 + (w >> 1)) * H_STEP + (w & 1) * 1536) + g * 64 + (q ^ (g >> 1)) * 16;
    const uint64_t desc_base = make_desc(sbase, 16, 1024) | (1ull << 62);
#pragma unroll 1
    for (int i = 0;; i++) {
        const int s0 = (i & 1) * 16, par = (i >> 1) & 1;
        const uint64_t d0 = desc_base + (uint64_t)((i & 1) * (LN_TILE / 16));
        TRACE(WG, i, 0);
        if (WG == 0) mbar_wait(bar_full + s0, par);
        bar_sync(1 + WG, 256);
        TRACE(WG, i, 1);
        uint32_t step, more;
        wg_fence();
#pragma unroll
        for (int k = 0; k < 24; k++) {
            if (WG == 0 && k == 12) mbar_wait(bar_full + s0 + 8, par);
            mma_rs_n128(acc, a[k], d0 + (uint64_t)((k >> 2) * 1024 + (k & 3) * 2), k != 0);
            if (k == P1_ARR) bar_arrive(2 - WG, 256);
            if (k % 6 == 5) wg_commit();
        }
        asm volatile("ld.shared.v2.u32 {%0, %1}, [%2];\n" : "=r"(step), "=r"(more) : "r"(sbase + P1_OFF_TILE + (i & 3) * 16) : "memory");
        TRACE(WG, i, 2);
        if (WG == 1) {
            wg_wait<2>();
            if (lane < 2) mbar_arrive_cluster(empty_remote + s0);
        }
        hp += step;
        TRACE(WG, i, 3);
        wg_wait<0>();
        TRACE(WG, i, 4);
        if (lane < (WG == 0 ? 4 : 2)) mbar_arrive_cluster(empty_remote + s0 + WG * 8);
#pragma unroll
        for (int c = 0; c < 8; c++) {
            uint32_t p[4];
#pragma unroll
            for (int u = 0; u < 4; u++) p[u] = gelu2<GEN>(acc[8 * (c >> 1) + 2 * u + (c & 1)], fs[c & 1]);
            p1_pack<GEN>(c, p, dd, sq, sc2);
            p1_store(c, p, hp);
        }
#pragma unroll
        for (int r = 0; r < 2; r++) {
            const uint32_t u = bf2_add(sq[r], sq[2 + r]);
            ssq[r] += bf_lo(u) + bf_hi(u);
        }
        if (lane == 0) mbar_arrive(bar_pace);
        if (!more) break;
    }
    TSTAMP(0, 21);
    if (WG == 0) bar_sync(1, 256);
#pragma unroll
    for (int r = 0; r < 2; r++) {
        ssq[r] += __shfl_xor_sync(0xffffffffu, ssq[r], 1);
        ssq[r] += __shfl_xor_sync(0xffffffffu, ssq[r], 2);
        if (q == 0) atomicAdd(&g_sums[p1_parity(sbase)][cb * 64 + w * 16 + r * 8 + g], ssq[r]);
    }
}

__global__ void __cluster_dims__(2, 1, 1) __launch_bounds__(512, 1)
pass1_kernel(const __grid_constant__ CUtensorMap wmap, const __nv_bfloat16* __restrict__ x, const __nv_bfloat16* __restrict__ dw,
             const __nv_bfloat16* __restrict__ w2, const __nv_bfloat16* __restrict__ grn_b, int zero) {
    extern __shared__ __align__(1024) uint8_t smem[];
    const uint32_t sbase = smem_u32(smem);
    const uint32_t bar_full = sbase + P1_OFF_BAR, bar_empty = bar_full + P1_NST * 8, bar_w = bar_empty + P1_NST * 8;
    const int tid = threadIdx.x;
    const int warp = __shfl_sync(0xffffffffu, tid >> 5, 0), lane = tid & 31;
    const uint32_t rank = cluster_rank();
    const int cig = blockIdx.x % GRP_CTAS;
    uint8_t* const ring = reinterpret_cast<uint8_t*>(g_ln);

    TSTAMP(0, 0);
    TRACEW(110 + warp, 0);
    const uint32_t bar_pace = bar_w + 16, bar_xfull = bar_pace + 32, bar_xempty = bar_xfull + 8, bar_done = bar_xfull + 16;
    const uint32_t bar_raw = sbase + P1_OFF_RAW;
    const int ln0 = blockIdx.x >> 2, first = blockIdx.x / GRP_CTAS;
    const uint8_t* xsrc = reinterpret_cast<const uint8_t*>(x) + (size_t)(NGRP * 4 + blockIdx.x) * P1_X;

    if (warp >= 12) {
        reg_dec<24>();
        asm volatile("barrier.cluster.arrive.relaxed.aligned;\n" ::: "memory");
        asm volatile("barrier.cluster.wait.aligned;\n" ::: "memory");
        if (warp == 12) {
            int prev = first - NGRP, t = first, next = t + NGRP;
            const uint32_t rbase = mapa(sbase, lane & 1);
#pragma unroll 1
            for (int i = 1; t < NT_RING; i++) {
                const int s0 = (i & 1) * 2, par = ((i + 1) >> 1 & 1) ^ 1;
                const int round = t / LN_RING, slot = t - round * LN_RING;
                const uint8_t* src = ring + slot * LN_TILE + rank * (P1_SLOT / 2);
                int draw = 0;
                if (rank == 0 && lane == 0) draw = atomicAdd(&g_flag[LN_RING + (cig >> 2)][(cig >> 1) & 1][0], 1u);
                flag_wait<true>(&g_flag[slot][0][0], 4 * round + 4);
                TRACEW(i, 2);
                asm volatile("fence.proxy.async.global;\n" ::: "memory");
                draw = 2 * NGRP + __shfl_sync(0xffffffffu, draw, 0);
#pragma unroll
                for (int h = 0; h < 2; h++) {
                    mbar_wait(bar_empty + (s0 + h) * 8, par);
                    TRACEW(i, 4 + h);
                    if (elect_one()) {
                        mbar_expect_tx(bar_full + (s0 + h) * 8, P1_SLOT + 16 - 16 * h);
                        bulk_g2s_mc(sbase + (s0 + h) * P1_SLOT + rank * (P1_SLOT / 2), src + h * P1_SLOT, P1_SLOT / 2, bar_full + (s0 + h) * 8, (uint16_t)3);
                    }
                    __syncwarp();
                    if (h == 0 && rank == 0 && lane < 2)
                        asm volatile("st.async.shared::cluster.mbarrier::complete_tx::bytes.v4.u32 [%0], {%1, %2, %3, %3}, [%4];\n"
                                     ::"r"(rbase + P1_OFF_TILE + (i & 3) * 16), "r"((t - prev) * (2 * H_TILE)), "r"((int)(next < NT_RING)), "r"(draw),
                                       "r"(rbase + P1_OFF_BAR + s0 * 8) : "memory");
                }
                prev = t;
                t = next;
                next = draw;
                if (rank != 0) {
                    mbar_wait(bar_full + (s0 ^ 2) * 8, ((i - 1) >> 1) & 1);
                    asm volatile("ld.shared.u32 %0, [%1];\n" : "=r"(t) : "r"(sbase + P1_OFF_TILE + ((i - 1) & 3) * 16 + 8) : "memory");
                }
            }
        } else if (warp == 13) {
            int ph = 0;
            unsigned target = 0;
#pragma unroll 1
            for (int i = ln0 + LN_STEP; i < NT_RING; i += LN_STEP, ph ^= 1) {
                target += ph * (GRP_CTAS / 2);
                xsrc += (size_t)NUM_CTAS * P1_X;
                mbar_wait(bar_xempty, ph);
                if (elect_one()) {
                    mbar_expect_tx(bar_xfull, P1_X);
                    bulk_g2s(sbase + P1_OFF_X, xsrc, P1_X, bar_xfull);
                }
                __syncwarp();
                const uint32_t off = flag_wait<false>(&g_flag[ln0 + (ph ^ 1) * LN_STEP][1][0], target);
                mbar_wait(bar_done, ph);
                if (elect_one()) {
                    asm volatile("st.shared.u32 [%0], %1;\n" ::"r"(bar_done + 8), "r"(off) : "memory");
                    mbar_arrive(bar_xfull);
                }
                __syncwarp();
            }
        } else if (warp == 15) {
            if (rank == 1 && lane < 2) mbar_arrive(bar_empty + (2 + lane) * 8);
            const uint32_t par = g_epoch & 1;
            asm volatile("st.shared.u32 [%0], %1;\n" ::"r"(sbase + P1_OFF_TILE - 4), "r"(par) : "memory");
            if (blockIdx.x < 16) reinterpret_cast<float4*>(g_sums[par ^ 1])[blockIdx.x * 32 + lane] = make_float4(0.f, 0.f, 0.f, 0.f);
            bar_arrive(3, 160);
            {
                bar_sync(4, 288);
                mbar_wait(bar_raw + 8, 0);
                const uint32_t o = lane * 16384 + rank * 8192, peer = mapa(sbase, rank ^ 1);
                if (lane < 6)
                    asm volatile("cp.async.bulk.shared::cluster.shared::cta.mbarrier::complete_tx::bytes [%0], [%1], 8192, [%2];\n"
                                 ::"r"(peer + o), "r"(sbase + o), "r"(peer + P1_OFF_BAR + (lane >= 3 ? 8 : 0)) : "memory");
                __syncwarp();
            }
            int t = first, next = t + NGRP;
            if (rank == 1) {
                mbar_wait(bar_full, 0);
                mbar_wait(bar_full + 8, 0);
                if (lane < 2) mbar_arrive(bar_empty + lane * 8);
            }
#pragma unroll 1
            for (int i = 1; rank == 1 && t < NT_RING; i++) {
                const int s0 = (i & 1) * 16;
                mbar_wait(bar_full + s0, (i >> 1) & 1);
                mbar_wait(bar_full + s0 + 8, (i >> 1) & 1);
                if (lane == 0) asm volatile("red.relaxed.gpu.global.add.u32 [%0], 1;\n" ::"l"(&g_flag[t % LN_RING][1][0]) : "memory");
                t = next;
                asm volatile("ld.shared.u32 %0, [%1];\n" : "=r"(next) : "r"(sbase + P1_OFF_TILE + (i & 3) * 16 + 8) : "memory");
                if (lane < 2) mbar_arrive(bar_empty + s0 + lane * 8);
                TRACEW(i, 3);
            }
        } else if (warp == 14) {
            int ph = 0;
#pragma unroll 1
            for (int i = ln0; i < NT_RING; i += LN_STEP, ph ^= 1) {
                mbar_wait(bar_done, ph);
                TRACEW(i / LN_STEP, 0);
                asm volatile("fence.proxy.async.global;\n" ::: "memory");
                if (elect_one()) asm volatile("red.release.gpu.global.add.u32 [%0], 1;\n" ::"l"(&g_flag[ln0 + ph * LN_STEP][0][0]) : "memory");
                __syncwarp();
                TRACEW(i / LN_STEP, 1);
            }
        }
        __syncwarp();
        cluster_sync();
    } else if (warp >= 8) {
        reg_dec<88>();
        asm volatile("barrier.cluster.arrive.relaxed.aligned;\n" ::: "memory");
        {
            const int l8 = lane & 7, row = (warp - 8) * 4 + (lane >> 3), px = (blockIdx.x & 3) * 32 + row;
            uint32_t d[6][4];
#pragma unroll
            for (int j = 0; j < 6; j++) {
                const uint4 t = reinterpret_cast<const uint4*>(dw)[j * 8 + l8];
                d[j][0] = t.x; d[j][1] = t.y; d[j][2] = t.z; d[j][3] = t.w;
            }
            const int n = (px & 64) + perm32(2 * row + ((px >> 5) & 1));
            uint8_t* const dst0 = ring + ln0 * LN_TILE + n * 128 + ((l8 ^ (n & 7)) << 4);
            const uint32_t src = sbase + P1_OFF_X + ((warp - 8) * 8 + (lane >> 3)) * (C_DIM * 2) + l8 * 16;
            int ph = 0;
            asm volatile("barrier.cluster.wait.aligned;\n" ::: "memory");
#pragma unroll 1
            for (int i = ln0; i < NT_RING; i += LN_STEP, ph ^= 1) {
                TRACE(2, i / LN_STEP, 0);
                mbar_wait(bar_xfull, ph);
                uint32_t off;
                asm volatile("ld.shared.u32 %0, [%1];\n" : "=r"(off) : "r"(bar_done + 8) : "memory");
                TRACE(2, i / LN_STEP, 1);
#pragma unroll 1
                for (int ps = 0; ps < 2; ps++) {
                    uint32_t v[6][4];
#pragma unroll
                    for (int j = 0; j < 6; j++)
                        asm volatile("ld.shared.v4.u32 {%0,%1,%2,%3}, [%4];\n"
                                     : "=r"(v[j][0]), "=r"(v[j][1]), "=r"(v[j][2]), "=r"(v[j][3]) : "r"(src + ps * (4 * C_DIM * 2) + j * 128) : "memory");
                    ln_row<P1_PACE>(v, d, bar_pace + (warp - 8) * 8, off, zero, ps == 1 && lane == 0 ? bar_xempty : 0);
                    uint8_t* dst = dst0 + ph * (LN_STEP * LN_TILE) + ps * 4096;
#pragma unroll
                    for (int j = 0; j < 6; j++) *reinterpret_cast<uint4*>(dst + j * 16384) = make_uint4(v[j][0], v[j][1], v[j][2], v[j][3]);
                    TRACE(2, i / LN_STEP, 3 + ps);
                }
                asm volatile("fence.proxy.async.global;\nfence.acq_rel.cta;\n" ::: "memory");
                __syncwarp();
                if (lane == 0) mbar_arrive(bar_done);
                TRACE(2, i / LN_STEP, 5);
                TRACE(2, i / LN_STEP, 2);
            }
        }
        const int gw = (warp - 8) * NUM_CTAS + blockIdx.x;
        bar_sync(3, 160);
        if (gw < 288) {
            const int np = (gw % 12) * 32 + lane, kb = gw / 12;
            const __nv_bfloat16* wc = w2 + (size_t)kb * 64 * C_DIM + perm32(np);
            float bsum = 0.f;
#pragma unroll 2
            for (int c = 0; c < 8; c++) {
                float f[8];
#pragma unroll
                for (int e = 0; e < 8; e++) {
                    f[e] = __bfloat162float(wc[(c * 8 + e) * C_DIM]);
                    bsum = fmaf(__bfloat162float(grn_b[kb * 64 + c * 8 + e]), f[e], bsum);
                    f[e] *= __uint_as_float(__ldcg(&g_ex[kb * 64 + c * 8 + e]) << 23);
                }
                g_w2img[(((kb * 4 + (c >> 1)) * 48 + (np >> 3)) * 2 + (c & 1)) * 8 + (np & 7)] =
                    make_uint4(pack_f16(f[0], f[1]), pack_f16(f[2], f[3]), pack_f16(f[4], f[5]), pack_f16(f[6], f[7]));
            }
            atomicAdd(&g_sums[p1_parity(sbase)][HID + np], bsum);
        }
        __syncwarp();
        cluster_sync();
    } else {
        uint32_t d[6][4];
#pragma unroll
        for (int j = 0; j < 6; j++)
            asm volatile("ld.global.nc.v4.u32 {%0,%1,%2,%3}, [%4];\n" : "=r"(d[j][0]), "=r"(d[j][1]), "=r"(d[j][2]), "=r"(d[j][3])
                         : "l"(reinterpret_cast<const uint4*>(dw) + j * 8 + (lane & 7)) : "memory");
        if (tid == 0) {
            mbar_init(bar_raw, 1);
            mbar_init(bar_raw + 8, 8);
            asm volatile("fence.mbarrier_init.release.cluster;\n" ::: "memory");
            mbar_expect_tx(bar_raw, P1_SLOT);
            for (int i = 0; i < 6; i++)
                bulk_g2s(sbase + i * 16384 + (rank ^ 1) * 8192, x + (size_t)(first * 128 + rank * 64) * C_DIM + i * 4096, 8192, bar_raw);
        }
        if (tid == 32) {
            mbar_init(bar_xfull, 2);
            mbar_init(bar_xempty, 4);
            mbar_init(bar_done, 4);
            asm volatile("fence.mbarrier_init.release.cluster;\n" ::: "memory");
            mbar_expect_tx(bar_xfull, P1_X);
            bulk_g2s(sbase + P1_OFF_X, xsrc, P1_X, bar_xfull);
            asm volatile("st.shared.u32 [%0], 1;\n" ::"r"(bar_done + 8) : "memory");
            mbar_arrive(bar_xfull);
        }
        if (tid == 64) {
            asm volatile("st.shared.v4.u32 [%0], {0, 1, %1, %1};\n" ::"r"(sbase + P1_OFF_TILE), "r"(first + NGRP) : "memory");
            for (int i = 0; i < P1_NST; i++) {
                mbar_init(bar_full + i * 8, 1);
                mbar_init(bar_empty + i * 8, 16 + rank);
                mbar_init(bar_pace + i * 8, 1);
                if (i < 2) mbar_expect_tx(bar_full + i * 8, P1_SLOT / 2);
            }
            asm volatile("fence.mbarrier_init.release.cluster;\n" ::: "memory");
            if (blockIdx.x < 64) (&g_half[0][0])[blockIdx.x] = 0;
            else if (blockIdx.x == 64) g_prog = 0;
        }
        if (tid == 96) {
            for (int i = 0; i < 2; i++) mbar_init(bar_w + i * 8, 1);
            asm volatile("fence.mbarrier_init.release.cluster;\n" ::: "memory");
        }
        __syncwarp();
        asm volatile("barrier.cluster.arrive.relaxed.aligned;\n" ::: "memory");
        if (tid == 96)
            for (int i = 0; i < 2; i++) {
                mbar_expect_tx(bar_w + i * 8, P1_SLOT);
                tma2(sbase + (2 + i) * P1_SLOT, &wmap, cig * 128 + i * 64, 0, bar_w + i * 8);
                tma2(sbase + (2 + i) * P1_SLOT + P1_SLOT / 2, &wmap, cig * 128 + i * 64, 192, bar_w + i * 8);
            }
        __syncwarp();
        reg_inc<200>();
        TRACEW(110 + warp, 1);
        const int wg = warp >> 2, w = warp & 3;
        uint32_t a[24][4];
        {
            const int n = warp * 8 + (lane >> 3), px = (n & 1) * 32 + (n >> 5) * 4 + ((n >> 1) & 1) * 8 + ((n >> 3) & 3);
            if (wg == 1) bar_arrive(1, 256);
            gdc_launch();
            asm volatile("barrier.cluster.wait.aligned;\n" ::: "memory");
#pragma unroll 1
            for (int ps = -1; ps < 2; ps++) {
                if (ps == 0) mbar_wait(bar_raw, 0);
                TRACEW(110 + warp, 2 + (ps == 0));
                uint32_t v[6][4];
#pragma unroll
                for (int j = 0; j < 6; j++) {
                    const uint32_t o = (px + (ps & 1) * 16) * (C_DIM * 2) + j * 128;
                    asm volatile("ld.shared.v4.u32 {%0,%1,%2,%3}, [%4];\n" : "=r"(v[j][0]), "=r"(v[j][1]), "=r"(v[j][2]), "=r"(v[j][3])
                                 : "r"(sbase + (rank ^ 1) * 8192 + (lane & 7) * 16 + o + (o & ~8191u)) : "memory");
                }
                ln_row<false>(v, d, 0, 0, zero, 0);
                const uint32_t p = sbase + (rank * 64 + n + (ps & 1) * 4) * 128 + (((lane ^ n ^ (ps & 1) * 4) & 7) << 4);
#pragma unroll
                for (int j = 0; j < 6; j++)
                    asm volatile("st.shared.v4.u32 [%4], {%0,%1,%2,%3};\n"
                                 ::"r"(v[j][0]), "r"(v[j][1]), "r"(v[j][2]), "r"(v[j][3]), "r"(p + j * 16384) : "memory");
            }
            asm volatile("fence.proxy.async.shared::cta;\n" ::: "memory");
            __syncwarp();
            if (lane == 0) mbar_arrive_cluster(mapa(bar_raw + 8, rank ^ 1));
            bar_arrive(4, 288);
            TRACEW(110 + warp, 4);
            const uint32_t src = sbase + (2 + wg) * P1_SLOT + ((lane >> 4) * 8 + (lane & 7)) * 128 + (((2 * w + ((lane >> 3) & 1)) ^ (lane & 7)) << 4);
            mbar_wait(bar_w + wg * 8, 0);
            TRACEW(110 + warp, 5);
            uint32_t dep = 0;
#pragma unroll
            for (int k = 0; k < 24; k++) {
                ldsm4t(a[k], src + k * 2048);
                dep |= a[k][0];
            }
            __syncwarp();
            if (lane < 4) mbar_arrive_cluster(mapa(bar_empty, lane & 1) + (2 + (lane >> 1)) * 8 + (dep & zero));
        }
        uint32_t ex[2];
#pragma unroll
        for (int r = 0; r < 2; r++) {
            float t = 0.f;
#pragma unroll
            for (int j = 0; j < 6; j++) {
                uint32_t c = bf2_mul(a[4 * j][r], a[4 * j][r]);
#pragma unroll
                for (int k = 1; k < 8; k++) c = bf2_fma(a[4 * j + k / 2][r + (k & 1) * 2], a[4 * j + k / 2][r + (k & 1) * 2], c);
                t += bf_lo(c) + bf_hi(c);
            }
            t += __shfl_xor_sync(0xffffffffu, t, 1);
            t += __shfl_xor_sync(0xffffffffu, t, 2);
            ex[r] = min(max(__float_as_uint(13.9f * __fsqrt_rn(t)) >> 23, 72u), 198u);
            if ((lane & 3) == 0) g_ex[cig * 128 + wg * 64 + w * 16 + r * 8 + (lane >> 2)] = ex[r];
        }
        const uint32_t sc2 = 0x47004700u - ((ex[0] | ex[1] << 16) << 7);
        uint32_t big;
        asm volatile("{\n.reg .pred p;\nsetp.gt.u32 p, %1, 16;\nbar.red.or.pred p, 5, 256, p;\nselp.u32 %0, 1, 0, p;\n}\n"
                     : "=r"(big) : "r"(max(ex[0] - 125u, ex[1] - 125u)) : "memory");
        float fs[2] = {1.f, 1.f};
        if (!__shfl_sync(0xffffffffu, big, 0)) {
#pragma unroll
            for (int k = 0; k < 24; k++)
#pragma unroll
                for (int j = 0; j < 4; j++) a[k][j] = bf2_to_h2(a[k][j]);
            if (warp < 4) p1_consumer<0, false>(a, sc2, fs, sbase, w, lane, zero);
            else p1_consumer<1, false>(a, sc2, fs, sbase, w, lane, zero);
        } else {
#pragma unroll
            for (int r = 0; r < 2; r++) fs[r] = __uint_as_float((268u - ex[r]) << 23);
#pragma unroll
            for (int k = 0; k < 24; k++)
#pragma unroll
                for (int j = 0; j < 4; j++)
                    asm("cvt.rn.f16x2.f32 %0, %1, %2;\n" : "=r"(a[k][j]) : "f"(bf_hi(a[k][j]) * fs[j & 1]), "f"(bf_lo(a[k][j]) * fs[j & 1]));
#pragma unroll
            for (int r = 0; r < 2; r++) fs[r] = __uint_as_float((ex[r] - 14u) << 23);
            if (warp < 4) p1_consumer<0, true>(a, sc2 + 0x38003800u, fs, sbase, w, lane, zero);
            else p1_consumer<1, true>(a, sc2 + 0x38003800u, fs, sbase, w, lane, zero);
        }
        cluster_sync();
        TSTAMP(0, 30);
    }
}

#define P2_NB_ 5
#define P2_NA_ 5
#define P2_DELTA_ 7
#define P2_EXTRA 0
#define P2_HSLEEP 64
#define P2_T0 5
#define P2_TS 11
constexpr int P2_B = 24576, P2_NB = P2_NB_;
constexpr int P2_A = 3072, P2_NA = P2_NA_;
constexpr int P2_XROW = C_DIM * 2;
constexpr int P2_OFF_A = P2_B * P2_NB;
constexpr int P2_OFF_X = P2_OFF_A + 3 * P2_NA * P2_A;
constexpr int P2_XHALF = 32 * P2_XROW + 64;
constexpr int P2_OFF_BIAS = P2_OFF_X + 64 * P2_XROW + 128;
constexpr int P2_OFF_ONES = P2_OFF_BIAS + 48 * 128;
constexpr int P2_OFF_BAR = P2_OFF_ONES + 256;
constexpr int P2_SMEM = P2_OFF_BAR + (2 * P2_NB + 6 * P2_NA + 3) * 8;
constexpr int P2_LAG = 16;
constexpr int P2_NCL = NUM_CTAS / 2, P2_ITEMS = NT128 / P2_NCL, P2_SHARED = NT128 - P2_ITEMS * P2_NCL;
constexpr int P2_POS = P2_LAG * (P2_ITEMS + 2);
constexpr int P2_XC = 8 * P2_XROW;
constexpr uint32_t ACC_UP = 0x3fc23fc2u;
constexpr float ACC_UPF = 1.515625f;
constexpr int P2_DELTA = P2_DELTA_;
__device__ __forceinline__ int p2_tile(int cl, int n) {
    return n == 0 ? NT128 - 1 - cl : n < 0 || n == P2_ITEMS ? NT128 - 1 - P2_NCL - (cl >> 1) : cl + P2_NCL * (n - 1);
}

#define P2_EG 2
__device__ __forceinline__ void p2_epilogue(const uint32_t (&acc0)[48], const uint32_t (&acc1)[48], uint32_t sx, int zero) {
    uint32_t v[2][P2_EG][4];
    auto load = [&](int c, uint32_t a) {
#pragma unroll
        for (int j = 0; j < P2_EG; j++) {
            const int u = c * P2_EG + j;
            asm volatile("ld.shared.v4.u32 {%0,%1,%2,%3}, [%4];\n" : "=r"(v[c & 1][j][0]), "=r"(v[c & 1][j][1]), "=r"(v[c & 1][j][2]), "=r"(v[c & 1][j][3])
                         : "r"(a + (u >> 1) * 64 + (u & 1) * 4 * P2_XROW) : "memory");
        }
    };
    load(0, sx);
#pragma unroll
    for (int c = 0; c < 24 / P2_EG; c++) {
        if (c + 1 < 24 / P2_EG) load(c + 1, sx + (v[c & 1][P2_EG - 1][0] & zero));
#pragma unroll
        for (int j = 0; j < P2_EG; j++) {
            const int u = c * P2_EG + j, i = 8 * ((u >> 1) % 6) + (u & 1);
            const uint32_t (&acc)[48] = u < 12 ? acc0 : acc1;
            uint32_t (&w)[4] = v[c & 1][j];
#pragma unroll
            for (int e = 0; e < 4; e++) w[e] = bf2_fma(pack_bf16(h_lo(acc[i + 2 * e]), h_hi(acc[i + 2 * e])), ACC_UP, w[e]);
            asm volatile("st.shared.v4.u32 [%4], {%0,%1,%2,%3};\n" ::"r"(w[0]), "r"(w[1]), "r"(w[2]), "r"(w[3]),
                         "r"(sx + (u >> 1) * 64 + (u & 1) * 4 * P2_XROW) : "memory");
        }
    }
}

__device__ __forceinline__ void p2_unpack(uint32_t (&u)[4], uint32_t o1, uint32_t o2, uint32_t o3) {
    u[2] = o1 & 0x87ff87ffu;
    u[1] = o2 & 0x87ff87ffu;
    u[3] = o3 & 0x87ff87ffu;
    u[0] = __byte_perm((o2 & 0x78007800u) | ((o3 >> 4) & 0x07800780u), 0, 0x2301) | ((o1 >> 4) & 0x07800780u);
}
__device__ __forceinline__ void p2_epilogue_add(const uint32_t (&acc)[48], uint8_t* o) {
    auto up = [&](int i) { return pack_bf16(h_lo(acc[i / 2]) * ACC_UPF, h_hi(acc[i / 2]) * ACC_UPF); };
#pragma unroll
    for (int t = 0; t < 6; t++)
#pragma unroll
        for (int r = 0; r < 2; r++)
            asm volatile("red.global.add.noftz.v4.bf16x2 [%0], {%1,%2,%3,%4};\n" ::"l"(o + t * 64 + r * 4 * P2_XROW),
                         "r"(up(16 * t + 2 * r)), "r"(up(16 * t + 2 * r + 4)), "r"(up(16 * t + 2 * r + 8)), "r"(up(16 * t + 2 * r + 12)) : "memory");
}

__global__ void __cluster_dims__(2, 1, 1) __launch_bounds__(512, 1)
pass2_kernel(const __nv_bfloat16* __restrict__ x, const __nv_bfloat16* __restrict__ grn_g, __nv_bfloat16* __restrict__ out, int zero) {
    extern __shared__ __align__(1024) uint8_t smem[];
    const uint32_t sbase = smem_u32(smem);
    const uint32_t bar_bfull = sbase + P2_OFF_BAR, bar_bempty = bar_bfull + P2_NB * 8;
    const uint32_t bar_afull = bar_bempty + P2_NB * 8, bar_aempty = bar_afull + 3 * P2_NA * 8;
    const uint32_t bar_xfull = bar_aempty + 3 * P2_NA * 8, bar_oready = bar_xfull + 8, s_pos = bar_xfull + 16;
    int tid;
    asm volatile("mov.u32 %0, %%tid.x;\n" : "=r"(tid));
    const int warp = __shfl_sync(0xffffffffu, tid >> 5, 0), lane = tid & 31;
    const uint32_t rank = cluster_rank();
    const int cl = blockIdx.x >> 1, pair = cl >> 1;
    const int k0 = (4 * pair + (cl & 1) * 32) % 48;
    const int head = pair < P2_SHARED && !(cl & 1), tail = pair < P2_SHARED && (cl & 1);

    TSTAMP(1, 0);
    if (tid == 384) {
        for (int i = 0; i < P2_NB; i++) {
            mbar_init(bar_bfull + i * 8, 1);
            mbar_init(bar_bempty + i * 8, 24);
        }
        for (int i = 0; i < 3 * P2_NA; i++) {
            mbar_init(bar_afull + i * 8, 1);
            mbar_init(bar_aempty + i * 8, 4);
        }
        mbar_init(bar_xfull, 2);
        mbar_init(bar_oready, 4);
        asm volatile("st.shared.u32 [%0], 0;\n" ::"r"(s_pos) : "memory");
        asm volatile("fence.mbarrier_init.release.cluster;\n" ::: "memory");
    }
    __syncthreads();
    cluster_sync_relaxed();

    if (warp >= 12) {
        reg_dec<32>();
        if (warp == 12) {
            const uint8_t* wsrc = reinterpret_cast<const uint8_t*>(g_w2img) + rank * (P2_B / 2);
            int st = 0, ph = 1, kb = k0;
            const int busy = head ? 0 : tail ? P2_POS - 24 : P2_POS;
            gdc_wait();
#pragma unroll 1
            for (int p = 0; p < P2_POS; p++) {
                mbar_wait(bar_bempty + st * 8, ph);
                TR2P(p, 0);
                if (elect_one()) {
                    mbar_expect_tx(bar_bfull + st * 8, P2_B);
                    bulk_g2s_mc(sbase + st * P2_B + rank * (P2_B / 2), wsrc + kb * P2_B, P2_B / 2, bar_bfull + st * 8, (uint16_t)3);
                    asm volatile("st.volatile.shared.u32 [%0], %1;\n" ::"r"(s_pos), "r"(p) : "memory");
                    const int idle = ((unsigned)(p - P2_LAG) >= P2_POS - 2 * P2_LAG) + ((unsigned)(p - 2 * P2_LAG) >= P2_POS - 4 * P2_LAG && (unsigned)(p - busy) >= 24);
                    if (idle) asm volatile("mbarrier.arrive.shared::cta.b64 _, [%0], %1;\n" ::"r"(bar_bempty + st * 8), "r"(idle * 8) : "memory");
                    if (rank == 0) asm volatile("red.relaxed.gpu.global.add.u32 [%0], 1;\n" ::"l"(&g_prog) : "memory");
                }
                __syncwarp();
                if (++st == P2_NB) { st = 0; ph ^= 1; }
                if (++kb == 48) kb = 0;
            }
            mbar_wait(bar_bempty + st * 8, ph);
            if (lane == 0) mbar_arrive(bar_bfull + st * 8);
        } else if (warp == 13) {
            const uint8_t* src[3];
            int n[3], left[3], wrap[3];
            uint32_t st[3];
            auto item = [&](int w) {
                int u = k0 + (n[w] < 0 ? 0 : n[w] == P2_ITEMS ? 40 : w * P2_LAG);
                if (u >= 48) u -= 48;
                left[w] = n[w] < 0 || n[w] == P2_ITEMS ? 24 : 48;
                wrap[w] = left[w] - (48 - u);
                src[w] = reinterpret_cast<const uint8_t*>(g_h) + (size_t)p2_tile(cl, n[w]) * (2 * H_TILE) + rank * H_HALF + u * H_STEP;
            };
#pragma unroll
            for (int w = 0; w < 3; w++) {
                n[w] = w == 2 && head ? -1 : w;
                st[w] = 0x80000000u;
                item(w);
            }
            gdc_wait();
#pragma unroll 1
            for (int done = 0; done < 3;) {
                bool idle = true;
#pragma unroll
                for (int w = 0; w < 3; w++) {
                    const uint32_t o = (st[w] & 0xff) + w * P2_NA * 8;
                    if (left[w] >= 0 && mbar_test(bar_aempty + o, st[w] >> 31)) {
                        idle = false;
                        if (left[w] == 0) {
                            if (lane == 0) mbar_arrive(bar_afull + o);
                            left[w] = -1;
                            done++;
                        } else {
                            if (elect_one()) {
                                mbar_expect_tx(bar_afull + o, P2_A);
                                bulk_g2s(sbase + P2_OFF_A + o * (P2_A / 8), src[w], P2_A, bar_afull + o);
                            }
                            __syncwarp();
                            src[w] += H_STEP;
                            st[w] += 8;
                            if ((st[w] & 0xff) == P2_NA * 8) st[w] ^= 0x80000000u | (P2_NA * 8);
                            if (--left[w] == wrap[w]) src[w] -= 48 * H_STEP;
                            if (left[w] == 0 && (n[w] += 3) < P2_ITEMS + tail) item(w);
                        }
                    }
                }
                if (idle) __nanosleep(P2_HSLEEP);
                SAFE_BREAK
            }
        } else if (warp == 14) {
            const uint32_t sx = sbase + P2_OFF_X;
            size_t o = 0;
            auto pace = [&](int target) {
                int v;
                while (true) {
                    asm volatile("ld.volatile.shared.u32 %0, [%1];\n" : "=r"(v) : "r"(s_pos) : "memory");
                    if (v * 16 >= target) break;
                    __nanosleep(100);
                    SAFE_BREAK
                }
            };
#pragma unroll 1
            for (int n = -head; n <= P2_ITEMS; n++) {
                const size_t on = (size_t)(2 * p2_tile(cl, n) + rank) * (64 * C_DIM * 2);
                const bool st = n + head > 0, ld = n < P2_ITEMS;
                if (st) mbar_wait(bar_oready, (n - 1 + head) & 1);
                TR2P(n + 1, 1);
                if (lane == 0) {
                    if (n == 1 && head) {
                        asm volatile("cp.async.bulk.wait_group 0;\nfence.proxy.async.global;\n" ::: "memory");
                        asm volatile("st.release.gpu.global.u32 [%0], 1;\n" ::"l"(&g_half[pair][rank]) : "memory");
                    }
                    if (ld) mbar_expect_tx(bar_xfull, 64 * C_DIM * 2);
                    int t = st && n < P2_ITEMS - 1 ? (P2_LAG * (n + 2) + P2_T0 - 1) * 16 : -1024;
#pragma unroll 1
                    for (int c = 0; st && c < 64 * P2_XROW; c += P2_XC) {
                        pace(t += P2_TS);
                        bulk_s2g(reinterpret_cast<uint8_t*>(out) + o + c, sx + c + (c >= 32 * P2_XROW ? 64 : 0), P2_XC);
                    }
                    asm volatile("cp.async.bulk.commit_group;\ncp.async.bulk.wait_group.read 0;\n" ::: "memory");
#pragma unroll 1
                    for (int c = 0; ld && c < 64 * P2_XROW; c += P2_XC) {
                        pace(t += P2_TS);
                        bulk_g2s(sx + c + (c >= 32 * P2_XROW ? 64 : 0), reinterpret_cast<const uint8_t*>(x) + on + c, P2_XC, bar_xfull);
                    }
                    TR2P(n + 1, 2);
                    if (rank == 0 && n > 0 && n < P2_ITEMS - 2)
                        flag_wait<false>(&g_prog, P2_NCL * (P2_LAG * (n + 3) + P2_EXTRA) + (tail ? P2_SHARED - P2_NCL : P2_SHARED) * P2_DELTA);
                    if (ld) mbar_arrive(bar_xfull);
                    TR2P(n + 1, 3);
                }
                __syncwarp();
                o = on;
            }
            asm volatile("cp.async.bulk.wait_group 0;\n" ::: "memory");
            TR2P(30, 1);
        }
        __syncwarp();
        cluster_sync();
        if (warp == 14) TR2P(31, 1);
    } else {
        reg_inc<160>();
        const int wg = warp >> 2, w = warp & 3, g = lane >> 2, q = lane & 3;
        const uint32_t sx = sbase + P2_OFF_X + (g & 1) * P2_XHALF + (w * 8 + (g >> 1)) * P2_XROW + q * 16;
        const uint32_t af = bar_afull + wg * P2_NA * 8, ae = bar_aempty + wg * P2_NA * 8;
        const uint32_t s_a = sbase + P2_OFF_A - bar_afull * (P2_A / 8) + (lane >> 3) * 512 + (lane & 7) * 64 +
                             ((w ^ ((lane & 7) >> 1)) << 4);
        uint32_t acc0[48], acc1[48];
        uint4 a0[2], a1[2];
        int st = 0, ph = 0;

        {
            float* s_red = reinterpret_cast<float*>(smem + P2_OFF_ONES);
            float gx[4], part = 0.f;
            __nv_bfloat16 gg[4];
#pragma unroll
            for (int i = 0; i < 4; i++) gg[i] = grn_g[tid + 384 * i];
            TSTAMP(1, 27);
            gdc_wait();
            TSTAMP(1, 1);
            if (blockIdx.x == 120 && tid < (LN_RING + 3) * 2) (&g_flag[0][0][0])[tid * 8] = 0;
            if (blockIdx.x == 121 && tid == 0) g_epoch++;
#pragma unroll
            for (int i = 0; i < 4; i++) gx[i] = __ldcg(&g_sums[0][tid + 384 * i]) + __ldcg(&g_sums[1][tid + 384 * i]);
            const float bias = (__ldcg(&g_sums[0][HID + tid]) + __ldcg(&g_sums[1][HID + tid])) * (1.0f / ACC_UPF);
#pragma unroll
            for (int i = 0; i < 4; i++) {
                gx[i] = sqrtf(gx[i] * (HSCALE * HSCALE) + 1e-6f);
                part += gx[i];
            }
#pragma unroll
            for (int o = 16; o > 0; o >>= 1) part += __shfl_xor_sync(0xffffffffu, part, o);
            TSTAMP(1, 26);
            if (lane == 0) s_red[warp] = part;
            bar_sync(1, 384);
            float tot = 0.f;
#pragma unroll
            for (int i = 0; i < 12; i++) tot += s_red[i];
            const float inv = 1.0f / (tot * (1.0f / HID) + 1e-6f);
            bar_sync(1, 384);
            *reinterpret_cast<uint2*>(smem + P2_OFF_BIAS + tid * 16) = make_uint2(pack_f16(bias, bias - h_lo(pack_f16(bias, 0.f))), 0u);
#pragma unroll
            for (int i = 0; i < 4; i++) {
                const int k = tid + 384 * i;
                *reinterpret_cast<__nv_bfloat16*>(smem + P2_OFF_BIAS + ((k >> 4) * 4 + ((k >> 1) & 3)) * 16 + 8 + ((k >> 3) & 1) * 4 + (k & 1) * 2) =
                    __float2bfloat16(fmaf(__bfloat162float(gg[i]) * (gx[i] * inv), HSCALE / ACC_UPF, HSCALE / ACC_UPF - 1.0f));
            }
            TSTAMP(1, 25);
            if (tid < 16) reinterpret_cast<uint4*>(smem + P2_OFF_ONES)[tid] = make_uint4(tid < 8 ? 0x3c003c00u : 0u, 0u, 0u, 0u);
            asm volatile("fence.proxy.async.shared::cta;\n" ::: "memory");
            bar_sync(1, 384);
        }
        TSTAMP(1, 28);
        const uint32_t s_t = sbase + P2_OFF_BIAS + q * 16 + 8;
        const int first = wg == 2 && head ? 0 : wg * P2_LAG;
        int kt = (k0 + first) % 48;

        int pos = first;
        const int who = __shfl_sync(0xffffffffu, lane == 2 ? 0 : lane < 2 ? 1 : 2, lane);
        const uint32_t rel0 = who ? mapa(bar_bempty, lane & 1) : mapa(ae, rank), rel1 = rel0 + (who ? P2_NB : P2_NA) * 8;
        uint32_t rel = rel1 - 8;
        auto next_rel = [&](bool go) {
            if (go) rel += 8;
            if (rel == rel1) rel = rel0;
        };
        auto release_b = [&]() {
            next_rel(who == 1);
            if (who == 1) mbar_arrive_cluster(rel);
        };
        auto seek = [&](int p) {
            st = p % P2_NB;
            ph = p / P2_NB & 1;
            if (who == 1) rel = (st ? rel0 + st * 8 : rel1) - 8;
            int v;
            while (true) {
                asm volatile("ld.volatile.shared.u32 %0, [%1];\n" : "=r"(v) : "r"(s_pos) : "memory");
                if (v >= p) break;
                __nanosleep(200);
                SAFE_BREAK
            }
        };
        auto publish = [&]() {
            asm volatile("fence.proxy.async.shared::cta;\n" ::: "memory");
            __syncwarp();
            if (who == 0) mbar_arrive(bar_oready);
        };
        bool ok_a, pend = false;
        uint32_t abar = af, pa = 0;
        auto fetch = [&](uint4 (&a)[2]) {
            uint32_t u0[4], u1[4];
            const uint32_t src = s_a + abar * (P2_A / 8);
            abar += 8;
            if (abar == af + P2_NA * 8) { abar = af; pa ^= 0x80000000u; }
            uint2 t0, t1;
            asm volatile("ld.shared.v2.u32 {%0,%1}, [%2];\n" : "=r"(t0.x), "=r"(t0.y) : "r"(s_t + kt * 128) : "memory");
            asm volatile("ld.shared.v2.u32 {%0,%1}, [%2];\n" : "=r"(t1.x), "=r"(t1.y) : "r"(s_t + kt * 128 + 64) : "memory");
            const bool ok_b = mbar_test(bar_bfull + st * 8, ph);
            ok_a = mbar_test(abar, pa >> 31);
            uint32_t o[6];
            asm volatile("ldmatrix.sync.aligned.m8n8.x4.trans.shared.b16 {%0,%1,%2,%3}, [%4];\n"
                         : "=r"(o[0]), "=r"(o[1]), "=r"(o[2]), "=r"(o[3]) : "r"(src) : "memory");
            asm volatile("ldmatrix.sync.aligned.m8n8.x2.trans.shared.b16 {%0,%1}, [%2];\n"
                         : "=r"(o[4]), "=r"(o[5]) : "r"(src + 2048) : "memory");
            p2_unpack(u0, o[0], o[1], o[2]);
            p2_unpack(u1, o[3], o[4], o[5]);
            auto grn = [&](uint32_t u, uint32_t t) { u = bf2_fma(u, t, u); return (u & 0x0fff0fffu) * 7u + u; };
            a[0] = make_uint4(grn(u0[0], t0.x), grn(u0[1], t0.x), grn(u0[2], t0.y), grn(u0[3], t0.y));
            a[1] = make_uint4(grn(u1[0], t1.x), grn(u1[1], t1.x), grn(u1[2], t1.y), grn(u1[3], t1.y));
            if (++kt == 48) kt = 0;
            if (!ok_b) mbar_wait(bar_bfull + st * 8, ph);
        };
        auto step = [&](const uint4 (&a)[2], uint4 (&an)[2], int thr) {
            TR2(0);
            const uint64_t db = make_desc(sbase + st * P2_B, 128, 256);
            wg_fence();
            mma_rs_n192(acc0, a[0], db);
            mma_rs_n192(acc1, a[0], db + 384);
            mma_rs_n192(acc0, a[1], db + 768);
            mma_rs_n192(acc1, a[1], db + 768 + 384);
            wg_commit();
            next_rel(who < thr);
            if (++st == P2_NB) { st = 0; ph ^= 1; }
            wg_wait<1>();
            if (!ok_a) {
                if (who < thr) mbar_arrive_cluster(rel);
                if (thr == 1 && pend) publish();
                thr = 0;
                mbar_wait(abar, pa >> 31);
            }
            if (who < thr) mbar_arrive_cluster(rel);
            fetch(an);
            pos++;
        };
        seek(first);
        mbar_wait(af, 0);
        fetch(a0);
#pragma unroll 1
        for (int n = wg == 2 && head ? -1 : wg;; n += 3) {
            TSTAMP(1, 2 + n);
            const uint64_t ones = make_desc(sbase + P2_OFF_ONES + (n == P2_ITEMS ? 128 : 0), n == P2_ITEMS ? 0 : 128, 0);
            wg_fence();
            mma_ss_n192_init(acc0, ones, make_desc(sbase + P2_OFF_BIAS, 0, 128));
            mma_ss_n192_init(acc1, ones, make_desc(sbase + P2_OFF_BIAS + 3072, 0, 128));
            wg_commit();
            const int p0 = n < 0 || n == P2_ITEMS ? 12 : 0;
            const bool more = n + 3 < P2_ITEMS + tail;
#pragma unroll 1
            for (int p = p0; p < 24; p++) {
                step(a0, a1, p == p0 ? 1 : 2);
                step(a1, a0, 2);
            }
            if (n == P2_ITEMS) {
                flag_wait<true>(&g_half[pair][rank], 1);
                TR2(1);
                wg_wait<0>();
                TR2(2);
                release_b();
                uint8_t* o = reinterpret_cast<uint8_t*>(out) + (size_t)((2 * p2_tile(cl, -1) + rank) * 64 + (g & 1) * 32 + w * 8 + (g >> 1)) * P2_XROW + q * 16;
                p2_epilogue_add(acc0, o);
                p2_epilogue_add(acc1, o + 384);
                TR2(3);
                break;
            }
            mbar_wait(bar_xfull, (n + head) & 1);
            TR2(1);
            wg_wait<0>();
            TR2(2);
            release_b();
            __syncwarp();
            p2_epilogue(acc0, acc1, sx, zero);
            TR2(3);
            if (!more) {
                publish();
                break;
            }
            pend = true;
            ok_a = false;
            if (n < 0 || n + 3 == P2_ITEMS) {
                publish();
                pend = false;
                seek(n < 0 ? 2 * P2_LAG : P2_POS - 24);
                if (abar == af) { abar = af + P2_NA * 8; pa ^= 0x80000000u; }
                abar -= 8;
                kt += 7;
                if (kt >= 48) kt -= 48;
                fetch(a0);
                pos += 8;
            }
        }
        TSTAMP(1, 29);
        cluster_sync();
        TSTAMP(1, 30);
    }
}

}

extern "C" void kernel_launch(void* const* d_in, const int* in_sizes, int n_in, void* d_out, int out_size) {
    const __nv_bfloat16* x = (const __nv_bfloat16*)d_in[0];
    const __nv_bfloat16* dw = (const __nv_bfloat16*)d_in[1];
    const __nv_bfloat16* w1 = (const __nv_bfloat16*)d_in[2];
    const __nv_bfloat16* w2 = (const __nv_bfloat16*)d_in[3];
    const __nv_bfloat16* grn_g = (const __nv_bfloat16*)d_in[4];
    const __nv_bfloat16* grn_b = (const __nv_bfloat16*)d_in[5];
    __nv_bfloat16* out = (__nv_bfloat16*)d_out;

    cudaFuncSetAttribute(pass1_kernel, cudaFuncAttributeMaxDynamicSharedMemorySize, P1_SMEM);
    cudaFuncSetAttribute(pass2_kernel, cudaFuncAttributeMaxDynamicSharedMemorySize, P2_SMEM);

    typedef CUresult (*EncodeFn)(CUtensorMap*, CUtensorMapDataType, cuuint32_t, void*, const cuuint64_t*, const cuuint64_t*,
                                 const cuuint32_t*, const cuuint32_t*, CUtensorMapInterleave, CUtensorMapSwizzle,
                                 CUtensorMapL2promotion, CUtensorMapFloatOOBfill);
    static EncodeFn encode = nullptr;
    if (!encode) {
        cudaDriverEntryPointQueryResult qres;
        cudaGetDriverEntryPoint("cuTensorMapEncodeTiled", (void**)&encode, cudaEnableDefault, &qres);
    }
    CUtensorMap wmap;
    const cuuint64_t gdim[2] = {HID, C_DIM};
    const cuuint64_t gstr[1] = {HID * 2};
    const cuuint32_t box[2] = {64, 192}, estr[2] = {1, 1};
    CUresult er = encode(&wmap, CU_TENSOR_MAP_DATA_TYPE_BFLOAT16, 2, (void*)w1, gdim, gstr, box, estr, CU_TENSOR_MAP_INTERLEAVE_NONE,
           CU_TENSOR_MAP_SWIZZLE_128B, CU_TENSOR_MAP_L2_PROMOTION_L2_128B, CU_TENSOR_MAP_FLOAT_OOB_FILL_NONE);
    if (er != CUDA_SUCCESS) printf("tensor map encode failed %d\n", (int)er);

    pass1_kernel<<<NUM_CTAS, 512, P1_SMEM>>>(wmap, x, dw, w2, grn_b, 0);

    cudaLaunchAttribute attr[1];
    attr[0].id = cudaLaunchAttributeProgrammaticStreamSerialization;
    attr[0].val.programmaticStreamSerializationAllowed = 1;
    cudaLaunchConfig_t cfg = {};
    cfg.gridDim = dim3(NUM_CTAS);
    cfg.stream = 0;
    cfg.attrs = attr;
    cfg.numAttrs = 1;
    cfg.blockDim = dim3(512);
    cfg.dynamicSmemBytes = P2_SMEM;
    cudaLaunchKernelEx(&cfg, pass2_kernel, x, grn_g, out, 0);
}
```

```cpp
#include <cuda.h>
#include <cuda_runtime.h>
#include <cuda_bf16.h>
#include <stdint.h>
#include <stdio.h>

namespace {

constexpr int M_TOTAL = 384 * 384;
constexpr int C_DIM   = 384;
constexpr int HID     = 1536;
constexpr int NT128   = M_TOTAL / 128;
constexpr int NUM_CTAS = 132;

constexpr int NGRP = 11, GRP_CTAS = 12;
constexpr int LN_STEP = NUM_CTAS / 4, LN_RING = 2 * LN_STEP;
constexpr int NT_RING = NT128 - NGRP;
constexpr int LN_TILE = 128 * C_DIM * 2;
constexpr int H_TILE = 64 * HID * 3 / 2;
constexpr int H_HALF = 3072, H_STEP = 6144;

__device__ __align__(1024) uint4 g_h[(size_t)M_TOTAL * HID * 3 / 32];
__device__ __align__(1024) uint4 g_ln[LN_RING * LN_TILE / 16];
__device__ __align__(1024) uint4 g_w2img[HID * C_DIM * 2 / 16];
__device__ __align__(16) float g_sums[2][HID + 2 * C_DIM];
__device__ unsigned g_ex[HID];
__device__ unsigned g_epoch, g_par;
__device__ __align__(128) unsigned g_img;
__device__ __align__(128) unsigned g_prog;
__device__ __align__(128) unsigned g_half[32][2];
__device__ unsigned g_flag[LN_RING + 4][2][8];
#define TSTAMP(k, i)
#define TRACE(wg, pos, i)
#define TRACEW(pos, i)

#define TR2(i)
#define TR2P(pos, i)
__host__ __device__ __forceinline__ int perm32(int n) {
    return (n & ~31) | (((n >> 1) & 3) << 3) | (((n >> 3) & 3) << 1) | (n & 1);
}

__device__ __forceinline__ uint32_t smem_u32(const void* p) { return (uint32_t)__cvta_generic_to_shared(p); }

__device__ __forceinline__ void mbar_init(uint32_t bar, uint32_t count) {
    asm volatile("mbarrier.init.shared::cta.b64 [%0], %1;\n" ::"r"(bar), "r"(count) : "memory");
}
__device__ __forceinline__ void mbar_expect_tx(uint32_t bar, uint32_t bytes) {
    asm volatile("mbarrier.arrive.expect_tx.shared::cta.b64 _, [%0], %1;\n" ::"r"(bar), "r"(bytes) : "memory");
}
__device__ __forceinline__ void mbar_arrive(uint32_t bar) {
    asm volatile("mbarrier.arrive.shared::cta.b64 _, [%0];\n" ::"r"(bar) : "memory");
}
__device__ __forceinline__ void mbar_arrive_cluster(uint32_t bar_cluster_addr) {
    asm volatile("mbarrier.arrive.shared::cluster.b64 _, [%0];\n" ::"r"(bar_cluster_addr) : "memory");
}
#define SAFE_BREAK
__device__ __forceinline__ void mbar_wait(uint32_t bar, uint32_t parity) {
    asm volatile(
        "{\n"
        ".reg .pred p;\n"
        "LAB_WAIT:\n"
        "mbarrier.try_wait.parity.shared::cta.b64 p, [%0], %1;\n"
        "@!p bra LAB_WAIT;\n"
        "}\n" ::"r"(bar), "r"(parity) : "memory");
}
__device__ __forceinline__ bool mbar_test(uint32_t bar, uint32_t parity) {
    uint32_t ok;
    asm volatile("{\n.reg .pred p;\n"
                 "mbarrier.test_wait.parity.shared::cta.b64 p, [%1], %2;\n"
                 "selp.u32 %0, 1, 0, p;\n}\n" : "=r"(ok) : "r"(bar), "r"(parity) : "memory");
    return ok != 0;
}
__device__ __forceinline__ uint32_t mapa(uint32_t addr, uint32_t rank) {
    uint32_t r;
    asm volatile("mapa.shared::cluster.u32 %0, %1, %2;\n" : "=r"(r) : "r"(addr), "r"(rank));
    return r;
}
__device__ __forceinline__ void bulk_g2s(uint32_t dst, const void* src, uint32_t bytes, uint32_t bar) {
    asm volatile("cp.async.bulk.shared::cluster.global.mbarrier::complete_tx::bytes [%0], [%1], %2, [%3];\n"
                 ::"r"(dst), "l"(src), "r"(bytes), "r"(bar) : "memory");
}
__device__ __forceinline__ void bulk_g2s_mc(uint32_t dst, const void* src, uint32_t bytes, uint32_t bar, uint16_t mask) {
    asm volatile("cp.async.bulk.shared::cluster.global.mbarrier::complete_tx::bytes.multicast::cluster [%0], [%1], %2, [%3], %4;\n"
                 ::"r"(dst), "l"(src), "r"(bytes), "r"(bar), "h"(mask) : "memory");
}
__device__ __forceinline__ void tma2(uint32_t dst, const CUtensorMap* map, int c0, int c1, uint32_t bar) {
    asm volatile("cp.async.bulk.tensor.2d.shared::cluster.global.tile.mbarrier::complete_tx::bytes [%0], [%1, {%2, %3}], [%4];\n"
                 ::"r"(dst), "l"(map), "r"(c0), "r"(c1), "r"(bar) : "memory");
}
template <bool ACQ>
__device__ __forceinline__ uint32_t flag_wait(const unsigned* p, unsigned target) {
    unsigned v, n = 0;
    do {
        if (ACQ) asm volatile("ld.acquire.gpu.global.u32 %0, [%1];\n" : "=r"(v) : "l"(p) : "memory");
        else asm volatile("ld.relaxed.gpu.global.u32 %0, [%1];\n" : "=r"(v) : "l"(p) : "memory");
        n++;
    } while (v < target);
    return n == 1;
}
__device__ __forceinline__ void ldsm4t(uint32_t (&r)[4], uint32_t addr) {
    asm volatile("ldmatrix.sync.aligned.m8n8.x4.trans.shared.b16 {%0,%1,%2,%3}, [%4];\n"
                 : "=r"(r[0]), "=r"(r[1]), "=r"(r[2]), "=r"(r[3]) : "r"(addr) : "memory");
}
__device__ __forceinline__ void bulk_s2g(void* dst, uint32_t src, uint32_t bytes) {
    asm volatile("cp.async.bulk.global.shared::cta.bulk_group [%0], [%1], %2;\n" ::"l"(dst), "r"(src), "r"(bytes) : "memory");
}
__device__ __forceinline__ void cluster_sync() {
    asm volatile("barrier.cluster.arrive.aligned;\nbarrier.cluster.wait.aligned;\n" ::: "memory");
}
__device__ __forceinline__ void cluster_sync_relaxed() {
    asm volatile("barrier.cluster.arrive.relaxed.aligned;\nbarrier.cluster.wait.aligned;\n" ::: "memory");
}
__device__ __forceinline__ void gdc_wait() { asm volatile("griddepcontrol.wait;\n" ::: "memory"); }
__device__ __forceinline__ void gdc_launch() { asm volatile("griddepcontrol.launch_dependents;\n" ::: "memory"); }
__device__ __forceinline__ uint32_t cluster_rank() {
    uint32_t r;
    asm volatile("mov.u32 %0, %%cluster_ctarank;\n" : "=r"(r));
    return r;
}
__device__ __forceinline__ bool elect_one() {
    uint32_t pred;
    asm volatile("{\n.reg .pred p;\nelect.sync _|p, 0xffffffff;\nselp.u32 %0, 1, 0, p;\n}\n" : "=r"(pred));
    return pred != 0;
}
__device__ __forceinline__ void wg_fence() { asm volatile("wgmma.fence.sync.aligned;\n" ::: "memory"); }
__device__ __forceinline__ void wg_commit() { asm volatile("wgmma.commit_group.sync.aligned;\n" ::: "memory"); }
template <int N> __device__ __forceinline__ void wg_wait() {
    asm volatile("wgmma.wait_group.sync.aligned %0;\n" ::"n"(N) : "memory");
}
template <int R> __device__ __forceinline__ void reg_inc() { asm volatile("setmaxnreg.inc.sync.aligned.u32 %0;\n" ::"n"(R)); }
template <int R> __device__ __forceinline__ void reg_dec() { asm volatile("setmaxnreg.dec.sync.aligned.u32 %0;\n" ::"n"(R)); }
__device__ __forceinline__ void bar_sync(int id, int n) { asm volatile("bar.sync %0, %1;\n" ::"r"(id), "r"(n) : "memory"); }
__device__ __forceinline__ void bar_arrive(int id, int n) { asm volatile("bar.arrive %0, %1;\n" ::"r"(id), "r"(n) : "memory"); }

__device__ __forceinline__ uint64_t make_desc(uint32_t saddr, uint32_t lbo, uint32_t sbo) {
    return (uint64_t)((saddr & 0x3FFFF) >> 4) | ((uint64_t)(lbo >> 4) << 16) | ((uint64_t)(sbo >> 4) << 32);
}

__device__ __forceinline__ void stg128_cs(void* p, uint32_t a, uint32_t b, uint32_t c, uint32_t d) {
    asm volatile("st.global.cs.v4.u32 [%0], {%1,%2,%3,%4};\n" ::"l"(p), "r"(a), "r"(b), "r"(c), "r"(d) : "memory");
}
__device__ __forceinline__ uint32_t pack_bf16(float lo, float hi) {
    uint32_t r;
    asm("cvt.rn.bf16x2.f32 %0, %1, %2;\n" : "=r"(r) : "f"(hi), "f"(lo));
    return r;
}
__device__ __forceinline__ float bf_lo(uint32_t v) { return __uint_as_float(v << 16); }
__device__ __forceinline__ float bf_hi(uint32_t v) { return __uint_as_float(v & 0xffff0000u); }
__device__ __forceinline__ uint32_t bf2_mul(uint32_t a, uint32_t b) {
    uint32_t r;
    asm("mul.rn.bf16x2 %0, %1, %2;\n" : "=r"(r) : "r"(a), "r"(b));
    return r;
}
__device__ __forceinline__ uint32_t bf2_fma(uint32_t a, uint32_t b, uint32_t c) {
    uint32_t r;
    asm("fma.rn.bf16x2 %0, %1, %2, %3;\n" : "=r"(r) : "r"(a), "r"(b), "r"(c));
    return r;
}
__device__ __forceinline__ uint32_t bf2_add(uint32_t a, uint32_t b) {
    uint32_t r;
    asm("add.rn.bf16x2 %0, %1, %2;\n" : "=r"(r) : "r"(a), "r"(b));
    return r;
}
constexpr float KAPPA = 0.3292034911525734f;
constexpr float GELU_C = 2.423681954311584f;
constexpr float HSCALE = 1.0f / (2.0f * KAPPA);
__device__ __forceinline__ float acc_bound(float bias, float asum) { return fmaxf(asum, fabsf(bias) * 0.0625f); }
__device__ __forceinline__ uint32_t acc_exp(float z) { return max(__float_as_uint(z) >> 23, 10u); }
__device__ __forceinline__ void sched_break(int zero) {
    asm volatile("{\n.reg .pred p;\nsetp.ne.s32 p, %0, 0;\nSB_LOOP:\n@p nanosleep.u32 1;\n@p bra SB_LOOP;\n}\n" ::"r"(zero));
}

#define ACC8(d, o) "+f"(d[o + 0]), "+f"(d[o + 1]), "+f"(d[o + 2]), "+f"(d[o + 3]), "+f"(d[o + 4]), "+f"(d[o + 5]), "+f"(d[o + 6]), "+f"(d[o + 7])

#define ACCR8(d, o) "+r"(d[o + 0]), "+r"(d[o + 1]), "+r"(d[o + 2]), "+r"(d[o + 3]), "+r"(d[o + 4]), "+r"(d[o + 5]), "+r"(d[o + 6]), "+r"(d[o + 7])
__device__ __forceinline__ void mma_rs_n128(uint32_t (&d)[32], const uint32_t (&a)[4], uint64_t desc, int scale_d) {
    asm volatile(
        "{\n.reg .pred p;\nsetp.ne.b32 p, %37, 0;\n"
        "wgmma.mma_async.sync.aligned.m64n128k16.f16.f16.f16 "
        "{%0,%1,%2,%3,%4,%5,%6,%7,%8,%9,%10,%11,%12,%13,%14,%15,"
        "%16,%17,%18,%19,%20,%21,%22,%23,%24,%25,%26,%27,%28,%29,%30,%31},"
        "{%32,%33,%34,%35}, %36, p, 1, 1, 0;\n}\n"
        : ACCR8(d, 0), ACCR8(d, 8), ACCR8(d, 16), ACCR8(d, 24)
        : "r"(a[0]), "r"(a[1]), "r"(a[2]), "r"(a[3]), "l"(desc), "r"(scale_d));
}
__device__ __forceinline__ uint32_t bf2_as_h2(uint32_t v) { return (v & 0x0fff0fffu) * 7u + v; }
__device__ __forceinline__ float h_lo(uint32_t v) {
    float r;
    asm("{\n.reg .b16 l, h;\nmov.b32 {l, h}, %1;\ncvt.f32.f16 %0, l;\n}\n" : "=f"(r) : "r"(v));
    return r;
}
__device__ __forceinline__ float h_hi(uint32_t v) {
    float r;
    asm("{\n.reg .b16 l, h;\nmov.b32 {l, h}, %1;\ncvt.f32.f16 %0, h;\n}\n" : "=f"(r) : "r"(v));
    return r;
}

__device__ __forceinline__ void mma_rs_n192(uint32_t (&d)[48], const uint4& a, uint64_t db) {
    asm volatile(
        "{\n.reg .pred p;\nsetp.ne.b32 p, %53, 0;\n"
        "wgmma.mma_async.sync.aligned.m64n192k16.f16.f16.f16 "
        "{%0,%1,%2,%3,%4,%5,%6,%7,%8,%9,%10,%11,%12,%13,%14,%15,"
        "%16,%17,%18,%19,%20,%21,%22,%23,%24,%25,%26,%27,%28,%29,%30,%31,"
        "%32,%33,%34,%35,%36,%37,%38,%39,%40,%41,%42,%43,%44,%45,%46,%47},"
        "{%48,%49,%50,%51}, %52, p, 1, 1, 0;\n}\n"
        : ACCR8(d, 0), ACCR8(d, 8), ACCR8(d, 16), ACCR8(d, 24), ACCR8(d, 32), ACCR8(d, 40)
        : "r"(a.x), "r"(a.y), "r"(a.z), "r"(a.w), "l"(db), "r"(1));
}

__device__ __forceinline__ void mma_ss_n192_init(uint32_t (&d)[48], uint64_t da, uint64_t db) {
    asm volatile(
        "{\n.reg .pred p;\nsetp.ne.b32 p, %50, 0;\n"
        "wgmma.mma_async.sync.aligned.m64n192k16.f16.f16.f16 "
        "{%0,%1,%2,%3,%4,%5,%6,%7,%8,%9,%10,%11,%12,%13,%14,%15,"
        "%16,%17,%18,%19,%20,%21,%22,%23,%24,%25,%26,%27,%28,%29,%30,%31,"
        "%32,%33,%34,%35,%36,%37,%38,%39,%40,%41,%42,%43,%44,%45,%46,%47},"
        "%48, %49, p, 1, 1, 0, 0;\n}\n"
        : ACCR8(d, 0), ACCR8(d, 8), ACCR8(d, 16), ACCR8(d, 24), ACCR8(d, 32), ACCR8(d, 40)
        : "l"(da), "l"(db), "r"(0));
}
__device__ __forceinline__ uint32_t pack_f16(float lo, float hi) {
    uint32_t r;
    asm("cvt.rn.f16x2.f32 %0, %1, %2;\n" : "=r"(r) : "f"(hi), "f"(lo));
    return r;
}

#define P1_REGS 192
#define P1_WARM 0
#define P1_DEF 3
#define P1_DMID 0
#define P1_ARR 23
constexpr int P1_SLOT = LN_TILE / 2, P1_NST = 4;
constexpr int P1_X = 32 * C_DIM * 2;
constexpr int P1_OFF_X = P1_SLOT * P1_NST;
constexpr int P1_OFF_BAR = P1_OFF_X + P1_X;
constexpr int P1_OFF_TILE = P1_OFF_BAR + (2 * P1_NST + 2 + 4) * 8;
constexpr int P1_OFF_RAW = P1_OFF_TILE + 64;
constexpr int P1_OFF_DW = P1_OFF_RAW + 32;
constexpr int P1_SMEM = P1_OFF_DW + C_DIM * 2;

__device__ __forceinline__ float rsqrt_fast(float x) {
    float r;
    asm("rsqrt.approx.ftz.f32 %0, %1;\n" : "=f"(r) : "f"(x));
    return r;
}
__device__ __forceinline__ float row_sum(const uint32_t (&c)[4]) {
    const uint32_t u = bf2_add(bf2_add(c[0], c[1]), bf2_add(c[2], c[3]));
    float s = bf_lo(u) + bf_hi(u);
#pragma unroll
    for (int o = 1; o < 8; o <<= 1) s += __shfl_xor_sync(0xffffffffu, s, o);
    return s;
}
__device__ __forceinline__ void ln_row(uint32_t (&v)[6][4], const uint32_t (&d)[6][4], int zero, uint32_t bar_read) {
    uint32_t c[4];
#pragma unroll
    for (int i = 0; i < 6; i++)
#pragma unroll
        for (int k = 0; k < 4; k++) c[k] = bf2_fma(v[i][k], d[i][k], i ? c[k] : 0);
    const float inv = 1.0f / C_DIM;
    const float m = row_sum(c) * inv;
    const uint32_t nm = pack_bf16(-m, -m);
    const float e = m + bf_lo(nm);
    if (bar_read) mbar_arrive(bar_read + (nm & zero));
#pragma unroll
    for (int i = 0; i < 6; i++) {
#pragma unroll
        for (int k = 0; k < 4; k++) {
            v[i][k] = bf2_fma(v[i][k], d[i][k], nm);
            c[k] = i ? bf2_fma(v[i][k], v[i][k], c[k]) : bf2_mul(v[i][k], v[i][k]);
        }
    }
    float r = KAPPA * rsqrt_fast(fmaxf(fmaf(-e, e, row_sum(c) * inv), 0.f) + 1e-5f);
    const uint32_t sh = pack_bf16(-e * r * 0x1p-112f, -e * r * 0x1p-112f);
    if (__any_sync(0xffffffffu, r < 0x1p-14f)) {
        const uint32_t f = r < 0x1p-14f ? 0x23802380u : 0x3f803f80u;
        if (r < 0x1p-14f) r *= 0x1p56f;
#pragma unroll
        for (int i = 0; i < 6; i++)
#pragma unroll
            for (int k = 0; k < 4; k++) v[i][k] = bf2_mul(v[i][k], f);
    }
    const uint32_t rs = pack_bf16(r * 0x1p-112f, r * 0x1p-112f);
#pragma unroll
    for (int i = 0; i < 6; i++)
#pragma unroll
        for (int k = 0; k < 4; k++) v[i][k] = bf2_as_h2(bf2_fma(v[i][k], rs, sh));
}

__device__ __forceinline__ void load_dw(uint32_t (&d)[6][4], uint32_t sbase, int lane) {
    mbar_wait(sbase + P1_OFF_RAW + 16, 0);
#pragma unroll
    for (int j = 0; j < 6; j++)
        asm volatile("ld.shared.v4.u32 {%0,%1,%2,%3}, [%4];\n" : "=r"(d[j][0]), "=r"(d[j][1]), "=r"(d[j][2]), "=r"(d[j][3])
                     : "r"(sbase + P1_OFF_DW + j * 128 + (lane & 7) * 16) : "memory");
}

__device__ __forceinline__ float gelu_s(float y) {
    float u = y * fmaf(y, y, GELU_C);
    float t;
    asm volatile("tanh.approx.f32 %0, %1;\n" : "=f"(t) : "f"(u));
    return fmaf(y, t, y);
}
__device__ __forceinline__ constexpr int p1_reg(int c, int u) { return 16 * (c >> 1) + 4 * (u >> 1) + 2 * (c & 1) + (u & 1); }
template <bool BIG>
__device__ __forceinline__ void p1_pack(int c, uint32_t (&p)[4], uint32_t (&dd)[4], uint32_t (&sq)[4], uint32_t sc2) {
    uint32_t& s = sq[(c >> 2) * 2 + (c & 1)];
    s = (c & 2) ? bf2_fma(p[0], p[0], s) : bf2_mul(p[0], p[0]);
    s = bf2_fma(p[3], p[3], bf2_fma(p[2], p[2], bf2_fma(p[1], p[1], s)));
#pragma unroll
    for (int u = 0; u < 4; u++) {
        uint32_t v;
        if (c & 1) asm("{\n.reg .b16 l, h;\n.reg .b32 f;\nmov.b32 {l, h}, %2;\nmov.b32 f, {h, h};\nmul.rn.bf16x2 %0, %1, f;\n}\n" : "=r"(v) : "r"(p[u]), "r"(sc2));
        else asm("{\n.reg .b16 l, h;\n.reg .b32 f;\nmov.b32 {l, h}, %2;\nmov.b32 f, {l, l};\nmul.rn.bf16x2 %0, %1, f;\n}\n" : "=r"(v) : "r"(p[u]), "r"(sc2));
        if (BIG) v = bf2_mul(v, 0x07800780u);
        if ((c & 3) == 0) dd[u] = v;
        else {
            uint32_t n = dd[u];
            if ((c & 3) == 1) { n <<= 4; dd[u] = __byte_perm(dd[u], 0, 0x2301); }
            if ((c & 3) == 2) dd[u] <<= 4;
            asm("lop3.b32 %0, %1, %2, 0x78007800, 0xd8;\n" : "=r"(p[u]) : "r"(v), "r"(n));
        }
    }
}
__device__ __forceinline__ void p1_store(int c, const uint32_t (&p)[4], uint8_t* hptr) {
    if (c & 3) stg128_cs(hptr + (c >> 2) * H_HALF + ((c & 3) - 1) * 512, p[0], p[1], p[2], p[3]);
}

__device__ __forceinline__ uint32_t p1_parity(uint32_t sbase) {
    uint32_t v;
    asm volatile("ld.shared.u32 %0, [%1];\n" : "=r"(v) : "r"(sbase + P1_OFF_TILE - 4) : "memory");
    return v;
}
template <bool GEN>
__device__ __forceinline__ uint32_t gelu2(uint32_t y, float fs) {
    if (GEN) return pack_bf16(gelu_s(h_lo(y) * fs), gelu_s(h_hi(y) * fs));
    uint32_t g;
    asm("{\n.reg .b32 w;\n"
        "fma.rn.f16x2 w, %1, %1, %2;\n"
        "mul.rn.f16x2 w, w, %1;\n"
        "tanh.approx.f16x2 w, w;\n"
        "fma.rn.f16x2 %0, %1, w, %1;\n}\n" : "=r"(g) : "r"(y), "r"(0x40d940d9u));
    return pack_bf16(h_lo(g), h_hi(g));
}
template <bool GEN, int C0, int C1, class F>
__device__ __forceinline__ void p1_epilogue(F v, uint32_t (&sq)[4], uint32_t (&dd)[4], float (&ssq)[2], uint32_t sc2, uint8_t* hp) {
    const float fs[2] = {__uint_as_float(0x78000000u - (sc2 << 16)), __uint_as_float(0x78000000u - (sc2 & 0xffff0000u))};
#pragma unroll
    for (int c = C0; c < C1; c++) {
        uint32_t p[4];
#pragma unroll
        for (int u = 0; u < 4; u++) p[u] = gelu2<GEN>(v(c, u), fs[c & 1]);
        p1_pack<GEN>(c, p, dd, sq, sc2);
        p1_store(c, p, hp);
    }
    if (C1 == 8) {
#pragma unroll
        for (int r = 0; r < 2; r++) {
            const uint32_t u = bf2_add(sq[r], sq[2 + r]);
            ssq[r] += bf_lo(u) + bf_hi(u);
        }
    }
}
__device__ __forceinline__ void p1_consumer(const uint32_t (&a)[24][4], uint32_t sc2, bool gen, uint32_t sbase, int wg, int w, int lane) {
    const uint32_t bar_full = sbase + P1_OFF_BAR, bar_empty = bar_full + P1_NST * 8;
    const uint32_t empty_remote = mapa(bar_empty, lane & 1);
    const int g = lane >> 2, q = lane & 3, cb = (blockIdx.x % GRP_CTAS) * 2 + wg;
    float ssq[2] = {0.f, 0.f};
    uint32_t acc[32], sq[4] = {}, dd[4] = {}, dfr[P1_DEF * 4 + 1] = {};
    auto from_acc = [&](int c, int u) { return acc[8 * (c >> 1) + 2 * u + (c & 1)]; };
    auto from_dfr = [&](int c, int u) { return dfr[(c - 8 + P1_DEF) * 4 + u]; };
    bool pend = false;
    TSTAMP(0, 1);

    uint8_t* hp = reinterpret_cast<uint8_t*>(g_h) + (size_t)(blockIdx.x / GRP_CTAS) * (2 * H_TILE) + ((cb * 2 + (w >> 1)) * H_STEP + (w & 1) * 1536) + g * 64 + (q ^ (g >> 1)) * 16;
    const uint64_t desc_base = make_desc(sbase, 16, 1024) | (1ull << 62);
#pragma unroll 1
    for (int i = 0;; i++) {
        const int s0 = (i & 1) * 16, par = (i >> 1) & 1;
        const uint64_t d0 = desc_base + (uint64_t)((i & 1) * (LN_TILE / 16));
        TRACE(wg, i, 0);
        mbar_wait(bar_full + s0, par);
        bar_sync(1 + wg, 256);
        TRACE(wg, i, 1);
        uint32_t step, more;
        wg_fence();
#pragma unroll
        for (int k = 0; k < 24; k++) {
            if (k == 12) mbar_wait(bar_full + s0 + 8, par);
            mma_rs_n128(acc, a[k], d0 + (uint64_t)((k >> 2) * 1024 + (k & 3) * 2), k != 0);
            if (k == P1_ARR) bar_arrive(2 - wg, 256);
            if (k % 12 == 11) wg_commit();
            if (P1_DMID && k == 11 && pend) p1_epilogue<false, 8 - P1_DEF, 8 - P1_DEF + P1_DMID>(from_dfr, sq, dd, ssq, sc2, hp);
        }
        asm volatile("ld.shared.v2.u32 {%0, %1}, [%2];\n" : "=r"(step), "=r"(more) : "r"(sbase + P1_OFF_TILE + (i & 3) * 16) : "memory");
        TRACE(wg, i, 2);
        wg_wait<1>();
        if (lane < 2) mbar_arrive_cluster(empty_remote + s0);
        if (P1_DEF > P1_DMID && pend) p1_epilogue<false, 8 - P1_DEF + P1_DMID, 8>(from_dfr, sq, dd, ssq, sc2, hp);
        hp += step;
        TRACE(wg, i, 3);
        wg_wait<0>();
        TRACE(wg, i, 4);
        if (lane < 2) mbar_arrive_cluster(empty_remote + s0 + 8);
        if (gen) p1_epilogue<true, 0, 8>(from_acc, sq, dd, ssq, sc2, hp);
        else {
#pragma unroll
            for (int j = 0; j < P1_DEF * 4; j++) asm volatile("mov.b32 %0, %1;\n" : "=r"(dfr[j]) : "r"(from_acc(8 - P1_DEF + j / 4, j % 4)));
            p1_epilogue<false, 0, 8 - P1_DEF>(from_acc, sq, dd, ssq, sc2, hp);
            pend = true;
        }
        if (!more) break;
    }
    if (P1_DEF && pend) p1_epilogue<false, 8 - P1_DEF, 8>(from_dfr, sq, dd, ssq, sc2, hp);
    TSTAMP(0, 21);
    if (wg == 0) bar_sync(1, 256);
#pragma unroll
    for (int r = 0; r < 2; r++) {
        ssq[r] += __shfl_xor_sync(0xffffffffu, ssq[r], 1);
        ssq[r] += __shfl_xor_sync(0xffffffffu, ssq[r], 2);
        if (q == 0) atomicAdd(&g_sums[p1_parity(sbase)][cb * 64 + w * 16 + r * 8 + g], ssq[r]);
    }
}

__global__ void __cluster_dims__(2, 1, 1) __launch_bounds__(512, 1)
pass1_kernel(const __grid_constant__ CUtensorMap wmap, const __nv_bfloat16* __restrict__ x, const __nv_bfloat16* __restrict__ dw,
             const __nv_bfloat16* __restrict__ w2, const __nv_bfloat16* __restrict__ grn_b, int zero) {
    extern __shared__ __align__(1024) uint8_t smem[];
    const uint32_t sbase = smem_u32(smem);
    const uint32_t bar_full = sbase + P1_OFF_BAR, bar_empty = bar_full + P1_NST * 8, bar_w = bar_empty + P1_NST * 8;
    const int tid = threadIdx.x;
    const int warp = __shfl_sync(0xffffffffu, tid >> 5, 0), lane = tid & 31;
    const uint32_t rank = cluster_rank();
    const int cig = blockIdx.x % GRP_CTAS;
    uint8_t* const ring = reinterpret_cast<uint8_t*>(g_ln);

    TSTAMP(0, 0);
    TRACEW(110 + warp, 0);
    const uint32_t bar_xfull = bar_w + 16, bar_xempty = bar_xfull + 8, bar_done = bar_xfull + 16;
    const uint32_t bar_raw = sbase + P1_OFF_RAW;
    const int ln0 = blockIdx.x >> 2, first = blockIdx.x / GRP_CTAS;
    const uint8_t* xsrc = reinterpret_cast<const uint8_t*>(x) + (size_t)(NGRP * 4 + blockIdx.x) * P1_X;

    if (warp >= 12) {
        reg_dec<40>();
        asm volatile("barrier.cluster.arrive.relaxed.aligned;\n" ::: "memory");
        asm volatile("barrier.cluster.wait.aligned;\n" ::: "memory");
        if (warp == 12) {
            int prev = first - NGRP, t = first, next = t + NGRP;
            const uint32_t rbase = mapa(sbase, lane & 1);
#pragma unroll 1
            for (int i = 1; t < NT_RING; i++) {
                const int s0 = (i & 1) * 2, par = ((i + 1) >> 1 & 1) ^ 1;
                const int round = t / LN_RING, slot = t - round * LN_RING;
                const uint8_t* src = ring + slot * LN_TILE + rank * (P1_SLOT / 2);
                int draw = 0;
                if (rank == 0 && lane == 0) draw = atomicAdd(&g_flag[LN_RING + (cig >> 2)][(cig >> 1) & 1][0], 1u);
                flag_wait<true>(&g_flag[slot][0][0], 4 * round + 4);
                TRACEW(i, 2);
                asm volatile("fence.proxy.async.global;\n" ::: "memory");
                draw = 2 * NGRP + __shfl_sync(0xffffffffu, draw, 0);
#pragma unroll
                for (int h = 0; h < 2; h++) {
                    mbar_wait(bar_empty + (s0 + h) * 8, par);
                    TRACEW(i, 4 + h);
                    if (elect_one()) {
                        mbar_expect_tx(bar_full + (s0 + h) * 8, P1_SLOT + 16 - 16 * h);
                        bulk_g2s_mc(sbase + (s0 + h) * P1_SLOT + rank * (P1_SLOT / 2), src + h * P1_SLOT, P1_SLOT / 2, bar_full + (s0 + h) * 8, (uint16_t)3);
                    }
                    __syncwarp();
                    if (h == 0 && rank == 0 && lane < 2)
                        asm volatile("st.async.shared::cluster.mbarrier::complete_tx::bytes.v4.u32 [%0], {%1, %2, %3, %3}, [%4];\n"
                                     ::"r"(rbase + P1_OFF_TILE + (i & 3) * 16), "r"((t - prev) * (2 * H_TILE)), "r"((int)(next < NT_RING)), "r"(draw),
                                       "r"(rbase + P1_OFF_BAR + s0 * 8) : "memory");
                }
                prev = t;
                t = next;
                next = draw;
                if (rank != 0) {
                    mbar_wait(bar_full + (s0 ^ 2) * 8, ((i - 1) >> 1) & 1);
                    asm volatile("ld.shared.u32 %0, [%1];\n" : "=r"(t) : "r"(sbase + P1_OFF_TILE + ((i - 1) & 3) * 16 + 8) : "memory");
                }
            }
        } else if (warp == 13) {
            int ph = 0;
            unsigned target = 0;
#pragma unroll 1
            for (int i = ln0 + LN_STEP; i < NT_RING; i += LN_STEP, ph ^= 1) {
                target += ph * (GRP_CTAS / 2);
                xsrc += (size_t)NUM_CTAS * P1_X;
                mbar_wait(bar_xempty, ph);
                if (elect_one()) {
                    mbar_expect_tx(bar_xfull, P1_X);
                    bulk_g2s(sbase + P1_OFF_X, xsrc, P1_X, bar_xfull);
                }
                __syncwarp();
                flag_wait<false>(&g_flag[ln0 + (ph ^ 1) * LN_STEP][1][0], target);
                mbar_wait(bar_done, ph);
                if (elect_one()) mbar_arrive(bar_xfull);
                __syncwarp();
            }
        } else if (warp == 15) {
            if (rank == 1 && lane < 2) mbar_arrive(bar_empty + (2 + lane) * 8);
            const uint32_t par = g_epoch & 1;
            asm volatile("st.shared.u32 [%0], %1;\n" ::"r"(sbase + P1_OFF_TILE - 4), "r"(par) : "memory");
            if (blockIdx.x == 18) g_par = par;
            if (blockIdx.x < 18) reinterpret_cast<float4*>(g_sums[par ^ 1])[blockIdx.x * 32 + lane] = make_float4(0.f, 0.f, 0.f, 0.f);
            bar_arrive(3, 160);
            {
                bar_sync(4, 288);
                mbar_wait(bar_raw + 8, 0);
                const uint32_t o = lane * 16384 + rank * 8192, peer = mapa(sbase, rank ^ 1);
                if (lane < 6)
                    asm volatile("cp.async.bulk.shared::cluster.shared::cta.mbarrier::complete_tx::bytes [%0], [%1], 8192, [%2];\n"
                                 ::"r"(peer + o), "r"(sbase + o), "r"(peer + P1_OFF_BAR + (lane >= 3 ? 8 : 0)) : "memory");
                __syncwarp();
            }
            if (rank == 0) {
                flag_wait<true>(&g_flag[40][1][0], GRP_CTAS / 2);
                const int col = (cig >> 1) * 64 + lane * 2;
                float bsum[2] = {0.f, 0.f}, asum[2] = {0.f, 0.f};
#pragma unroll 2
                for (int k = first * 140; k < min(first * 140 + 140, HID); k++) {
                    const uint32_t v = *reinterpret_cast<const uint32_t*>(w2 + k * C_DIM + col);
                    const float b = __bfloat162float(grn_b[k]), f = __uint_as_float(__ldcg(&g_ex[k]) << 23);
                    bsum[0] = fmaf(b, bf_lo(v), bsum[0]);
                    bsum[1] = fmaf(b, bf_hi(v), bsum[1]);
                    asum[0] = fmaf(f, fabsf(bf_lo(v)), asum[0]);
                    asum[1] = fmaf(f, fabsf(bf_hi(v)), asum[1]);
                }
                float* sums = g_sums[par] + HID + perm32(col);
#pragma unroll
                for (int j = 0; j < 2; j++) {
                    atomicAdd(sums + j, bsum[j]);
                    atomicAdd(sums + C_DIM + j, asum[j]);
                }
                __threadfence();
                __syncwarp();
                if (lane == 0) asm volatile("red.release.gpu.global.add.u32 [%0], 1;\n" ::"l"(&g_flag[LN_RING + 3][0][0]) : "memory");
            }
            int t = first, next = t + NGRP;
            if (rank == 1) {
                mbar_wait(bar_full, 0);
                mbar_wait(bar_full + 8, 0);
                if (lane < 2) mbar_arrive(bar_empty + lane * 8);
            }
#pragma unroll 1
            for (int i = 1; rank == 1 && t < NT_RING; i++) {
                const int s0 = (i & 1) * 16;
                mbar_wait(bar_full + s0, (i >> 1) & 1);
                mbar_wait(bar_full + s0 + 8, (i >> 1) & 1);
                if (lane == 0) asm volatile("red.relaxed.gpu.global.add.u32 [%0], 1;\n" ::"l"(&g_flag[t % LN_RING][1][0]) : "memory");
                t = next;
                asm volatile("ld.shared.u32 %0, [%1];\n" : "=r"(next) : "r"(sbase + P1_OFF_TILE + (i & 3) * 16 + 8) : "memory");
                if (lane < 2) mbar_arrive(bar_empty + s0 + lane * 8);
                TRACEW(i, 3);
            }
        } else if (warp == 14) {
            int ph = 0;
#pragma unroll 1
            for (int i = ln0; i < NT_RING; i += LN_STEP, ph ^= 1) {
                mbar_wait(bar_done, ph);
                TRACEW(i / LN_STEP, 0);
                asm volatile("fence.proxy.async.global;\n" ::: "memory");
                if (elect_one()) asm volatile("red.release.gpu.global.add.u32 [%0], 1;\n" ::"l"(&g_flag[ln0 + ph * LN_STEP][0][0]) : "memory");
                __syncwarp();
                TRACEW(i / LN_STEP, 1);
            }
        }
        __syncwarp();
        cluster_sync();
    } else if (warp >= 8) {
        reg_dec<88>();
        asm volatile("barrier.cluster.arrive.relaxed.aligned;\n" ::: "memory");
        {
            const int l8 = lane & 7, row = (warp - 8) * 4 + (lane >> 3), px = (blockIdx.x & 3) * 32 + row;
            uint32_t d[6][4] = {};
            const int n = (px & 64) + perm32(2 * row + ((px >> 5) & 1));
            uint8_t* const dst0 = ring + ln0 * LN_TILE + n * 128 + ((l8 ^ (n & 7)) << 4);
            const uint32_t src = sbase + P1_OFF_X + ((warp - 8) * 8 + (lane >> 3)) * (C_DIM * 2) + l8 * 16;
            int ph = 0;
            asm volatile("barrier.cluster.wait.aligned;\n" ::: "memory");
#pragma unroll 1
            for (int i = ln0; i < NT_RING; i += LN_STEP, ph ^= 1) {
                TRACE(2, i / LN_STEP, 0);
#pragma unroll 1
                for (int ps = i == ln0 ? -1 : 0; ps < 2; ps++) {
                    if (ps == 0) {
                        if (i == ln0) load_dw(d, sbase, lane);
                        mbar_wait(bar_xfull, ph);
                        TRACE(2, i / LN_STEP, 1);
                    }
                    uint32_t v[6][4];
#pragma unroll
                    for (int j = 0; j < 6; j++)
                        asm volatile("ld.shared.v4.u32 {%0,%1,%2,%3}, [%4];\n"
                                     : "=r"(v[j][0]), "=r"(v[j][1]), "=r"(v[j][2]), "=r"(v[j][3]) : "r"(src + (ps & 1) * (4 * C_DIM * 2) + j * 128) : "memory");
                    ln_row(v, d, zero, ps == 1 && lane == 0 ? bar_xempty : 0);
                    uint8_t* dst = dst0 + ph * (LN_STEP * LN_TILE) + ps * 4096;
#pragma unroll
                    for (int j = 0; j < 6; j++)
                        asm volatile("{\n.reg .pred p;\nsetp.ge.s32 p, %5, 0;\n@p st.global.v4.u32 [%0], {%1,%2,%3,%4};\n}\n"
                                     ::"l"(dst + j * 16384), "r"(v[j][0]), "r"(v[j][1]), "r"(v[j][2]), "r"(v[j][3]), "r"(ps) : "memory");
                    TRACE(2, i / LN_STEP, 3 + (ps & 1));
                }
                asm volatile("fence.proxy.async.global;\nfence.acq_rel.cta;\n" ::: "memory");
                __syncwarp();
                if (lane == 0) mbar_arrive(bar_done);
                TRACE(2, i / LN_STEP, 5);
                TRACE(2, i / LN_STEP, 2);
            }
        }
        const int gw = (warp - 8) * NUM_CTAS + blockIdx.x;
        bar_sync(3, 160);
        if (gw < 288) {
            const int np = (gw % 12) * 32 + lane, kb = gw / 12;
            const __nv_bfloat16* wc = w2 + (size_t)kb * 64 * C_DIM + perm32(np);
            const float* sums = g_sums[p1_parity(sbase)] + HID;
            flag_wait<true>(&g_flag[LN_RING + 3][0][0], NUM_CTAS / 2);
            float z = 0.f;
#pragma unroll
            for (int j = 0; j < C_DIM / 32; j++) z = fmaxf(z, acc_bound(__ldcg(sums + j * 32 + lane), __ldcg(sums + C_DIM + j * 32 + lane)));
            const float sc = __uint_as_float((263u - acc_exp(__uint_as_float(__reduce_max_sync(0xffffffffu, __float_as_uint(z))))) << 23);
#pragma unroll 2
            for (int c = 0; c < 8; c++) {
                float f[8];
#pragma unroll
                for (int e = 0; e < 8; e++)
                    f[e] = __bfloat162float(wc[(c * 8 + e) * C_DIM]) * __uint_as_float(__ldcg(&g_ex[kb * 64 + c * 8 + e]) << 23) * sc;
                g_w2img[(((kb * 4 + (c >> 1)) * 48 + (np >> 3)) * 2 + (c & 1)) * 8 + (np & 7)] =
                    make_uint4(pack_f16(f[0], f[1]), pack_f16(f[2], f[3]), pack_f16(f[4], f[5]), pack_f16(f[6], f[7]));
            }
            asm volatile("fence.proxy.async.global;\n" ::: "memory");
            __threadfence();
            __syncwarp();
            if (lane == 0) asm volatile("red.release.gpu.global.add.u32 [%0], 1;\n" ::"l"(&g_img) : "memory");
        }
        __syncwarp();
        cluster_sync();
    } else {
        if (tid == 0) {
            mbar_init(bar_raw, 1);
            mbar_init(bar_raw + 8, 8);
            asm volatile("fence.mbarrier_init.release.cluster;\n" ::: "memory");
            mbar_expect_tx(bar_raw, P1_SLOT);
            for (int i = 0; i < 6; i++)
                bulk_g2s(sbase + i * 16384 + (rank ^ 1) * 8192, x + (size_t)(first * 128 + rank * 64) * C_DIM + i * 4096, 8192, bar_raw);
        }
        if (tid == 32) {
            mbar_init(bar_raw + 16, 1);
            mbar_init(bar_xfull, 2);
            mbar_init(bar_xempty, 4);
            mbar_init(bar_done, 4);
            asm volatile("fence.mbarrier_init.release.cluster;\n" ::: "memory");
            mbar_expect_tx(bar_raw + 16, C_DIM * 2);
            bulk_g2s(sbase + P1_OFF_DW, dw, C_DIM * 2, bar_raw + 16);
            mbar_expect_tx(bar_xfull, P1_X);
            bulk_g2s(sbase + P1_OFF_X, xsrc, P1_X, bar_xfull);
            mbar_arrive(bar_xfull);
        }
        if (tid == 64) {
            asm volatile("st.shared.v4.u32 [%0], {0, 1, %1, %1};\n" ::"r"(sbase + P1_OFF_TILE), "r"(first + NGRP) : "memory");
            for (int i = 0; i < P1_NST; i++) {
                mbar_init(bar_full + i * 8, 1);
                mbar_init(bar_empty + i * 8, 16 + rank);
                if (i < 2) mbar_expect_tx(bar_full + i * 8, P1_SLOT / 2);
            }
            asm volatile("fence.mbarrier_init.release.cluster;\n" ::: "memory");
            if (blockIdx.x < 64) (&g_half[0][0])[blockIdx.x] = 0;
            else if (blockIdx.x == 64) g_prog = 0;
            else if (blockIdx.x == 65) g_img = 0;
        }
        if (tid == 96) {
            for (int i = 0; i < 2; i++) mbar_init(bar_w + i * 8, 1);
            asm volatile("fence.mbarrier_init.release.cluster;\n" ::: "memory");
        }
        __syncwarp();
        asm volatile("barrier.cluster.arrive.relaxed.aligned;\n" ::: "memory");
        if (tid == 96)
            for (int i = 0; i < 2; i++) {
                mbar_expect_tx(bar_w + i * 8, P1_SLOT);
                tma2(sbase + (2 + i) * P1_SLOT, &wmap, cig * 128 + i * 64, 0, bar_w + i * 8);
                tma2(sbase + (2 + i) * P1_SLOT + P1_SLOT / 2, &wmap, cig * 128 + i * 64, 192, bar_w + i * 8);
            }
        __syncwarp();
        reg_inc<P1_REGS>();
        TRACEW(110 + warp, 1);
        const int wg = warp >> 2, w = warp & 3;
        uint32_t a[24][4], ex[2], gen;
        const uint32_t wsrc = sbase + (2 + wg) * P1_SLOT + ((lane >> 4) * 8 + (lane & 7)) * 128 + (((2 * w + ((lane >> 3) & 1)) ^ (lane & 7)) << 4);
        gdc_launch();
        asm volatile("barrier.cluster.wait.aligned;\n" ::: "memory");
#pragma unroll 1
        for (int it = P1_WARM ? 1 - wg : 1; it < 2; it++) {
            if (it) {
                const int n = warp * 8 + (lane >> 3), px = (n & 1) * 32 + (n >> 5) * 4 + ((n >> 1) & 1) * 8 + ((n >> 3) & 3);
                uint32_t d[6][4] = {};
#pragma unroll 1
                for (int ps = P1_WARM ? wg - 1 : -1; ps < 2; ps++) {
                    if (ps == 0) {
                        load_dw(d, sbase, lane);
                        mbar_wait(bar_raw, 0);
                    }
                    TRACEW(110 + warp, 2 + (ps == 0));
                    uint32_t v[6][4];
#pragma unroll
                    for (int j = 0; j < 6; j++) {
                        const uint32_t o = (px + (ps & 1) * 16) * (C_DIM * 2) + j * 128;
                        asm volatile("ld.shared.v4.u32 {%0,%1,%2,%3}, [%4];\n" : "=r"(v[j][0]), "=r"(v[j][1]), "=r"(v[j][2]), "=r"(v[j][3])
                                     : "r"(sbase + (rank ^ 1) * 8192 + (lane & 7) * 16 + o + (o & ~8191u)) : "memory");
                    }
                    ln_row(v, d, zero, 0);
                    const uint32_t p = sbase + (rank * 64 + n + (ps & 1) * 4) * 128 + (((lane ^ n ^ (ps & 1) * 4) & 7) << 4);
#pragma unroll
                    for (int j = 0; j < 6; j++)
                        asm volatile("st.shared.v4.u32 [%4], {%0,%1,%2,%3};\n"
                                     ::"r"(v[j][0]), "r"(v[j][1]), "r"(v[j][2]), "r"(v[j][3]), "r"(p + j * 16384) : "memory");
                }
                asm volatile("fence.proxy.async.shared::cta;\n" ::: "memory");
                __syncwarp();
                if (lane == 0) mbar_arrive_cluster(mapa(bar_raw + 8, rank ^ 1));
                bar_arrive(4, 288);
                if (wg == 1) bar_arrive(1, 256);
                TRACEW(110 + warp, 4);
                mbar_wait(bar_w + wg * 8, 0);
                TRACEW(110 + warp, 5);
            }
#pragma unroll
            for (int k = 0; k < 24; k++) ldsm4t(a[k], wsrc + k * 2048);
#pragma unroll
            for (int r = 0; r < 2; r++) {
                float t = 0.f;
#pragma unroll
                for (int j = 0; j < 6; j++) {
                    uint32_t c = bf2_mul(a[4 * j][r], a[4 * j][r]);
#pragma unroll
                    for (int k = 1; k < 8; k++) c = bf2_fma(a[4 * j + k / 2][r + (k & 1) * 2], a[4 * j + k / 2][r + (k & 1) * 2], c);
                    t += bf_lo(c) + bf_hi(c);
                }
                t += __shfl_xor_sync(0xffffffffu, t, 1);
                t += __shfl_xor_sync(0xffffffffu, t, 2);
                ex[r] = min(max(__float_as_uint(13.9f * __fsqrt_rn(t)) >> 23, 72u), 198u);
            }
            asm volatile("{\n.reg .pred p;\nsetp.gt.u32 p, %1, 16;\nbar.red.or.pred p, %2, 128, p;\nselp.u32 %0, 1, 0, p;\n}\n"
                         : "=r"(gen) : "r"(max(ex[0] - 125u, ex[1] - 125u)), "r"(5 + wg) : "memory");
            gen = __shfl_sync(0xffffffffu, gen, 0);
            if (gen) {
#pragma unroll
                for (int k = 0; k < 24; k++)
#pragma unroll
                    for (int j = 0; j < 4; j++) a[k][j] = bf2_mul(a[k][j], (268u - ex[j & 1]) * 0x00800080u);
            }
#pragma unroll
            for (int k = 0; k < 24; k++)
#pragma unroll
                for (int j = 0; j < 4; j++) {
                    a[k][j] = bf2_as_h2(bf2_mul(a[k][j], 0x07800780u));
                    asm volatile("" : "+r"(a[k][j]));
                }
            TRACEW(110 + warp, 6);
        }
        if ((lane & 3) < 2) g_ex[cig * 128 + wg * 64 + w * 16 + (lane & 1) * 8 + (lane >> 2)] = lane & 1 ? ex[1] : ex[0];
        if (lane < 4) mbar_arrive_cluster(mapa(bar_empty, lane & 1) + (2 + (lane >> 1)) * 8);
        TRACEW(110 + warp, 7);
        p1_consumer(a, (gen ? 0x7f007f00u : 0x47004700u) - ((ex[0] | ex[1] << 16) << 7), gen, sbase, wg, w, lane);
        cluster_sync();
        TSTAMP(0, 30);
    }
}

#define P2_NB_ 5
#define P2_NA_ 5
#define P2_DELTA_ 7
#define P2_EXTRA 0
#define P2_HSLEEP 64
#define P2_T0 5
#define P2_TS 11
constexpr int P2_B = 24576, P2_NB = P2_NB_;
constexpr int P2_A = 3072, P2_NA = P2_NA_;
constexpr int P2_XROW = C_DIM * 2;
constexpr int P2_OFF_A = P2_B * P2_NB;
constexpr int P2_OFF_X = P2_OFF_A + 3 * P2_NA * P2_A;
constexpr int P2_XHALF = 32 * P2_XROW + 64;
constexpr int P2_OFF_BIAS = P2_OFF_X + 64 * P2_XROW + 128;
constexpr int P2_OFF_ONES = P2_OFF_BIAS + 48 * 128;
constexpr int P2_OFF_GRN = P2_OFF_ONES + 256;
constexpr int P2_OFF_RED = P2_OFF_GRN + HID * 2;
constexpr int P2_OFF_BAR = P2_OFF_RED + 256;
constexpr int P2_SMEM = P2_OFF_BAR + (2 * P2_NB + 6 * P2_NA + 3) * 8;
constexpr int P2_LAG = 16;
constexpr int P2_NCL = NUM_CTAS / 2, P2_ITEMS = NT128 / P2_NCL, P2_SHARED = NT128 - P2_ITEMS * P2_NCL;
constexpr int P2_POS = P2_LAG * (P2_ITEMS + 2);
constexpr int P2_XC = 8 * P2_XROW;
constexpr int P2_DELTA = P2_DELTA_;
__device__ __forceinline__ int p2_tile(int cl, int n) {
    return n == 0 ? NT128 - 1 - cl : n < 0 || n == P2_ITEMS ? NT128 - 1 - P2_NCL - (cl >> 1) : cl + P2_NCL * (n - 1);
}

#define P2_EG 2
__device__ __forceinline__ void p2_epilogue(const uint32_t (&acc0)[48], const uint32_t (&acc1)[48], uint32_t sx, float up, int zero) {
    uint32_t v[2][P2_EG][4];
    auto load = [&](int c, uint32_t a) {
#pragma unroll
        for (int j = 0; j < P2_EG; j++) {
            const int u = c * P2_EG + j;
            asm volatile("ld.shared.v4.u32 {%0,%1,%2,%3}, [%4];\n" : "=r"(v[c & 1][j][0]), "=r"(v[c & 1][j][1]), "=r"(v[c & 1][j][2]), "=r"(v[c & 1][j][3])
                         : "r"(a + (u >> 1) * 64 + (u & 1) * 4 * P2_XROW) : "memory");
        }
    };
    load(0, sx);
#pragma unroll
    for (int c = 0; c < 24 / P2_EG; c++) {
        if (c + 1 < 24 / P2_EG) load(c + 1, sx + (v[c & 1][P2_EG - 1][0] & zero));
#pragma unroll
        for (int j = 0; j < P2_EG; j++) {
            const int u = c * P2_EG + j, i = 8 * ((u >> 1) % 6) + (u & 1);
            const uint32_t (&acc)[48] = u < 12 ? acc0 : acc1;
            uint32_t (&w)[4] = v[c & 1][j];
#pragma unroll
            for (int e = 0; e < 4; e++) w[e] = bf2_add(pack_bf16(h_lo(acc[i + 2 * e]) * up, h_hi(acc[i + 2 * e]) * up), w[e]);
            asm volatile("st.shared.v4.u32 [%4], {%0,%1,%2,%3};\n" ::"r"(w[0]), "r"(w[1]), "r"(w[2]), "r"(w[3]),
                         "r"(sx + (u >> 1) * 64 + (u & 1) * 4 * P2_XROW) : "memory");
        }
    }
}

__device__ __forceinline__ void p2_unpack(uint32_t (&u)[4], uint32_t o1, uint32_t o2, uint32_t o3) {
    u[2] = o1 & 0x87ff87ffu;
    u[1] = o2 & 0x87ff87ffu;
    u[3] = o3 & 0x87ff87ffu;
    u[0] = __byte_perm((o2 & 0x78007800u) | ((o3 >> 4) & 0x07800780u), 0, 0x2301) | ((o1 >> 4) & 0x07800780u);
}
__device__ __forceinline__ void p2_epilogue_add(const uint32_t (&acc)[48], uint8_t* o, float f, int zero) {
#pragma unroll
    for (int t = 0; t < 12; t++) {
        uint32_t v[4];
#pragma unroll
        for (int e = 0; e < 4; e++) {
            v[e] = acc[8 * (t >> 1) + (t & 1) + 2 * e];
            asm volatile("" : "+r"(v[e]));
            v[e] = pack_bf16(h_lo(v[e]) * f, h_hi(v[e]) * f);
        }
        asm volatile("red.global.add.noftz.v4.bf16x2 [%0], {%1,%2,%3,%4};\n" ::"l"(o + (t >> 1) * 64 + (t & 1) * 4 * P2_XROW),
                     "r"(v[0]), "r"(v[1]), "r"(v[2]), "r"(v[3]) : "memory");
        if (t % 3 == 2) sched_break(zero);
    }
}

__global__ void __cluster_dims__(2, 1, 1) __launch_bounds__(512, 1)
pass2_kernel(const __nv_bfloat16* __restrict__ x, const __nv_bfloat16* __restrict__ grn_g, __nv_bfloat16* __restrict__ out, int zero) {
    extern __shared__ __align__(1024) uint8_t smem[];
    const uint32_t sbase = smem_u32(smem);
    const uint32_t bar_bfull = sbase + P2_OFF_BAR, bar_bempty = bar_bfull + P2_NB * 8;
    const uint32_t bar_afull = bar_bempty + P2_NB * 8, bar_aempty = bar_afull + 3 * P2_NA * 8;
    const uint32_t bar_xfull = bar_aempty + 3 * P2_NA * 8, bar_oready = bar_xfull + 8, s_pos = bar_xfull + 16;
    int tid;
    asm volatile("mov.u32 %0, %%tid.x;\n" : "=r"(tid));
    const int warp = __shfl_sync(0xffffffffu, tid >> 5, 0), lane = tid & 31;
    const uint32_t rank = cluster_rank();
    const int cl = blockIdx.x >> 1, pair = cl >> 1;
    const int k0 = (4 * pair + (cl & 1) * 32) % 48;
    const int head = pair < P2_SHARED && !(cl & 1), tail = pair < P2_SHARED && (cl & 1);

    uint32_t par, gg[4];
    float pre[4];
    if (warp < 12) {
        asm volatile("ld.global.cg.u32 %0, [%1];\n" : "=r"(par) : "l"(&g_par) : "memory");
#pragma unroll
        for (int i = 0; i < 4; i++) {
            asm volatile("ld.global.cg.f32 %0, [%1];\n" : "=f"(pre[i]) : "l"(&g_sums[i & 1][HID + (i >> 1) * C_DIM + tid]) : "memory");
            asm volatile("ld.global.nc.u16 %0, [%1];\n" : "=r"(gg[i]) : "l"(grn_g + tid + 384 * i) : "memory");
        }
    }
    TSTAMP(1, 0);
    if (tid == 384) {
        for (int i = 0; i < P2_NB; i++) {
            mbar_init(bar_bfull + i * 8, 1);
            mbar_init(bar_bempty + i * 8, 24);
        }
        for (int i = 0; i < 3 * P2_NA; i++) {
            mbar_init(bar_afull + i * 8, 1);
            mbar_init(bar_aempty + i * 8, 4);
        }
        mbar_init(bar_xfull, 2);
        mbar_init(bar_oready, 4);
        asm volatile("st.shared.u32 [%0], 0;\n" ::"r"(s_pos) : "memory");
        asm volatile("fence.mbarrier_init.release.cluster;\n" ::: "memory");
    }
    __syncthreads();
    cluster_sync_relaxed();

    if (warp >= 12) {
        reg_dec<32>();
        if (warp == 12) {
            const uint8_t* wsrc = reinterpret_cast<const uint8_t*>(g_w2img) + rank * (P2_B / 2);
            int st = 0, ph = 1, kb = k0;
            const int busy = head ? 0 : tail ? P2_POS - 24 : P2_POS;
            flag_wait<true>(&g_img, 288);
            asm volatile("fence.proxy.async.global;\n" ::: "memory");
#pragma unroll 1
            for (int p = 0; p < P2_POS; p++) {
                mbar_wait(bar_bempty + st * 8, ph);
                TR2P(p, 0);
                if (elect_one()) {
                    mbar_expect_tx(bar_bfull + st * 8, P2_B);
                    bulk_g2s_mc(sbase + st * P2_B + rank * (P2_B / 2), wsrc + kb * P2_B, P2_B / 2, bar_bfull + st * 8, (uint16_t)3);
                    asm volatile("st.volatile.shared.u32 [%0], %1;\n" ::"r"(s_pos), "r"(p) : "memory");
                    const int idle = ((unsigned)(p - P2_LAG) >= P2_POS - 2 * P2_LAG) + ((unsigned)(p - 2 * P2_LAG) >= P2_POS - 4 * P2_LAG && (unsigned)(p - busy) >= 24);
                    if (idle) asm volatile("mbarrier.arrive.shared::cta.b64 _, [%0], %1;\n" ::"r"(bar_bempty + st * 8), "r"(idle * 8) : "memory");
                    if (rank == 0) asm volatile("red.relaxed.gpu.global.add.u32 [%0], 1;\n" ::"l"(&g_prog) : "memory");
                }
                __syncwarp();
                if (++st == P2_NB) { st = 0; ph ^= 1; }
                if (++kb == 48) kb = 0;
            }
            mbar_wait(bar_bempty + st * 8, ph);
            if (lane == 0) mbar_arrive(bar_bfull + st * 8);
        } else if (warp == 13) {
            const uint8_t* src[3];
            int n[3], left[3], wrap[3];
            uint32_t st[3];
            auto item = [&](int w) {
                int u = k0 + (n[w] < 0 ? 0 : n[w] == P2_ITEMS ? 40 : w * P2_LAG);
                if (u >= 48) u -= 48;
                left[w] = n[w] < 0 || n[w] == P2_ITEMS ? 24 : 48;
                wrap[w] = left[w] - (48 - u);
                src[w] = reinterpret_cast<const uint8_t*>(g_h) + (size_t)p2_tile(cl, n[w]) * (2 * H_TILE) + rank * H_HALF + u * H_STEP;
            };
#pragma unroll
            for (int w = 0; w < 3; w++) {
                n[w] = w == 2 && head ? -1 : w;
                st[w] = 0x80000000u;
                item(w);
            }
            gdc_wait();
#pragma unroll 1
            for (int done = 0; done < 3;) {
                bool idle = true;
#pragma unroll
                for (int w = 0; w < 3; w++) {
                    const uint32_t o = (st[w] & 0xff) + w * P2_NA * 8;
                    if (left[w] >= 0 && mbar_test(bar_aempty + o, st[w] >> 31)) {
                        idle = false;
                        if (left[w] == 0) {
                            if (lane == 0) mbar_arrive(bar_afull + o);
                            left[w] = -1;
                            done++;
                        } else {
                            if (elect_one()) {
                                mbar_expect_tx(bar_afull + o, P2_A);
                                bulk_g2s(sbase + P2_OFF_A + o * (P2_A / 8), src[w], P2_A, bar_afull + o);
                            }
                            __syncwarp();
                            src[w] += H_STEP;
                            st[w] += 8;
                            if ((st[w] & 0xff) == P2_NA * 8) st[w] ^= 0x80000000u | (P2_NA * 8);
                            if (--left[w] == wrap[w]) src[w] -= 48 * H_STEP;
                            if (left[w] == 0 && (n[w] += 3) < P2_ITEMS + tail) item(w);
                        }
                    }
                }
                if (idle) __nanosleep(P2_HSLEEP);
                SAFE_BREAK
            }
        } else if (warp == 14) {
            const uint32_t sx = sbase + P2_OFF_X;
            size_t o = 0;
            auto pace = [&](int target) {
                int v;
                while (true) {
                    asm volatile("ld.volatile.shared.u32 %0, [%1];\n" : "=r"(v) : "r"(s_pos) : "memory");
                    if (v * 16 >= target) break;
                    __nanosleep(100);
                    SAFE_BREAK
                }
            };
#pragma unroll 1
            for (int n = -head; n <= P2_ITEMS; n++) {
                const size_t on = (size_t)(2 * p2_tile(cl, n) + rank) * (64 * C_DIM * 2);
                const bool st = n + head > 0, ld = n < P2_ITEMS;
                if (st) mbar_wait(bar_oready, (n - 1 + head) & 1);
                TR2P(n + 1, 1);
                if (lane == 0) {
                    if (n == 1 && head) {
                        asm volatile("cp.async.bulk.wait_group 0;\nfence.proxy.async.global;\n" ::: "memory");
                        asm volatile("st.release.gpu.global.u32 [%0], 1;\n" ::"l"(&g_half[pair][rank]) : "memory");
                    }
                    if (ld) mbar_expect_tx(bar_xfull, 64 * C_DIM * 2);
                    int t = st && n < P2_ITEMS - 1 ? (P2_LAG * (n + 2) + P2_T0 - 1) * 16 : -1024;
#pragma unroll 1
                    for (int c = 0; st && c < 64 * P2_XROW; c += P2_XC) {
                        pace(t += P2_TS);
                        bulk_s2g(reinterpret_cast<uint8_t*>(out) + o + c, sx + c + (c >= 32 * P2_XROW ? 64 : 0), P2_XC);
                    }
                    asm volatile("cp.async.bulk.commit_group;\ncp.async.bulk.wait_group.read 0;\n" ::: "memory");
#pragma unroll 1
                    for (int c = 0; ld && c < 64 * P2_XROW; c += P2_XC) {
                        pace(t += P2_TS);
                        bulk_g2s(sx + c + (c >= 32 * P2_XROW ? 64 : 0), reinterpret_cast<const uint8_t*>(x) + on + c, P2_XC, bar_xfull);
                    }
                    TR2P(n + 1, 2);
                    if (rank == 0 && n > 0 && n < P2_ITEMS - 2)
                        flag_wait<false>(&g_prog, P2_NCL * (P2_LAG * (n + 3) + P2_EXTRA) + (tail ? P2_SHARED - P2_NCL : P2_SHARED) * P2_DELTA);
                    if (ld) mbar_arrive(bar_xfull);
                    TR2P(n + 1, 3);
                }
                __syncwarp();
                o = on;
            }
            asm volatile("cp.async.bulk.wait_group 0;\n" ::: "memory");
            TR2P(30, 1);
        }
        __syncwarp();
        cluster_sync();
        if (warp == 14) TR2P(31, 1);
    } else {
        reg_inc<160>();
        const int wg = warp >> 2, w = warp & 3, g = lane >> 2, q = lane & 3;
        const uint32_t sx = sbase + P2_OFF_X + (g & 1) * P2_XHALF + (w * 8 + (g >> 1)) * P2_XROW + q * 16;
        const uint32_t af = bar_afull + wg * P2_NA * 8, ae = bar_aempty + wg * P2_NA * 8;
        const uint32_t s_a = sbase + P2_OFF_A - bar_afull * (P2_A / 8) + (lane >> 3) * 512 + (lane & 7) * 64 +
                             ((w ^ ((lane & 7) >> 1)) << 4);
        uint32_t acc0[48], acc1[48], dn;
        float up;
        uint4 a0[2], a1[2];
        int st = 0, ph = 0;

        {
            float4* s_red = reinterpret_cast<float4*>(smem + P2_OFF_RED);
            const float* sums = g_sums[par];
            float gx[4], part = 0.f, mx = 0.f;
            if (tid < 16) reinterpret_cast<uint4*>(smem + P2_OFF_ONES)[tid] = make_uint4(tid < 8 ? 0x3c003c00u : 0u, 0u, 0u, 0u);
            TSTAMP(1, 27);
            gdc_wait();
            TSTAMP(1, 1);
#pragma unroll
            for (int i = 0; i < 4; i++) gx[i] = __ldcg(sums + tid + 384 * i);
            if (blockIdx.x == 120 && tid < (LN_RING + 4) * 2) (&g_flag[0][0][0])[tid * 8] = 0;
            if (blockIdx.x == 121 && tid == 0) atomicAdd(&g_epoch, 1u);
            const float bias = pre[0] + pre[1];
            float z = __uint_as_float(__reduce_max_sync(0xffffffffu, __float_as_uint(acc_bound(bias, pre[2] + pre[3]))));
#pragma unroll
            for (int i = 0; i < 4; i++) {
                asm("sqrt.approx.f32 %0, %1;\n" : "=f"(gx[i]) : "f"(fmaf(gx[i], HSCALE * HSCALE, 1e-6f)));
                part += gx[i];
                gx[i] *= bf_lo(gg[i]);
                mx = fmaxf(mx, fabsf(gx[i]));
            }
#pragma unroll
            for (int o = 16; o > 0; o >>= 1) part += __shfl_xor_sync(0xffffffffu, part, o);
            mx = __uint_as_float(__reduce_max_sync(0xffffffffu, __float_as_uint(mx)));
            TSTAMP(1, 26);
            if (lane == 0) s_red[warp] = make_float4(part, mx, z, 0.f);
            bar_sync(1, 384);
            float tot = 0.f;
            {
                const float4 t = s_red[min(lane & 15, 11)];
                tot = (lane & 15) < 12 ? t.x : 0.f;
#pragma unroll
                for (int o = 8; o > 0; o >>= 1) tot += __shfl_xor_sync(0xffffffffu, tot, o);
                mx = __uint_as_float(__reduce_max_sync(0xffffffffu, __float_as_uint(t.y)));
                z = __uint_as_float(__reduce_max_sync(0xffffffffu, __float_as_uint(t.z)));
            }
            const float inv = __fdividef(1.0f, fmaf(tot, 1.0f / HID, 1e-6f));
#pragma unroll
            for (int i = 0; i < 4; i++) {
                const int k = tid + 384 * i;
                *reinterpret_cast<__nv_bfloat16*>(smem + P2_OFF_GRN + (k >> 5) * 64 + ((k >> 1) & 3) * 16 + ((k >> 3) & 3) * 4 + (k & 1) * 2) =
                    __float2bfloat16(gx[i] * inv);
            }
            const uint32_t j = max(__float_as_uint(fmaf(mx, inv, 1.0f) * 1.01f) >> 23, 130u) - 130u;
            dn = __shfl_sync(0xffffffffu, j ? (127u - j) * 0x00800080u : 0u, 0);
            const uint32_t e = min(acc_exp(z) - 9u + j, 253u);
            up = HSCALE * __uint_as_float(e << 23);
            const float b = bias * (1.0f / HSCALE) * __uint_as_float((254u - e) << 23);
            *reinterpret_cast<uint4*>(smem + P2_OFF_BIAS + tid * 16) = make_uint4(pack_f16(b, b - h_lo(pack_f16(b, 0.f))), 0u, 0u, 0u);
            TSTAMP(1, 25);
            asm volatile("fence.proxy.async.shared::cta;\n" ::: "memory");
            bar_sync(1, 384);
        }
        TSTAMP(1, 28);
        const uint32_t s_t = sbase + P2_OFF_GRN + q * 16;
        const int first = wg == 2 && head ? 0 : wg * P2_LAG;
        int kt = (k0 + first) % 48;

        int pos = first;
        const int who = __shfl_sync(0xffffffffu, lane == 2 ? 0 : lane < 2 ? 1 : 2, lane);
        const uint32_t rel0 = who ? mapa(bar_bempty, lane & 1) : mapa(ae, rank), rel1 = rel0 + (who ? P2_NB : P2_NA) * 8;
        uint32_t rel = rel1 - 8;
        auto next_rel = [&](bool go) {
            if (go) rel += 8;
            if (rel == rel1) rel = rel0;
        };
        auto release_b = [&]() {
            next_rel(who == 1);
            if (who == 1) mbar_arrive_cluster(rel);
        };
        auto seek = [&](int p) {
            st = p % P2_NB;
            ph = p / P2_NB & 1;
            if (who == 1) rel = (st ? rel0 + st * 8 : rel1) - 8;
            int v;
            while (true) {
                asm volatile("ld.volatile.shared.u32 %0, [%1];\n" : "=r"(v) : "r"(s_pos) : "memory");
                if (v >= p) break;
                __nanosleep(200);
                SAFE_BREAK
            }
        };
        auto publish = [&]() {
            asm volatile("fence.proxy.async.shared::cta;\n" ::: "memory");
            __syncwarp();
            if (who == 0) mbar_arrive(bar_oready);
        };
        bool ok_a, pend = false;
        uint32_t abar = af, pa = 0;
        auto fetch = [&](uint4 (&a)[2]) {
            uint32_t u0[4], u1[4];
            const uint32_t src = s_a + abar * (P2_A / 8);
            abar += 8;
            if (abar == af + P2_NA * 8) { abar = af; pa ^= 0x80000000u; }
            uint32_t t[4];
            asm volatile("ld.shared.v4.u32 {%0,%1,%2,%3}, [%4];\n" : "=r"(t[0]), "=r"(t[1]), "=r"(t[2]), "=r"(t[3]) : "r"(s_t + kt * 64) : "memory");
            const bool ok_b = mbar_test(bar_bfull + st * 8, ph);
            ok_a = mbar_test(abar, pa >> 31);
            uint32_t o[6];
            asm volatile("ldmatrix.sync.aligned.m8n8.x4.trans.shared.b16 {%0,%1,%2,%3}, [%4];\n"
                         : "=r"(o[0]), "=r"(o[1]), "=r"(o[2]), "=r"(o[3]) : "r"(src) : "memory");
            asm volatile("ldmatrix.sync.aligned.m8n8.x2.trans.shared.b16 {%0,%1}, [%2];\n"
                         : "=r"(o[4]), "=r"(o[5]) : "r"(src + 2048) : "memory");
            p2_unpack(u0, o[0], o[1], o[2]);
            p2_unpack(u1, o[3], o[4], o[5]);
#pragma unroll
            for (int i = 0; i < 4; i++) {
                u0[i] = bf2_fma(u0[i], t[i >> 1], u0[i]);
                u1[i] = bf2_fma(u1[i], t[2 + (i >> 1)], u1[i]);
            }
            if (dn) {
#pragma unroll
                for (int i = 0; i < 4; i++) {
                    u0[i] = bf2_mul(u0[i], dn);
                    u1[i] = bf2_mul(u1[i], dn);
                }
            }
            a[0] = make_uint4(bf2_as_h2(u0[0]), bf2_as_h2(u0[1]), bf2_as_h2(u0[2]), bf2_as_h2(u0[3]));
            a[1] = make_uint4(bf2_as_h2(u1[0]), bf2_as_h2(u1[1]), bf2_as_h2(u1[2]), bf2_as_h2(u1[3]));
            if (++kt == 48) kt = 0;
            if (!ok_b) mbar_wait(bar_bfull + st * 8, ph);
        };
        auto step = [&](const uint4 (&a)[2], uint4 (&an)[2], int thr) {
            TR2(0);
            const uint64_t db = make_desc(sbase + st * P2_B, 128, 256);
            wg_fence();
            mma_rs_n192(acc0, a[0], db);
            mma_rs_n192(acc1, a[0], db + 384);
            mma_rs_n192(acc0, a[1], db + 768);
            mma_rs_n192(acc1, a[1], db + 768 + 384);
            wg_commit();
            next_rel(who < thr);
            if (++st == P2_NB) { st = 0; ph ^= 1; }
            wg_wait<1>();
            if (!ok_a) {
                if (who < thr) mbar_arrive_cluster(rel);
                if (thr == 1 && pend) publish();
                thr = 0;
                mbar_wait(abar, pa >> 31);
            }
            if (who < thr) mbar_arrive_cluster(rel);
            fetch(an);
            pos++;
        };
        seek(first);
        mbar_wait(af, 0);
        fetch(a0);
#pragma unroll 1
        for (int n = wg == 2 && head ? -1 : wg;; n += 3) {
            TSTAMP(1, 2 + n);
            const uint64_t ones = make_desc(sbase + P2_OFF_ONES + (n == P2_ITEMS ? 128 : 0), n == P2_ITEMS ? 0 : 128, 0);
            wg_fence();
            mma_ss_n192_init(acc0, ones, make_desc(sbase + P2_OFF_BIAS, 0, 128));
            mma_ss_n192_init(acc1, ones, make_desc(sbase + P2_OFF_BIAS + 3072, 0, 128));
            wg_commit();
            const int p0 = n < 0 || n == P2_ITEMS ? 12 : 0;
            const bool more = n + 3 < P2_ITEMS + tail;
#pragma unroll 1
            for (int p = p0; p < 24; p++) {
                step(a0, a1, p == p0 ? 1 : 2);
                step(a1, a0, 2);
            }
            if (n == P2_ITEMS) {
                flag_wait<true>(&g_half[pair][rank], 1);
                TR2(1);
                wg_wait<0>();
                TR2(2);
                release_b();
                uint8_t* o = reinterpret_cast<uint8_t*>(out) + (size_t)((2 * p2_tile(cl, -1) + rank) * 64 + (g & 1) * 32 + w * 8 + (g >> 1)) * P2_XROW + q * 16;
                p2_epilogue_add(acc0, o, up, zero);
                p2_epilogue_add(acc1, o + 384, up, zero);
                TR2(3);
                break;
            }
            mbar_wait(bar_xfull, (n + head) & 1);
            TR2(1);
            wg_wait<0>();
            TR2(2);
            release_b();
            __syncwarp();
            p2_epilogue(acc0, acc1, sx, up, zero);
            TR2(3);
            if (!more) {
                publish();
                break;
            }
            pend = true;
            ok_a = false;
            if (n < 0 || n + 3 == P2_ITEMS) {
                publish();
                pend = false;
                seek(n < 0 ? 2 * P2_LAG : P2_POS - 24);
                if (abar == af) { abar = af + P2_NA * 8; pa ^= 0x80000000u; }
                abar -= 8;
                kt += 7;
                if (kt >= 48) kt -= 48;
                fetch(a0);
                pos += 8;
            }
        }
        TSTAMP(1, 29);
        cluster_sync();
        TSTAMP(1, 30);
    }
}

}

extern "C" void kernel_launch(void* const* d_in, const int* in_sizes, int n_in, void* d_out, int out_size) {
    const __nv_bfloat16* x = (const __nv_bfloat16*)d_in[0];
    const __nv_bfloat16* dw = (const __nv_bfloat16*)d_in[1];
    const __nv_bfloat16* w1 = (const __nv_bfloat16*)d_in[2];
    const __nv_bfloat16* w2 = (const __nv_bfloat16*)d_in[3];
    const __nv_bfloat16* grn_g = (const __nv_bfloat16*)d_in[4];
    const __nv_bfloat16* grn_b = (const __nv_bfloat16*)d_in[5];
    __nv_bfloat16* out = (__nv_bfloat16*)d_out;

    cudaFuncSetAttribute(pass1_kernel, cudaFuncAttributeMaxDynamicSharedMemorySize, P1_SMEM);
    cudaFuncSetAttribute(pass2_kernel, cudaFuncAttributeMaxDynamicSharedMemorySize, P2_SMEM);

    typedef CUresult (*EncodeFn)(CUtensorMap*, CUtensorMapDataType, cuuint32_t, void*, const cuuint64_t*, const cuuint64_t*,
                                 const cuuint32_t*, const cuuint32_t*, CUtensorMapInterleave, CUtensorMapSwizzle,
                                 CUtensorMapL2promotion, CUtensorMapFloatOOBfill);
    static EncodeFn encode = nullptr;
    if (!encode) {
        cudaDriverEntryPointQueryResult qres;
        cudaGetDriverEntryPoint("cuTensorMapEncodeTiled", (void**)&encode, cudaEnableDefault, &qres);
    }
    CUtensorMap wmap;
    const cuuint64_t gdim[2] = {HID, C_DIM};
    const cuuint64_t gstr[1] = {HID * 2};
    const cuuint32_t box[2] = {64, 192}, estr[2] = {1, 1};
    CUresult er = encode(&wmap, CU_TENSOR_MAP_DATA_TYPE_BFLOAT16, 2, (void*)w1, gdim, gstr, box, estr, CU_TENSOR_MAP_INTERLEAVE_NONE,
           CU_TENSOR_MAP_SWIZZLE_128B, CU_TENSOR_MAP_L2_PROMOTION_L2_128B, CU_TENSOR_MAP_FLOAT_OOB_FILL_NONE);
    if (er != CUDA_SUCCESS) printf("tensor map encode failed %d\n", (int)er);

    pass1_kernel<<<NUM_CTAS, 512, P1_SMEM>>>(wmap, x, dw, w2, grn_b, 0);

    cudaLaunchAttribute attr[1];
    attr[0].id = cudaLaunchAttributeProgrammaticStreamSerialization;
    attr[0].val.programmaticStreamSerializationAllowed = 1;
    cudaLaunchConfig_t cfg = {};
    cfg.gridDim = dim3(NUM_CTAS);
    cfg.stream = 0;
    cfg.attrs = attr;
    cfg.numAttrs = 1;
    cfg.blockDim = dim3(512);
    cfg.dynamicSmemBytes = P2_SMEM;
    cudaLaunchKernelEx(&cfg, pass2_kernel, x, grn_g, out, 0);
}
```

```cpp
#include <cuda.h>
#include <cuda_runtime.h>
#include <cuda_bf16.h>
#include <stdint.h>
#include <stdio.h>

namespace {

constexpr int M_TOTAL = 384 * 384;
constexpr int C_DIM   = 384;
constexpr int HID     = 1536;
constexpr int NT128   = M_TOTAL / 128;
constexpr int NUM_CTAS = 132;

constexpr int NGRP = 11, GRP_CTAS = 12;
constexpr int LN_STEP = NUM_CTAS / 4, LN_RING = 2 * LN_STEP;
constexpr int NT_RING = NT128 - NGRP;
constexpr int LN_TILE = 128 * C_DIM * 2;
constexpr int H_TILE = 64 * HID * 3 / 2;
constexpr int H_HALF = 3072, H_STEP = 6144;

__device__ __align__(1024) uint4 g_h[(size_t)M_TOTAL * HID * 3 / 32];
__device__ __align__(1024) uint4 g_ln[LN_RING * LN_TILE / 16];
__device__ __align__(1024) uint4 g_w2img[HID * C_DIM * 2 / 16];
__device__ __align__(16) float g_sums[2][HID + 2 * C_DIM];
__device__ unsigned g_ex[HID];
__device__ unsigned g_epoch, g_par;
__device__ __align__(128) unsigned g_img;
__device__ __align__(128) unsigned g_prog;
__device__ __align__(128) unsigned g_half[32][2];
__device__ unsigned g_flag[LN_RING + 4][2][8];
#define TSTAMP(k, i)
#define TRACE(wg, pos, i)
#define TRACEW(pos, i)

#define TR2(i)
#define TR2P(pos, i)
__host__ __device__ __forceinline__ int perm32(int n) {
    return (n & ~31) | (((n >> 1) & 3) << 3) | (((n >> 3) & 3) << 1) | (n & 1);
}

__device__ __forceinline__ uint32_t smem_u32(const void* p) { return (uint32_t)__cvta_generic_to_shared(p); }

__device__ __forceinline__ void mbar_init(uint32_t bar, uint32_t count) {
    asm volatile("mbarrier.init.shared::cta.b64 [%0], %1;\n" ::"r"(bar), "r"(count) : "memory");
}
__device__ __forceinline__ void mbar_expect_tx(uint32_t bar, uint32_t bytes) {
    asm volatile("mbarrier.arrive.expect_tx.shared::cta.b64 _, [%0], %1;\n" ::"r"(bar), "r"(bytes) : "memory");
}
__device__ __forceinline__ void mbar_arrive(uint32_t bar) {
    asm volatile("mbarrier.arrive.shared::cta.b64 _, [%0];\n" ::"r"(bar) : "memory");
}
__device__ __forceinline__ void mbar_arrive_cluster(uint32_t bar_cluster_addr) {
    asm volatile("mbarrier.arrive.shared::cluster.b64 _, [%0];\n" ::"r"(bar_cluster_addr) : "memory");
}
#define SAFE_BREAK
__device__ __forceinline__ void mbar_wait(uint32_t bar, uint32_t parity) {
    asm volatile(
        "{\n"
        ".reg .pred p;\n"
        "LAB_WAIT:\n"
        "mbarrier.try_wait.parity.shared::cta.b64 p, [%0], %1;\n"
        "@!p bra LAB_WAIT;\n"
        "}\n" ::"r"(bar), "r"(parity) : "memory");
}
__device__ __forceinline__ bool mbar_test(uint32_t bar, uint32_t parity) {
    uint32_t ok;
    asm volatile("{\n.reg .pred p;\n"
                 "mbarrier.test_wait.parity.shared::cta.b64 p, [%1], %2;\n"
                 "selp.u32 %0, 1, 0, p;\n}\n" : "=r"(ok) : "r"(bar), "r"(parity) : "memory");
    return ok != 0;
}
__device__ __forceinline__ uint32_t mapa(uint32_t addr, uint32_t rank) {
    uint32_t r;
    asm volatile("mapa.shared::cluster.u32 %0, %1, %2;\n" : "=r"(r) : "r"(addr), "r"(rank));
    return r;
}
__device__ __forceinline__ void bulk_g2s(uint32_t dst, const void* src, uint32_t bytes, uint32_t bar) {
    asm volatile("cp.async.bulk.shared::cluster.global.mbarrier::complete_tx::bytes [%0], [%1], %2, [%3];\n"
                 ::"r"(dst), "l"(src), "r"(bytes), "r"(bar) : "memory");
}
__device__ __forceinline__ void bulk_g2s_mc(uint32_t dst, const void* src, uint32_t bytes, uint32_t bar, uint16_t mask) {
    asm volatile("cp.async.bulk.shared::cluster.global.mbarrier::complete_tx::bytes.multicast::cluster [%0], [%1], %2, [%3], %4;\n"
                 ::"r"(dst), "l"(src), "r"(bytes), "r"(bar), "h"(mask) : "memory");
}
__device__ __forceinline__ void tma2(uint32_t dst, const CUtensorMap* map, int c0, int c1, uint32_t bar) {
    asm volatile("cp.async.bulk.tensor.2d.shared::cluster.global.tile.mbarrier::complete_tx::bytes [%0], [%1, {%2, %3}], [%4];\n"
                 ::"r"(dst), "l"(map), "r"(c0), "r"(c1), "r"(bar) : "memory");
}
template <bool ACQ>
__device__ __forceinline__ uint32_t flag_wait(const unsigned* p, unsigned target) {
    unsigned v, n = 0;
    do {
        if (ACQ) asm volatile("ld.acquire.gpu.global.u32 %0, [%1];\n" : "=r"(v) : "l"(p) : "memory");
        else asm volatile("ld.relaxed.gpu.global.u32 %0, [%1];\n" : "=r"(v) : "l"(p) : "memory");
        n++;
    } while (v < target);
    return n == 1;
}
__device__ __forceinline__ void ldsm4t(uint32_t (&r)[4], uint32_t addr) {
    asm volatile("ldmatrix.sync.aligned.m8n8.x4.trans.shared.b16 {%0,%1,%2,%3}, [%4];\n"
                 : "=r"(r[0]), "=r"(r[1]), "=r"(r[2]), "=r"(r[3]) : "r"(addr) : "memory");
}
__device__ __forceinline__ void bulk_s2g(void* dst, uint32_t src, uint32_t bytes) {
    asm volatile("cp.async.bulk.global.shared::cta.bulk_group [%0], [%1], %2;\n" ::"l"(dst), "r"(src), "r"(bytes) : "memory");
}
__device__ __forceinline__ void cluster_sync_relaxed() {
    asm volatile("barrier.cluster.arrive.relaxed.aligned;\nbarrier.cluster.wait.aligned;\n" ::: "memory");
}
__device__ __forceinline__ void gdc_wait() { asm volatile("griddepcontrol.wait;\n" ::: "memory"); }
__device__ __forceinline__ void gdc_launch() { asm volatile("griddepcontrol.launch_dependents;\n" ::: "memory"); }
__device__ __forceinline__ uint32_t cluster_rank() {
    uint32_t r;
    asm volatile("mov.u32 %0, %%cluster_ctarank;\n" : "=r"(r));
    return r;
}
__device__ __forceinline__ bool elect_one() {
    uint32_t pred;
    asm volatile("{\n.reg .pred p;\nelect.sync _|p, 0xffffffff;\nselp.u32 %0, 1, 0, p;\n}\n" : "=r"(pred));
    return pred != 0;
}
__device__ __forceinline__ void wg_fence() { asm volatile("wgmma.fence.sync.aligned;\n" ::: "memory"); }
__device__ __forceinline__ void wg_commit() { asm volatile("wgmma.commit_group.sync.aligned;\n" ::: "memory"); }
template <int N> __device__ __forceinline__ void wg_wait() {
    asm volatile("wgmma.wait_group.sync.aligned %0;\n" ::"n"(N) : "memory");
}
template <int R> __device__ __forceinline__ void reg_inc() { asm volatile("setmaxnreg.inc.sync.aligned.u32 %0;\n" ::"n"(R)); }
template <int R> __device__ __forceinline__ void reg_dec() { asm volatile("setmaxnreg.dec.sync.aligned.u32 %0;\n" ::"n"(R)); }
__device__ __forceinline__ void bar_sync(int id, int n) { asm volatile("bar.sync %0, %1;\n" ::"r"(id), "r"(n) : "memory"); }
__device__ __forceinline__ void bar_arrive(int id, int n) { asm volatile("bar.arrive %0, %1;\n" ::"r"(id), "r"(n) : "memory"); }

__device__ __forceinline__ uint64_t make_desc(uint32_t saddr, uint32_t lbo, uint32_t sbo) {
    return (uint64_t)((saddr & 0x3FFFF) >> 4) | ((uint64_t)(lbo >> 4) << 16) | ((uint64_t)(sbo >> 4) << 32);
}

__device__ __forceinline__ void stg128_cs(void* p, uint32_t a, uint32_t b, uint32_t c, uint32_t d) {
    asm volatile("st.global.cs.v4.u32 [%0], {%1,%2,%3,%4};\n" ::"l"(p), "r"(a), "r"(b), "r"(c), "r"(d) : "memory");
}
__device__ __forceinline__ uint32_t pack_bf16(float lo, float hi) {
    uint32_t r;
    asm("cvt.rn.bf16x2.f32 %0, %1, %2;\n" : "=r"(r) : "f"(hi), "f"(lo));
    return r;
}
__device__ __forceinline__ float bf_lo(uint32_t v) { return __uint_as_float(v << 16); }
__device__ __forceinline__ float bf_hi(uint32_t v) { return __uint_as_float(v & 0xffff0000u); }
__device__ __forceinline__ uint32_t bf2_mul(uint32_t a, uint32_t b) {
    uint32_t r;
    asm("mul.rn.bf16x2 %0, %1, %2;\n" : "=r"(r) : "r"(a), "r"(b));
    return r;
}
__device__ __forceinline__ uint32_t bf2_fma(uint32_t a, uint32_t b, uint32_t c) {
    uint32_t r;
    asm("fma.rn.bf16x2 %0, %1, %2, %3;\n" : "=r"(r) : "r"(a), "r"(b), "r"(c));
    return r;
}
__device__ __forceinline__ uint32_t bf2_add(uint32_t a, uint32_t b) {
    uint32_t r;
    asm("add.rn.bf16x2 %0, %1, %2;\n" : "=r"(r) : "r"(a), "r"(b));
    return r;
}
constexpr float KAPPA = 0.3292034911525734f;
constexpr float GELU_C = 2.423681954311584f;
constexpr float HSCALE = 1.0f / (2.0f * KAPPA);
__device__ __forceinline__ float acc_bound(float bias, float asum) { return fmaxf(asum, fabsf(bias) * 0.0625f); }
__device__ __forceinline__ uint32_t acc_exp(float z) { return max(__float_as_uint(z) >> 23, 10u); }
__device__ __forceinline__ void sched_break(int zero) {
    asm volatile("{\n.reg .pred p;\nsetp.ne.s32 p, %0, 0;\nSB_LOOP:\n@p nanosleep.u32 1;\n@p bra SB_LOOP;\n}\n" ::"r"(zero));
}

#define ACC8(d, o) "+f"(d[o + 0]), "+f"(d[o + 1]), "+f"(d[o + 2]), "+f"(d[o + 3]), "+f"(d[o + 4]), "+f"(d[o + 5]), "+f"(d[o + 6]), "+f"(d[o + 7])

#define ACCR8(d, o) "+r"(d[o + 0]), "+r"(d[o + 1]), "+r"(d[o + 2]), "+r"(d[o + 3]), "+r"(d[o + 4]), "+r"(d[o + 5]), "+r"(d[o + 6]), "+r"(d[o + 7])
__device__ __forceinline__ void mma_rs_n128(uint32_t (&d)[32], const uint32_t (&a)[4], uint64_t desc, int scale_d) {
    asm volatile(
        "{\n.reg .pred p;\nsetp.ne.b32 p, %37, 0;\n"
        "wgmma.mma_async.sync.aligned.m64n128k16.f16.f16.f16 "
        "{%0,%1,%2,%3,%4,%5,%6,%7,%8,%9,%10,%11,%12,%13,%14,%15,"
        "%16,%17,%18,%19,%20,%21,%22,%23,%24,%25,%26,%27,%28,%29,%30,%31},"
        "{%32,%33,%34,%35}, %36, p, 1, 1, 0;\n}\n"
        : ACCR8(d, 0), ACCR8(d, 8), ACCR8(d, 16), ACCR8(d, 24)
        : "r"(a[0]), "r"(a[1]), "r"(a[2]), "r"(a[3]), "l"(desc), "r"(scale_d));
}
__device__ __forceinline__ uint32_t bf2_as_h2(uint32_t v) { return (v & 0x0fff0fffu) * 7u + v; }
__device__ __forceinline__ float h_lo(uint32_t v) {
    float r;
    asm("{\n.reg .b16 l, h;\nmov.b32 {l, h}, %1;\ncvt.f32.f16 %0, l;\n}\n" : "=f"(r) : "r"(v));
    return r;
}
__device__ __forceinline__ float h_hi(uint32_t v) {
    float r;
    asm("{\n.reg .b16 l, h;\nmov.b32 {l, h}, %1;\ncvt.f32.f16 %0, h;\n}\n" : "=f"(r) : "r"(v));
    return r;
}

__device__ __forceinline__ void mma_rs_n192(uint32_t (&d)[48], const uint4& a, uint64_t db) {
    asm volatile(
        "{\n.reg .pred p;\nsetp.ne.b32 p, %53, 0;\n"
        "wgmma.mma_async.sync.aligned.m64n192k16.f16.f16.f16 "
        "{%0,%1,%2,%3,%4,%5,%6,%7,%8,%9,%10,%11,%12,%13,%14,%15,"
        "%16,%17,%18,%19,%20,%21,%22,%23,%24,%25,%26,%27,%28,%29,%30,%31,"
        "%32,%33,%34,%35,%36,%37,%38,%39,%40,%41,%42,%43,%44,%45,%46,%47},"
        "{%48,%49,%50,%51}, %52, p, 1, 1, 0;\n}\n"
        : ACCR8(d, 0), ACCR8(d, 8), ACCR8(d, 16), ACCR8(d, 24), ACCR8(d, 32), ACCR8(d, 40)
        : "r"(a.x), "r"(a.y), "r"(a.z), "r"(a.w), "l"(db), "r"(1));
}

__device__ __forceinline__ void mma_ss_n192_init(uint32_t (&d)[48], uint64_t da, uint64_t db) {
    asm volatile(
        "{\n.reg .pred p;\nsetp.ne.b32 p, %50, 0;\n"
        "wgmma.mma_async.sync.aligned.m64n192k16.f16.f16.f16 "
        "{%0,%1,%2,%3,%4,%5,%6,%7,%8,%9,%10,%11,%12,%13,%14,%15,"
        "%16,%17,%18,%19,%20,%21,%22,%23,%24,%25,%26,%27,%28,%29,%30,%31,"
        "%32,%33,%34,%35,%36,%37,%38,%39,%40,%41,%42,%43,%44,%45,%46,%47},"
        "%48, %49, p, 1, 1, 0, 0;\n}\n"
        : ACCR8(d, 0), ACCR8(d, 8), ACCR8(d, 16), ACCR8(d, 24), ACCR8(d, 32), ACCR8(d, 40)
        : "l"(da), "l"(db), "r"(0));
}
__device__ __forceinline__ uint32_t pack_f16(float lo, float hi) {
    uint32_t r;
    asm("cvt.rn.f16x2.f32 %0, %1, %2;\n" : "=r"(r) : "f"(hi), "f"(lo));
    return r;
}

#define P1_REGS 192
#define P1_WARM 0
#define P1_DEF 3
#define P1_DMID 0
#define P1_ARR 23
constexpr int P1_SLOT = LN_TILE / 2, P1_NST = 4;
constexpr int P1_X = 32 * C_DIM * 2;
constexpr int P1_OFF_X = P1_SLOT * P1_NST;
constexpr int P1_OFF_BAR = P1_OFF_X + P1_X;
constexpr int P1_OFF_TILE = P1_OFF_BAR + (2 * P1_NST + 2 + 4) * 8;
constexpr int P1_OFF_RAW = P1_OFF_TILE + 64;
constexpr int P1_OFF_DW = P1_OFF_RAW + 32;
constexpr int P1_SMEM = P1_OFF_DW + C_DIM * 2;

__device__ __forceinline__ float rsqrt_fast(float x) {
    float r;
    asm("rsqrt.approx.ftz.f32 %0, %1;\n" : "=f"(r) : "f"(x));
    return r;
}
__device__ __forceinline__ float row_sum(const uint32_t (&c)[4]) {
    const uint32_t u = bf2_add(bf2_add(c[0], c[1]), bf2_add(c[2], c[3]));
    float s = bf_lo(u) + bf_hi(u);
#pragma unroll
    for (int o = 1; o < 8; o <<= 1) s += __shfl_xor_sync(0xffffffffu, s, o);
    return s;
}
__device__ __forceinline__ void ln_row(uint32_t (&v)[6][4], const uint32_t (&d)[6][4], int zero, uint32_t bar_read) {
    uint32_t c[4];
#pragma unroll
    for (int i = 0; i < 6; i++)
#pragma unroll
        for (int k = 0; k < 4; k++) c[k] = bf2_fma(v[i][k], d[i][k], i ? c[k] : 0);
    const float inv = 1.0f / C_DIM;
    const float m = row_sum(c) * inv;
    const uint32_t nm = pack_bf16(-m, -m);
    const float e = m + bf_lo(nm);
    if (bar_read) mbar_arrive(bar_read + (nm & zero));
#pragma unroll
    for (int i = 0; i < 6; i++) {
#pragma unroll
        for (int k = 0; k < 4; k++) {
            v[i][k] = bf2_fma(v[i][k], d[i][k], nm);
            c[k] = i ? bf2_fma(v[i][k], v[i][k], c[k]) : bf2_mul(v[i][k], v[i][k]);
        }
    }
    float r = KAPPA * rsqrt_fast(fmaxf(fmaf(-e, e, row_sum(c) * inv), 0.f) + 1e-5f);
    const uint32_t sh = pack_bf16(-e * r * 0x1p-112f, -e * r * 0x1p-112f);
    if (__any_sync(0xffffffffu, r < 0x1p-14f)) {
        const uint32_t f = r < 0x1p-14f ? 0x23802380u : 0x3f803f80u;
        if (r < 0x1p-14f) r *= 0x1p56f;
#pragma unroll
        for (int i = 0; i < 6; i++)
#pragma unroll
            for (int k = 0; k < 4; k++) v[i][k] = bf2_mul(v[i][k], f);
    }
    const uint32_t rs = pack_bf16(r * 0x1p-112f, r * 0x1p-112f);
#pragma unroll
    for (int i = 0; i < 6; i++)
#pragma unroll
        for (int k = 0; k < 4; k++) v[i][k] = bf2_as_h2(bf2_fma(v[i][k], rs, sh));
}

__device__ __forceinline__ void load_dw(uint32_t (&d)[6][4], uint32_t sbase, int lane) {
    mbar_wait(sbase + P1_OFF_RAW + 16, 0);
#pragma unroll
    for (int j = 0; j < 6; j++)
        asm volatile("ld.shared.v4.u32 {%0,%1,%2,%3}, [%4];\n" : "=r"(d[j][0]), "=r"(d[j][1]), "=r"(d[j][2]), "=r"(d[j][3])
                     : "r"(sbase + P1_OFF_DW + j * 128 + (lane & 7) * 16) : "memory");
}

__device__ __forceinline__ float gelu_s(float y) {
    float u = y * fmaf(y, y, GELU_C);
    float t;
    asm volatile("tanh.approx.f32 %0, %1;\n" : "=f"(t) : "f"(u));
    return fmaf(y, t, y);
}
__device__ __forceinline__ constexpr int p1_reg(int c, int u) { return 16 * (c >> 1) + 4 * (u >> 1) + 2 * (c & 1) + (u & 1); }
template <bool BIG>
__device__ __forceinline__ void p1_pack(int c, uint32_t (&p)[4], uint32_t (&dd)[4], uint32_t (&sq)[4], uint32_t sc2) {
    uint32_t& s = sq[(c >> 2) * 2 + (c & 1)];
    s = (c & 2) ? bf2_fma(p[0], p[0], s) : bf2_mul(p[0], p[0]);
    s = bf2_fma(p[3], p[3], bf2_fma(p[2], p[2], bf2_fma(p[1], p[1], s)));
#pragma unroll
    for (int u = 0; u < 4; u++) {
        uint32_t v;
        if (c & 1) asm("{\n.reg .b16 l, h;\n.reg .b32 f;\nmov.b32 {l, h}, %2;\nmov.b32 f, {h, h};\nmul.rn.bf16x2 %0, %1, f;\n}\n" : "=r"(v) : "r"(p[u]), "r"(sc2));
        else asm("{\n.reg .b16 l, h;\n.reg .b32 f;\nmov.b32 {l, h}, %2;\nmov.b32 f, {l, l};\nmul.rn.bf16x2 %0, %1, f;\n}\n" : "=r"(v) : "r"(p[u]), "r"(sc2));
        if (BIG) v = bf2_mul(v, 0x07800780u);
        if ((c & 3) == 0) dd[u] = v;
        else {
            uint32_t n = dd[u];
            if ((c & 3) == 1) { n <<= 4; dd[u] = __byte_perm(dd[u], 0, 0x2301); }
            if ((c & 3) == 2) dd[u] <<= 4;
            asm("lop3.b32 %0, %1, %2, 0x78007800, 0xd8;\n" : "=r"(p[u]) : "r"(v), "r"(n));
        }
    }
}
__device__ __forceinline__ void p1_store(int c, const uint32_t (&p)[4], uint8_t* hptr) {
    if (c & 3) stg128_cs(hptr + (c >> 2) * H_HALF + ((c & 3) - 1) * 512, p[0], p[1], p[2], p[3]);
}

__device__ __forceinline__ uint32_t p1_parity(uint32_t sbase) {
    uint32_t v;
    asm volatile("ld.shared.u32 %0, [%1];\n" : "=r"(v) : "r"(sbase + P1_OFF_TILE - 4) : "memory");
    return v;
}
template <bool GEN>
__device__ __forceinline__ uint32_t gelu2(uint32_t y, float fs) {
    if (GEN) return pack_bf16(gelu_s(h_lo(y) * fs), gelu_s(h_hi(y) * fs));
    uint32_t g;
    asm("{\n.reg .b32 w;\n"
        "fma.rn.f16x2 w, %1, %1, %2;\n"
        "mul.rn.f16x2 w, w, %1;\n"
        "tanh.approx.f16x2 w, w;\n"
        "fma.rn.f16x2 %0, %1, w, %1;\n}\n" : "=r"(g) : "r"(y), "r"(0x40d940d9u));
    return pack_bf16(h_lo(g), h_hi(g));
}
template <bool GEN, int C0, int C1, class F>
__device__ __forceinline__ void p1_epilogue(F v, uint32_t (&sq)[4], uint32_t (&dd)[4], float (&ssq)[2], uint32_t sc2, uint8_t* hp) {
    const float fs[2] = {__uint_as_float(0x78000000u - (sc2 << 16)), __uint_as_float(0x78000000u - (sc2 & 0xffff0000u))};
#pragma unroll
    for (int c = C0; c < C1; c++) {
        uint32_t p[4];
#pragma unroll
        for (int u = 0; u < 4; u++) p[u] = gelu2<GEN>(v(c, u), fs[c & 1]);
        p1_pack<GEN>(c, p, dd, sq, sc2);
        p1_store(c, p, hp);
    }
    if (C1 == 8) {
#pragma unroll
        for (int r = 0; r < 2; r++) {
            const uint32_t u = bf2_add(sq[r], sq[2 + r]);
            ssq[r] += bf_lo(u) + bf_hi(u);
        }
    }
}
__device__ __forceinline__ void p1_consumer(const uint32_t (&a)[24][4], uint32_t sc2, bool gen, uint32_t sbase, int wg, int w, int lane) {
    const uint32_t bar_full = sbase + P1_OFF_BAR, bar_empty = bar_full + P1_NST * 8;
    const uint32_t empty_remote = mapa(bar_empty, lane & 1);
    const int g = lane >> 2, q = lane & 3, cb = (blockIdx.x % GRP_CTAS) * 2 + wg;
    float ssq[2] = {0.f, 0.f};
    uint32_t acc[32], sq[4] = {}, dd[4] = {}, dfr[P1_DEF * 4 + 1] = {};
    auto from_acc = [&](int c, int u) { return acc[8 * (c >> 1) + 2 * u + (c & 1)]; };
    auto from_dfr = [&](int c, int u) { return dfr[(c - 8 + P1_DEF) * 4 + u]; };
    bool pend = false;
    TSTAMP(0, 1);

    uint8_t* hp = reinterpret_cast<uint8_t*>(g_h) + (size_t)(blockIdx.x / GRP_CTAS) * (2 * H_TILE) + ((cb * 2 + (w >> 1)) * H_STEP + (w & 1) * 1536) + g * 64 + (q ^ (g >> 1)) * 16;
    const uint64_t desc_base = make_desc(sbase, 16, 1024) | (1ull << 62);
#pragma unroll 1
    for (int i = 0;; i++) {
        const int s0 = (i & 1) * 16, par = (i >> 1) & 1;
        const uint64_t d0 = desc_base + (uint64_t)((i & 1) * (LN_TILE / 16));
        TRACE(wg, i, 0);
        mbar_wait(bar_full + s0, par);
        bar_sync(1 + wg, 256);
        TRACE(wg, i, 1);
        uint32_t step, more;
        wg_fence();
#pragma unroll
        for (int k = 0; k < 24; k++) {
            if (k == 12) mbar_wait(bar_full + s0 + 8, par);
            mma_rs_n128(acc, a[k], d0 + (uint64_t)((k >> 2) * 1024 + (k & 3) * 2), k != 0);
            if (k == P1_ARR) bar_arrive(2 - wg, 256);
            if (k % 12 == 11) wg_commit();
            if (P1_DMID && k == 11 && pend) p1_epilogue<false, 8 - P1_DEF, 8 - P1_DEF + P1_DMID>(from_dfr, sq, dd, ssq, sc2, hp);
        }
        asm volatile("ld.shared.v2.u32 {%0, %1}, [%2];\n" : "=r"(step), "=r"(more) : "r"(sbase + P1_OFF_TILE + (i & 3) * 16) : "memory");
        TRACE(wg, i, 2);
        wg_wait<1>();
        if (lane < 2) mbar_arrive_cluster(empty_remote + s0);
        if (P1_DEF > P1_DMID && pend) p1_epilogue<false, 8 - P1_DEF + P1_DMID, 8>(from_dfr, sq, dd, ssq, sc2, hp);
        hp += step;
        TRACE(wg, i, 3);
        wg_wait<0>();
        TRACE(wg, i, 4);
        if (lane < 2) mbar_arrive_cluster(empty_remote + s0 + 8);
        if (gen) p1_epilogue<true, 0, 8>(from_acc, sq, dd, ssq, sc2, hp);
        else {
#pragma unroll
            for (int j = 0; j < P1_DEF * 4; j++) asm volatile("mov.b32 %0, %1;\n" : "=r"(dfr[j]) : "r"(from_acc(8 - P1_DEF + j / 4, j % 4)));
            p1_epilogue<false, 0, 8 - P1_DEF>(from_acc, sq, dd, ssq, sc2, hp);
            pend = true;
        }
        if (!more) break;
    }
    if (P1_DEF && pend) p1_epilogue<false, 8 - P1_DEF, 8>(from_dfr, sq, dd, ssq, sc2, hp);
    TSTAMP(0, 21);
    if (wg == 0) bar_sync(1, 256);
#pragma unroll
    for (int r = 0; r < 2; r++) {
        ssq[r] += __shfl_xor_sync(0xffffffffu, ssq[r], 1);
        ssq[r] += __shfl_xor_sync(0xffffffffu, ssq[r], 2);
        if (q == 0) atomicAdd(&g_sums[p1_parity(sbase)][cb * 64 + w * 16 + r * 8 + g], ssq[r]);
    }
}

__global__ void __cluster_dims__(2, 1, 1) __launch_bounds__(512, 1)
pass1_kernel(const __grid_constant__ CUtensorMap wmap, const __nv_bfloat16* __restrict__ x, const __nv_bfloat16* __restrict__ dw,
             const __nv_bfloat16* __restrict__ w2, const __nv_bfloat16* __restrict__ grn_b, int zero) {
    extern __shared__ __align__(1024) uint8_t smem[];
    const uint32_t sbase = smem_u32(smem);
    const uint32_t bar_full = sbase + P1_OFF_BAR, bar_empty = bar_full + P1_NST * 8, bar_w = bar_empty + P1_NST * 8;
    const int tid = threadIdx.x;
    const int warp = __shfl_sync(0xffffffffu, tid >> 5, 0), lane = tid & 31;
    const uint32_t rank = cluster_rank();
    const int cig = blockIdx.x % GRP_CTAS;
    uint8_t* const ring = reinterpret_cast<uint8_t*>(g_ln);

    TSTAMP(0, 0);
    TRACEW(110 + warp, 0);
    const uint32_t bar_xfull = bar_w + 16, bar_xempty = bar_xfull + 8, bar_done = bar_xfull + 16;
    const uint32_t bar_raw = sbase + P1_OFF_RAW;
    const int ln0 = blockIdx.x >> 2, first = blockIdx.x / GRP_CTAS;
    const uint8_t* xsrc = reinterpret_cast<const uint8_t*>(x) + (size_t)(NGRP * 4 + blockIdx.x) * P1_X;

    if (warp >= 12) {
        reg_dec<40>();
        asm volatile("barrier.cluster.arrive.relaxed.aligned;\n" ::: "memory");
        asm volatile("barrier.cluster.wait.aligned;\n" ::: "memory");
        if (warp == 12) {
            int prev = first - NGRP, t = first, next = t + NGRP;
            const uint32_t rbase = mapa(sbase, lane & 1);
            int i = 1;
#pragma unroll 1
            for (; t < NT_RING; i++) {
                const int s0 = (i & 1) * 2, par = ((i + 1) >> 1 & 1) ^ 1;
                const int round = t / LN_RING, slot = t - round * LN_RING;
                const uint8_t* src = ring + slot * LN_TILE + rank * (P1_SLOT / 2);
                int draw = 0;
                if (rank == 0 && lane == 0) draw = atomicAdd(&g_flag[LN_RING + (cig >> 2)][(cig >> 1) & 1][0], 1u);
                flag_wait<true>(&g_flag[slot][0][0], 4 * round + 4);
                TRACEW(i, 2);
                asm volatile("fence.proxy.async.global;\n" ::: "memory");
                draw = 2 * NGRP + __shfl_sync(0xffffffffu, draw, 0);
#pragma unroll
                for (int h = 0; h < 2; h++) {
                    mbar_wait(bar_empty + (s0 + h) * 8, par);
                    TRACEW(i, 4 + h);
                    if (elect_one()) {
                        mbar_expect_tx(bar_full + (s0 + h) * 8, P1_SLOT + 16 - 16 * h);
                        bulk_g2s_mc(sbase + (s0 + h) * P1_SLOT + rank * (P1_SLOT / 2), src + h * P1_SLOT, P1_SLOT / 2, bar_full + (s0 + h) * 8, (uint16_t)3);
                    }
                    __syncwarp();
                    if (h == 0 && rank == 0 && lane < 2)
                        asm volatile("st.async.shared::cluster.mbarrier::complete_tx::bytes.v4.u32 [%0], {%1, %2, %3, %3}, [%4];\n"
                                     ::"r"(rbase + P1_OFF_TILE + (i & 3) * 16), "r"((t - prev) * (2 * H_TILE)), "r"((int)(next < NT_RING)), "r"(draw),
                                       "r"(rbase + P1_OFF_BAR + s0 * 8) : "memory");
                }
                prev = t;
                t = next;
                next = draw;
                if (rank != 0) {
                    mbar_wait(bar_full + (s0 ^ 2) * 8, ((i - 1) >> 1) & 1);
                    asm volatile("ld.shared.u32 %0, [%1];\n" : "=r"(t) : "r"(sbase + P1_OFF_TILE + ((i - 1) & 3) * 16 + 8) : "memory");
                }
            }
#pragma unroll 1
            for (int j = 2 * i; j < 2 * i + 4; j++) mbar_wait(bar_empty + (j & 3) * 8, ((j + 2) >> 2 & 1) ^ 1);
        } else if (warp == 13) {
            int ph = 0;
            unsigned target = 0;
#pragma unroll 1
            for (int i = ln0 + LN_STEP; i < NT_RING; i += LN_STEP, ph ^= 1) {
                target += ph * (GRP_CTAS / 2);
                xsrc += (size_t)NUM_CTAS * P1_X;
                mbar_wait(bar_xempty, ph);
                if (elect_one()) {
                    mbar_expect_tx(bar_xfull, P1_X);
                    bulk_g2s(sbase + P1_OFF_X, xsrc, P1_X, bar_xfull);
                }
                __syncwarp();
                flag_wait<false>(&g_flag[ln0 + (ph ^ 1) * LN_STEP][1][0], target);
                mbar_wait(bar_done, ph);
                if (elect_one()) mbar_arrive(bar_xfull);
                __syncwarp();
            }
        } else if (warp == 15) {
            if (rank == 1 && lane < 2) mbar_arrive(bar_empty + (2 + lane) * 8);
            const uint32_t par = g_epoch & 1;
            asm volatile("st.shared.u32 [%0], %1;\n" ::"r"(sbase + P1_OFF_TILE - 4), "r"(par) : "memory");
            if (blockIdx.x == 18) g_par = par;
            if (blockIdx.x < 18) reinterpret_cast<float4*>(g_sums[par ^ 1])[blockIdx.x * 32 + lane] = make_float4(0.f, 0.f, 0.f, 0.f);
            bar_arrive(3, 160);
            {
                bar_sync(4, 288);
                mbar_wait(bar_raw + 8, 0);
                const uint32_t o = lane * 16384 + rank * 8192, peer = mapa(sbase, rank ^ 1);
                if (lane < 6)
                    asm volatile("cp.async.bulk.shared::cluster.shared::cta.mbarrier::complete_tx::bytes [%0], [%1], 8192, [%2];\n"
                                 ::"r"(peer + o), "r"(sbase + o), "r"(peer + P1_OFF_BAR + (lane >= 3 ? 8 : 0)) : "memory");
                __syncwarp();
            }
            if (rank == 0) {
                flag_wait<true>(&g_flag[40][1][0], GRP_CTAS / 2);
                const int col = (cig >> 1) * 64 + lane * 2;
                float bsum[2] = {0.f, 0.f}, asum[2] = {0.f, 0.f};
#pragma unroll 2
                for (int k = first * 140; k < min(first * 140 + 140, HID); k++) {
                    const uint32_t v = *reinterpret_cast<const uint32_t*>(w2 + k * C_DIM + col);
                    const float b = __bfloat162float(grn_b[k]), f = __uint_as_float(__ldcg(&g_ex[k]) << 23);
                    bsum[0] = fmaf(b, bf_lo(v), bsum[0]);
                    bsum[1] = fmaf(b, bf_hi(v), bsum[1]);
                    asum[0] = fmaf(f, fabsf(bf_lo(v)), asum[0]);
                    asum[1] = fmaf(f, fabsf(bf_hi(v)), asum[1]);
                }
                float* sums = g_sums[par] + HID + perm32(col);
#pragma unroll
                for (int j = 0; j < 2; j++) {
                    atomicAdd(sums + j, bsum[j]);
                    atomicAdd(sums + C_DIM + j, asum[j]);
                }
                __threadfence();
                __syncwarp();
                if (lane == 0) asm volatile("red.release.gpu.global.add.u32 [%0], 1;\n" ::"l"(&g_flag[LN_RING + 3][0][0]) : "memory");
            }
            int t = first, next = t + NGRP;
            if (rank == 1) {
                mbar_wait(bar_full, 0);
                mbar_wait(bar_full + 8, 0);
                if (lane < 2) mbar_arrive(bar_empty + lane * 8);
            }
#pragma unroll 1
            for (int i = 1; rank == 1 && t < NT_RING; i++) {
                const int s0 = (i & 1) * 16;
                mbar_wait(bar_full + s0, (i >> 1) & 1);
                mbar_wait(bar_full + s0 + 8, (i >> 1) & 1);
                if (lane == 0) asm volatile("red.relaxed.gpu.global.add.u32 [%0], 1;\n" ::"l"(&g_flag[t % LN_RING][1][0]) : "memory");
                t = next;
                asm volatile("ld.shared.u32 %0, [%1];\n" : "=r"(next) : "r"(sbase + P1_OFF_TILE + (i & 3) * 16 + 8) : "memory");
                if (lane < 2) mbar_arrive(bar_empty + s0 + lane * 8);
                TRACEW(i, 3);
            }
        } else if (warp == 14) {
            int ph = 0;
#pragma unroll 1
            for (int i = ln0; i < NT_RING; i += LN_STEP, ph ^= 1) {
                mbar_wait(bar_done, ph);
                TRACEW(i / LN_STEP, 0);
                asm volatile("fence.proxy.async.global;\n" ::: "memory");
                if (elect_one()) asm volatile("red.release.gpu.global.add.u32 [%0], 1;\n" ::"l"(&g_flag[ln0 + ph * LN_STEP][0][0]) : "memory");
                __syncwarp();
                TRACEW(i / LN_STEP, 1);
            }
        }
    } else if (warp >= 8) {
        reg_dec<88>();
        asm volatile("barrier.cluster.arrive.relaxed.aligned;\n" ::: "memory");
        {
            const int l8 = lane & 7, row = (warp - 8) * 4 + (lane >> 3), px = (blockIdx.x & 3) * 32 + row;
            uint32_t d[6][4] = {};
            const int n = (px & 64) + perm32(2 * row + ((px >> 5) & 1));
            uint8_t* const dst0 = ring + ln0 * LN_TILE + n * 128 + ((l8 ^ (n & 7)) << 4);
            const uint32_t src = sbase + P1_OFF_X + ((warp - 8) * 8 + (lane >> 3)) * (C_DIM * 2) + l8 * 16;
            int ph = 0;
            asm volatile("barrier.cluster.wait.aligned;\n" ::: "memory");
#pragma unroll 1
            for (int i = ln0; i < NT_RING; i += LN_STEP, ph ^= 1) {
                TRACE(2, i / LN_STEP, 0);
#pragma unroll 1
                for (int ps = i == ln0 ? -1 : 0; ps < 2; ps++) {
                    if (ps == 0) {
                        if (i == ln0) load_dw(d, sbase, lane);
                        mbar_wait(bar_xfull, ph);
                        TRACE(2, i / LN_STEP, 1);
                    }
                    uint32_t v[6][4];
#pragma unroll
                    for (int j = 0; j < 6; j++)
                        asm volatile("ld.shared.v4.u32 {%0,%1,%2,%3}, [%4];\n"
                                     : "=r"(v[j][0]), "=r"(v[j][1]), "=r"(v[j][2]), "=r"(v[j][3]) : "r"(src + (ps & 1) * (4 * C_DIM * 2) + j * 128) : "memory");
                    ln_row(v, d, zero, ps == 1 && lane == 0 ? bar_xempty : 0);
                    uint8_t* dst = dst0 + ph * (LN_STEP * LN_TILE) + ps * 4096;
#pragma unroll
                    for (int j = 0; j < 6; j++)
                        asm volatile("{\n.reg .pred p;\nsetp.ge.s32 p, %5, 0;\n@p st.global.v4.u32 [%0], {%1,%2,%3,%4};\n}\n"
                                     ::"l"(dst + j * 16384), "r"(v[j][0]), "r"(v[j][1]), "r"(v[j][2]), "r"(v[j][3]), "r"(ps) : "memory");
                    TRACE(2, i / LN_STEP, 3 + (ps & 1));
                }
                asm volatile("fence.proxy.async.global;\nfence.acq_rel.cta;\n" ::: "memory");
                __syncwarp();
                if (lane == 0) mbar_arrive(bar_done);
                TRACE(2, i / LN_STEP, 5);
                TRACE(2, i / LN_STEP, 2);
            }
        }
        const int gw = (warp - 8) * NUM_CTAS + blockIdx.x;
        bar_sync(3, 160);
        if (gw < 288) {
            const int np = (gw % 12) * 32 + lane, kb = gw / 12;
            const __nv_bfloat16* wc = w2 + (size_t)kb * 64 * C_DIM + perm32(np);
            const float* sums = g_sums[p1_parity(sbase)] + HID;
            flag_wait<true>(&g_flag[LN_RING + 3][0][0], NUM_CTAS / 2);
            float z = 0.f;
#pragma unroll
            for (int j = 0; j < C_DIM / 32; j++) z = fmaxf(z, acc_bound(__ldcg(sums + j * 32 + lane), __ldcg(sums + C_DIM + j * 32 + lane)));
            const float sc = __uint_as_float((263u - acc_exp(__uint_as_float(__reduce_max_sync(0xffffffffu, __float_as_uint(z))))) << 23);
#pragma unroll 2
            for (int c = 0; c < 8; c++) {
                float f[8];
#pragma unroll
                for (int e = 0; e < 8; e++)
                    f[e] = __bfloat162float(wc[(c * 8 + e) * C_DIM]) * __uint_as_float(__ldcg(&g_ex[kb * 64 + c * 8 + e]) << 23) * sc;
                g_w2img[(((kb * 4 + (c >> 1)) * 48 + (np >> 3)) * 2 + (c & 1)) * 8 + (np & 7)] =
                    make_uint4(pack_f16(f[0], f[1]), pack_f16(f[2], f[3]), pack_f16(f[4], f[5]), pack_f16(f[6], f[7]));
            }
            asm volatile("fence.proxy.async.global;\n" ::: "memory");
            __threadfence();
            __syncwarp();
            if (lane == 0) asm volatile("red.release.gpu.global.add.u32 [%0], 1;\n" ::"l"(&g_img) : "memory");
        }
    } else {
        if (tid == 0) {
            mbar_init(bar_raw, 1);
            mbar_init(bar_raw + 8, 8);
            asm volatile("fence.mbarrier_init.release.cluster;\n" ::: "memory");
            mbar_expect_tx(bar_raw, P1_SLOT);
            for (int i = 0; i < 6; i++)
                bulk_g2s(sbase + i * 16384 + (rank ^ 1) * 8192, x + (size_t)(first * 128 + rank * 64) * C_DIM + i * 4096, 8192, bar_raw);
        }
        if (tid == 32) {
            mbar_init(bar_raw + 16, 1);
            mbar_init(bar_xfull, 2);
            mbar_init(bar_xempty, 4);
            mbar_init(bar_done, 4);
            asm volatile("fence.mbarrier_init.release.cluster;\n" ::: "memory");
            mbar_expect_tx(bar_raw + 16, C_DIM * 2);
            bulk_g2s(sbase + P1_OFF_DW, dw, C_DIM * 2, bar_raw + 16);
            mbar_expect_tx(bar_xfull, P1_X);
            bulk_g2s(sbase + P1_OFF_X, xsrc, P1_X, bar_xfull);
            mbar_arrive(bar_xfull);
        }
        if (tid == 64) {
            asm volatile("st.shared.v4.u32 [%0], {0, 1, %1, %1};\n" ::"r"(sbase + P1_OFF_TILE), "r"(first + NGRP) : "memory");
            for (int i = 0; i < P1_NST; i++) {
                mbar_init(bar_full + i * 8, 1);
                mbar_init(bar_empty + i * 8, 16 + rank);
                if (i < 2) mbar_expect_tx(bar_full + i * 8, P1_SLOT / 2);
            }
            asm volatile("fence.mbarrier_init.release.cluster;\n" ::: "memory");
            if (blockIdx.x < 64) (&g_half[0][0])[blockIdx.x] = 0;
            else if (blockIdx.x == 64) g_prog = 0;
            else if (blockIdx.x == 65) g_img = 0;
        }
        if (tid == 96) {
            for (int i = 0; i < 2; i++) mbar_init(bar_w + i * 8, 1);
            asm volatile("fence.mbarrier_init.release.cluster;\n" ::: "memory");
        }
        __syncwarp();
        asm volatile("barrier.cluster.arrive.relaxed.aligned;\n" ::: "memory");
        if (tid == 96)
            for (int i = 0; i < 2; i++) {
                mbar_expect_tx(bar_w + i * 8, P1_SLOT);
                tma2(sbase + (2 + i) * P1_SLOT, &wmap, cig * 128 + i * 64, 0, bar_w + i * 8);
                tma2(sbase + (2 + i) * P1_SLOT + P1_SLOT / 2, &wmap, cig * 128 + i * 64, 192, bar_w + i * 8);
            }
        __syncwarp();
        reg_inc<P1_REGS>();
        TRACEW(110 + warp, 1);
        const int wg = warp >> 2, w = warp & 3;
        uint32_t a[24][4], ex[2], gen;
        const uint32_t wsrc = sbase + (2 + wg) * P1_SLOT + ((lane >> 4) * 8 + (lane & 7)) * 128 + (((2 * w + ((lane >> 3) & 1)) ^ (lane & 7)) << 4);
        gdc_launch();
        asm volatile("barrier.cluster.wait.aligned;\n" ::: "memory");
#pragma unroll 1
        for (int it = P1_WARM ? 1 - wg : 1; it < 2; it++) {
            if (it) {
                const int n = warp * 8 + (lane >> 3), px = (n & 1) * 32 + (n >> 5) * 4 + ((n >> 1) & 1) * 8 + ((n >> 3) & 3);
                uint32_t d[6][4] = {};
#pragma unroll 1
                for (int ps = P1_WARM ? wg - 1 : -1; ps < 2; ps++) {
                    if (ps == 0) {
                        load_dw(d, sbase, lane);
                        mbar_wait(bar_raw, 0);
                    }
                    TRACEW(110 + warp, 2 + (ps == 0));
                    uint32_t v[6][4];
#pragma unroll
                    for (int j = 0; j < 6; j++) {
                        const uint32_t o = (px + (ps & 1) * 16) * (C_DIM * 2) + j * 128;
                        asm volatile("ld.shared.v4.u32 {%0,%1,%2,%3}, [%4];\n" : "=r"(v[j][0]), "=r"(v[j][1]), "=r"(v[j][2]), "=r"(v[j][3])
                                     : "r"(sbase + (rank ^ 1) * 8192 + (lane & 7) * 16 + o + (o & ~8191u)) : "memory");
                    }
                    ln_row(v, d, zero, 0);
                    const uint32_t p = sbase + (rank * 64 + n + (ps & 1) * 4) * 128 + (((lane ^ n ^ (ps & 1) * 4) & 7) << 4);
#pragma unroll
                    for (int j = 0; j < 6; j++)
                        asm volatile("st.shared.v4.u32 [%4], {%0,%1,%2,%3};\n"
                                     ::"r"(v[j][0]), "r"(v[j][1]), "r"(v[j][2]), "r"(v[j][3]), "r"(p + j * 16384) : "memory");
                }
                asm volatile("fence.proxy.async.shared::cta;\n" ::: "memory");
                __syncwarp();
                if (lane == 0) mbar_arrive_cluster(mapa(bar_raw + 8, rank ^ 1));
                bar_arrive(4, 288);
                if (wg == 1) bar_arrive(1, 256);
                TRACEW(110 + warp, 4);
                mbar_wait(bar_w + wg * 8, 0);
                TRACEW(110 + warp, 5);
            }
#pragma unroll
            for (int k = 0; k < 24; k++) ldsm4t(a[k], wsrc + k * 2048);
#pragma unroll
            for (int r = 0; r < 2; r++) {
                float t = 0.f;
#pragma unroll
                for (int j = 0; j < 6; j++) {
                    uint32_t c = bf2_mul(a[4 * j][r], a[4 * j][r]);
#pragma unroll
                    for (int k = 1; k < 8; k++) c = bf2_fma(a[4 * j + k / 2][r + (k & 1) * 2], a[4 * j + k / 2][r + (k & 1) * 2], c);
                    t += bf_lo(c) + bf_hi(c);
                }
                t += __shfl_xor_sync(0xffffffffu, t, 1);
                t += __shfl_xor_sync(0xffffffffu, t, 2);
                ex[r] = min(max(__float_as_uint(13.9f * __fsqrt_rn(t)) >> 23, 72u), 198u);
            }
            asm volatile("{\n.reg .pred p;\nsetp.gt.u32 p, %1, 16;\nbar.red.or.pred p, %2, 128, p;\nselp.u32 %0, 1, 0, p;\n}\n"
                         : "=r"(gen) : "r"(max(ex[0] - 125u, ex[1] - 125u)), "r"(5 + wg) : "memory");
            gen = __shfl_sync(0xffffffffu, gen, 0);
            if (gen) {
#pragma unroll
                for (int k = 0; k < 24; k++)
#pragma unroll
                    for (int j = 0; j < 4; j++) a[k][j] = bf2_mul(a[k][j], (268u - ex[j & 1]) * 0x00800080u);
            }
#pragma unroll
            for (int k = 0; k < 24; k++)
#pragma unroll
                for (int j = 0; j < 4; j++) {
                    a[k][j] = bf2_as_h2(bf2_mul(a[k][j], 0x07800780u));
                    asm volatile("" : "+r"(a[k][j]));
                }
            TRACEW(110 + warp, 6);
        }
        if ((lane & 3) < 2) g_ex[cig * 128 + wg * 64 + w * 16 + (lane & 1) * 8 + (lane >> 2)] = lane & 1 ? ex[1] : ex[0];
        if (lane < 4) mbar_arrive_cluster(mapa(bar_empty, lane & 1) + (2 + (lane >> 1)) * 8);
        TRACEW(110 + warp, 7);
        p1_consumer(a, (gen ? 0x7f007f00u : 0x47004700u) - ((ex[0] | ex[1] << 16) << 7), gen, sbase, wg, w, lane);
        TSTAMP(0, 30);
    }
}

#define P2_NB_ 5
#define P2_NA_ 5
#define P2_DELTA_ 7
#define P2_EXTRA 0
#define P2_HSLEEP 64
#define P2_T0 5
#define P2_TS 11
constexpr int P2_B = 24576, P2_NB = P2_NB_;
constexpr int P2_A = 3072, P2_NA = P2_NA_;
constexpr int P2_XROW = C_DIM * 2;
constexpr int P2_OFF_A = P2_B * P2_NB;
constexpr int P2_OFF_X = P2_OFF_A + 3 * P2_NA * P2_A;
constexpr int P2_XHALF = 32 * P2_XROW + 64;
constexpr int P2_OFF_BIAS = P2_OFF_X + 64 * P2_XROW + 128;
constexpr int P2_OFF_ONES = P2_OFF_BIAS + 48 * 128;
constexpr int P2_OFF_GRN = P2_OFF_ONES + 256;
constexpr int P2_OFF_RED = P2_OFF_GRN + HID * 2;
constexpr int P2_OFF_BAR = P2_OFF_RED + 256;
constexpr int P2_SMEM = P2_OFF_BAR + (2 * P2_NB + 6 * P2_NA + 3) * 8;
constexpr int P2_LAG = 16;
constexpr int P2_NCL = NUM_CTAS / 2, P2_ITEMS = NT128 / P2_NCL, P2_SHARED = NT128 - P2_ITEMS * P2_NCL;
constexpr int P2_POS = P2_LAG * (P2_ITEMS + 2);
constexpr int P2_XC = 8 * P2_XROW;
constexpr int P2_DELTA = P2_DELTA_;
__device__ __forceinline__ int p2_tile(int cl, int n) {
    return n == 0 ? NT128 - 1 - cl : n < 0 || n == P2_ITEMS ? NT128 - 1 - P2_NCL - (cl >> 1) : cl + P2_NCL * (n - 1);
}

#define P2_EG 2
__device__ __forceinline__ void p2_epilogue(const uint32_t (&acc0)[48], const uint32_t (&acc1)[48], uint32_t sx, float up, int zero) {
    uint32_t v[2][P2_EG][4];
    auto load = [&](int c, uint32_t a) {
#pragma unroll
        for (int j = 0; j < P2_EG; j++) {
            const int u = c * P2_EG + j;
            asm volatile("ld.shared.v4.u32 {%0,%1,%2,%3}, [%4];\n" : "=r"(v[c & 1][j][0]), "=r"(v[c & 1][j][1]), "=r"(v[c & 1][j][2]), "=r"(v[c & 1][j][3])
                         : "r"(a + (u >> 1) * 64 + (u & 1) * 4 * P2_XROW) : "memory");
        }
    };
    load(0, sx);
#pragma unroll
    for (int c = 0; c < 24 / P2_EG; c++) {
        if (c + 1 < 24 / P2_EG) load(c + 1, sx + (v[c & 1][P2_EG - 1][0] & zero));
#pragma unroll
        for (int j = 0; j < P2_EG; j++) {
            const int u = c * P2_EG + j, i = 8 * ((u >> 1) % 6) + (u & 1);
            const uint32_t (&acc)[48] = u < 12 ? acc0 : acc1;
            uint32_t (&w)[4] = v[c & 1][j];
#pragma unroll
            for (int e = 0; e < 4; e++) w[e] = bf2_add(pack_bf16(h_lo(acc[i + 2 * e]) * up, h_hi(acc[i + 2 * e]) * up), w[e]);
            asm volatile("st.shared.v4.u32 [%4], {%0,%1,%2,%3};\n" ::"r"(w[0]), "r"(w[1]), "r"(w[2]), "r"(w[3]),
                         "r"(sx + (u >> 1) * 64 + (u & 1) * 4 * P2_XROW) : "memory");
        }
    }
}

__device__ __forceinline__ void p2_unpack(uint32_t (&u)[4], uint32_t o1, uint32_t o2, uint32_t o3) {
    u[2] = o1 & 0x87ff87ffu;
    u[1] = o2 & 0x87ff87ffu;
    u[3] = o3 & 0x87ff87ffu;
    u[0] = __byte_perm((o2 & 0x78007800u) | ((o3 >> 4) & 0x07800780u), 0, 0x2301) | ((o1 >> 4) & 0x07800780u);
}
__device__ __forceinline__ void p2_epilogue_add(const uint32_t (&acc)[48], uint8_t* o, float f, int zero) {
#pragma unroll
    for (int t = 0; t < 12; t++) {
        uint32_t v[4];
#pragma unroll
        for (int e = 0; e < 4; e++) {
            v[e] = acc[8 * (t >> 1) + (t & 1) + 2 * e];
            asm volatile("" : "+r"(v[e]));
            v[e] = pack_bf16(h_lo(v[e]) * f, h_hi(v[e]) * f);
        }
        asm volatile("red.global.add.noftz.v4.bf16x2 [%0], {%1,%2,%3,%4};\n" ::"l"(o + (t >> 1) * 64 + (t & 1) * 4 * P2_XROW),
                     "r"(v[0]), "r"(v[1]), "r"(v[2]), "r"(v[3]) : "memory");
        if (t % 3 == 2) sched_break(zero);
    }
}

__global__ void __cluster_dims__(2, 1, 1) __launch_bounds__(512, 1)
pass2_kernel(const __nv_bfloat16* __restrict__ x, const __nv_bfloat16* __restrict__ grn_g, __nv_bfloat16* __restrict__ out, int zero) {
    extern __shared__ __align__(1024) uint8_t smem[];
    const uint32_t sbase = smem_u32(smem);
    const uint32_t bar_bfull = sbase + P2_OFF_BAR, bar_bempty = bar_bfull + P2_NB * 8;
    const uint32_t bar_afull = bar_bempty + P2_NB * 8, bar_aempty = bar_afull + 3 * P2_NA * 8;
    const uint32_t bar_xfull = bar_aempty + 3 * P2_NA * 8, bar_oready = bar_xfull + 8, s_pos = bar_xfull + 16;
    int tid;
    asm volatile("mov.u32 %0, %%tid.x;\n" : "=r"(tid));
    const int warp = __shfl_sync(0xffffffffu, tid >> 5, 0), lane = tid & 31;
    const uint32_t rank = cluster_rank();
    const int cl = blockIdx.x >> 1, pair = cl >> 1;
    const int k0 = (4 * pair + (cl & 1) * 32) % 48;
    const int head = pair < P2_SHARED && !(cl & 1), tail = pair < P2_SHARED && (cl & 1);

    uint32_t par, gg[4];
    float pre[4];
    if (warp < 12) {
        asm volatile("ld.global.cg.u32 %0, [%1];\n" : "=r"(par) : "l"(&g_par) : "memory");
#pragma unroll
        for (int i = 0; i < 4; i++) {
            asm volatile("ld.global.cg.f32 %0, [%1];\n" : "=f"(pre[i]) : "l"(&g_sums[i & 1][HID + (i >> 1) * C_DIM + tid]) : "memory");
            asm volatile("ld.global.nc.u16 %0, [%1];\n" : "=r"(gg[i]) : "l"(grn_g + tid + 384 * i) : "memory");
        }
    }
    TSTAMP(1, 0);
    if (tid == 384) {
        for (int i = 0; i < P2_NB; i++) {
            mbar_init(bar_bfull + i * 8, 1);
            mbar_init(bar_bempty + i * 8, 24);
        }
        for (int i = 0; i < 3 * P2_NA; i++) {
            mbar_init(bar_afull + i * 8, 1);
            mbar_init(bar_aempty + i * 8, 4);
        }
        mbar_init(bar_xfull, 2);
        mbar_init(bar_oready, 4);
        asm volatile("st.shared.u32 [%0], 0;\n" ::"r"(s_pos) : "memory");
        asm volatile("fence.mbarrier_init.release.cluster;\n" ::: "memory");
    }
    __syncthreads();
    cluster_sync_relaxed();

    if (warp >= 12) {
        reg_dec<32>();
        if (warp == 12) {
            const uint8_t* wsrc = reinterpret_cast<const uint8_t*>(g_w2img) + rank * (P2_B / 2);
            int st = 0, ph = 1, kb = k0;
            const int busy = head ? 0 : tail ? P2_POS - 24 : P2_POS;
            flag_wait<true>(&g_img, 288);
            asm volatile("fence.proxy.async.global;\n" ::: "memory");
#pragma unroll 1
            for (int p = 0; p < P2_POS; p++) {
                mbar_wait(bar_bempty + st * 8, ph);
                TR2P(p, 0);
                if (elect_one()) {
                    mbar_expect_tx(bar_bfull + st * 8, P2_B);
                    bulk_g2s_mc(sbase + st * P2_B + rank * (P2_B / 2), wsrc + kb * P2_B, P2_B / 2, bar_bfull + st * 8, (uint16_t)3);
                    asm volatile("st.volatile.shared.u32 [%0], %1;\n" ::"r"(s_pos), "r"(p) : "memory");
                    const int idle = ((unsigned)(p - P2_LAG) >= P2_POS - 2 * P2_LAG) + ((unsigned)(p - 2 * P2_LAG) >= P2_POS - 4 * P2_LAG && (unsigned)(p - busy) >= 24);
                    if (idle) asm volatile("mbarrier.arrive.shared::cta.b64 _, [%0], %1;\n" ::"r"(bar_bempty + st * 8), "r"(idle * 8) : "memory");
                    if (rank == 0) asm volatile("red.relaxed.gpu.global.add.u32 [%0], 1;\n" ::"l"(&g_prog) : "memory");
                }
                __syncwarp();
                if (++st == P2_NB) { st = 0; ph ^= 1; }
                if (++kb == 48) kb = 0;
            }
            mbar_wait(bar_bempty + st * 8, ph);
            if (lane == 0) mbar_arrive(bar_bfull + st * 8);
#pragma unroll 1
            for (int p = 1; p < P2_NB; p++) {
                if (++st == P2_NB) { st = 0; ph ^= 1; }
                mbar_wait(bar_bempty + st * 8, ph);
            }
        } else if (warp == 13) {
            const uint8_t* src[3];
            int n[3], left[3], wrap[3];
            uint32_t st[3];
            auto item = [&](int w) {
                int u = k0 + (n[w] < 0 ? 0 : n[w] == P2_ITEMS ? 40 : w * P2_LAG);
                if (u >= 48) u -= 48;
                left[w] = n[w] < 0 || n[w] == P2_ITEMS ? 24 : 48;
                wrap[w] = left[w] - (48 - u);
                src[w] = reinterpret_cast<const uint8_t*>(g_h) + (size_t)p2_tile(cl, n[w]) * (2 * H_TILE) + rank * H_HALF + u * H_STEP;
            };
#pragma unroll
            for (int w = 0; w < 3; w++) {
                n[w] = w == 2 && head ? -1 : w;
                st[w] = 0x80000000u;
                item(w);
            }
            gdc_wait();
#pragma unroll 1
            for (int done = 0; done < 3;) {
                bool idle = true;
#pragma unroll
                for (int w = 0; w < 3; w++) {
                    const uint32_t o = (st[w] & 0xff) + w * P2_NA * 8;
                    if (left[w] >= 0 && mbar_test(bar_aempty + o, st[w] >> 31)) {
                        idle = false;
                        if (left[w] == 0) {
                            if (lane == 0) mbar_arrive(bar_afull + o);
                            left[w] = -1;
                            done++;
                        } else {
                            if (elect_one()) {
                                mbar_expect_tx(bar_afull + o, P2_A);
                                bulk_g2s(sbase + P2_OFF_A + o * (P2_A / 8), src[w], P2_A, bar_afull + o);
                            }
                            __syncwarp();
                            src[w] += H_STEP;
                            st[w] += 8;
                            if ((st[w] & 0xff) == P2_NA * 8) st[w] ^= 0x80000000u | (P2_NA * 8);
                            if (--left[w] == wrap[w]) src[w] -= 48 * H_STEP;
                            if (left[w] == 0 && (n[w] += 3) < P2_ITEMS + tail) item(w);
                        }
                    }
                }
                if (idle) __nanosleep(P2_HSLEEP);
                SAFE_BREAK
            }
        } else if (warp == 14) {
            const uint32_t sx = sbase + P2_OFF_X;
            size_t o = 0;
            auto pace = [&](int target) {
                int v;
                while (true) {
                    asm volatile("ld.volatile.shared.u32 %0, [%1];\n" : "=r"(v) : "r"(s_pos) : "memory");
                    if (v * 16 >= target) break;
                    __nanosleep(100);
                    SAFE_BREAK
                }
            };
#pragma unroll 1
            for (int n = -head; n <= P2_ITEMS; n++) {
                const size_t on = (size_t)(2 * p2_tile(cl, n) + rank) * (64 * C_DIM * 2);
                const bool st = n + head > 0, ld = n < P2_ITEMS;
                if (st) mbar_wait(bar_oready, (n - 1 + head) & 1);
                TR2P(n + 1, 1);
                if (lane == 0) {
                    if (n == 1 && head) {
                        asm volatile("cp.async.bulk.wait_group 0;\nfence.proxy.async.global;\n" ::: "memory");
                        asm volatile("st.release.gpu.global.u32 [%0], 1;\n" ::"l"(&g_half[pair][rank]) : "memory");
                    }
                    if (ld) mbar_expect_tx(bar_xfull, 64 * C_DIM * 2);
                    int t = st && n < P2_ITEMS - 1 ? (P2_LAG * (n + 2) + P2_T0 - 1) * 16 : -1024;
#pragma unroll 1
                    for (int c = 0; st && c < 64 * P2_XROW; c += P2_XC) {
                        pace(t += P2_TS);
                        bulk_s2g(reinterpret_cast<uint8_t*>(out) + o + c, sx + c + (c >= 32 * P2_XROW ? 64 : 0), P2_XC);
                    }
                    asm volatile("cp.async.bulk.commit_group;\ncp.async.bulk.wait_group.read 0;\n" ::: "memory");
#pragma unroll 1
                    for (int c = 0; ld && c < 64 * P2_XROW; c += P2_XC) {
                        pace(t += P2_TS);
                        bulk_g2s(sx + c + (c >= 32 * P2_XROW ? 64 : 0), reinterpret_cast<const uint8_t*>(x) + on + c, P2_XC, bar_xfull);
                    }
                    TR2P(n + 1, 2);
                    if (rank == 0 && n > 0 && n < P2_ITEMS - 2)
                        flag_wait<false>(&g_prog, P2_NCL * (P2_LAG * (n + 3) + P2_EXTRA) + (tail ? P2_SHARED - P2_NCL : P2_SHARED) * P2_DELTA);
                    if (ld) mbar_arrive(bar_xfull);
                    TR2P(n + 1, 3);
                }
                __syncwarp();
                o = on;
            }
            asm volatile("cp.async.bulk.wait_group 0;\n" ::: "memory");
            TR2P(30, 1);
        }
    } else {
        reg_inc<160>();
        const int wg = warp >> 2, w = warp & 3, g = lane >> 2, q = lane & 3;
        const uint32_t sx = sbase + P2_OFF_X + (g & 1) * P2_XHALF + (w * 8 + (g >> 1)) * P2_XROW + q * 16;
        const uint32_t af = bar_afull + wg * P2_NA * 8, ae = bar_aempty + wg * P2_NA * 8;
        const uint32_t s_a = sbase + P2_OFF_A - bar_afull * (P2_A / 8) + (lane >> 3) * 512 + (lane & 7) * 64 +
                             ((w ^ ((lane & 7) >> 1)) << 4);
        uint32_t acc0[48], acc1[48], dn;
        float up;
        uint4 a0[2], a1[2];
        int st = 0, ph = 0;

        {
            float4* s_red = reinterpret_cast<float4*>(smem + P2_OFF_RED);
            const float* sums = g_sums[par];
            float gx[4], part = 0.f, mx = 0.f;
            if (tid < 16) reinterpret_cast<uint4*>(smem + P2_OFF_ONES)[tid] = make_uint4(tid < 8 ? 0x3c003c00u : 0u, 0u, 0u, 0u);
            TSTAMP(1, 27);
            gdc_wait();
            TSTAMP(1, 1);
#pragma unroll
            for (int i = 0; i < 4; i++) gx[i] = __ldcg(sums + tid + 384 * i);
            if (blockIdx.x == 120 && tid < (LN_RING + 4) * 2) (&g_flag[0][0][0])[tid * 8] = 0;
            if (blockIdx.x == 121 && tid == 0) atomicAdd(&g_epoch, 1u);
            const float bias = pre[0] + pre[1];
            float z = __uint_as_float(__reduce_max_sync(0xffffffffu, __float_as_uint(acc_bound(bias, pre[2] + pre[3]))));
#pragma unroll
            for (int i = 0; i < 4; i++) {
                asm("sqrt.approx.f32 %0, %1;\n" : "=f"(gx[i]) : "f"(fmaf(gx[i], HSCALE * HSCALE, 1e-6f)));
                part += gx[i];
                gx[i] *= bf_lo(gg[i]);
                mx = fmaxf(mx, fabsf(gx[i]));
            }
#pragma unroll
            for (int o = 16; o > 0; o >>= 1) part += __shfl_xor_sync(0xffffffffu, part, o);
            mx = __uint_as_float(__reduce_max_sync(0xffffffffu, __float_as_uint(mx)));
            TSTAMP(1, 26);
            if (lane == 0) s_red[warp] = make_float4(part, mx, z, 0.f);
            bar_sync(1, 384);
            float tot = 0.f;
            {
                const float4 t = s_red[min(lane & 15, 11)];
                tot = (lane & 15) < 12 ? t.x : 0.f;
#pragma unroll
                for (int o = 8; o > 0; o >>= 1) tot += __shfl_xor_sync(0xffffffffu, tot, o);
                mx = __uint_as_float(__reduce_max_sync(0xffffffffu, __float_as_uint(t.y)));
                z = __uint_as_float(__reduce_max_sync(0xffffffffu, __float_as_uint(t.z)));
            }
            const float inv = __fdividef(1.0f, fmaf(tot, 1.0f / HID, 1e-6f));
#pragma unroll
            for (int i = 0; i < 4; i++) {
                const int k = tid + 384 * i;
                *reinterpret_cast<__nv_bfloat16*>(smem + P2_OFF_GRN + (k >> 5) * 64 + ((k >> 1) & 3) * 16 + ((k >> 3) & 3) * 4 + (k & 1) * 2) =
                    __float2bfloat16(gx[i] * inv);
            }
            const uint32_t j = max(__float_as_uint(fmaf(mx, inv, 1.0f) * 1.01f) >> 23, 130u) - 130u;
            dn = __shfl_sync(0xffffffffu, j ? (127u - j) * 0x00800080u : 0u, 0);
            const uint32_t e = min(acc_exp(z) - 9u + j, 253u);
            up = HSCALE * __uint_as_float(e << 23);
            const float b = bias * (1.0f / HSCALE) * __uint_as_float((254u - e) << 23);
            *reinterpret_cast<uint4*>(smem + P2_OFF_BIAS + tid * 16) = make_uint4(pack_f16(b, b - h_lo(pack_f16(b, 0.f))), 0u, 0u, 0u);
            TSTAMP(1, 25);
            asm volatile("fence.proxy.async.shared::cta;\n" ::: "memory");
            bar_sync(1, 384);
        }
        TSTAMP(1, 28);
        const uint32_t s_t = sbase + P2_OFF_GRN + q * 16;
        const int first = wg == 2 && head ? 0 : wg * P2_LAG;
        int kt = (k0 + first) % 48;

        int pos = first;
        const int who = __shfl_sync(0xffffffffu, lane == 2 ? 0 : lane < 2 ? 1 : 2, lane);
        const uint32_t rel0 = who ? mapa(bar_bempty, lane & 1) : mapa(ae, rank), rel1 = rel0 + (who ? P2_NB : P2_NA) * 8;
        uint32_t rel = rel1 - 8;
        auto next_rel = [&](bool go) {
            if (go) rel += 8;
            if (rel == rel1) rel = rel0;
        };
        auto release_b = [&]() {
            next_rel(who == 1);
            if (who == 1) mbar_arrive_cluster(rel);
        };
        auto seek = [&](int p) {
            st = p % P2_NB;
            ph = p / P2_NB & 1;
            if (who == 1) rel = (st ? rel0 + st * 8 : rel1) - 8;
            int v;
            while (true) {
                asm volatile("ld.volatile.shared.u32 %0, [%1];\n" : "=r"(v) : "r"(s_pos) : "memory");
                if (v >= p) break;
                __nanosleep(200);
                SAFE_BREAK
            }
        };
        auto publish = [&]() {
            asm volatile("fence.proxy.async.shared::cta;\n" ::: "memory");
            __syncwarp();
            if (who == 0) mbar_arrive(bar_oready);
        };
        bool ok_a, pend = false;
        uint32_t abar = af, pa = 0;
        auto fetch = [&](uint4 (&a)[2]) {
            uint32_t u0[4], u1[4];
            const uint32_t src = s_a + abar * (P2_A / 8);
            abar += 8;
            if (abar == af + P2_NA * 8) { abar = af; pa ^= 0x80000000u; }
            uint32_t t[4];
            asm volatile("ld.shared.v4.u32 {%0,%1,%2,%3}, [%4];\n" : "=r"(t[0]), "=r"(t[1]), "=r"(t[2]), "=r"(t[3]) : "r"(s_t + kt * 64) : "memory");
            const bool ok_b = mbar_test(bar_bfull + st * 8, ph);
            ok_a = mbar_test(abar, pa >> 31);
            uint32_t o[6];
            asm volatile("ldmatrix.sync.aligned.m8n8.x4.trans.shared.b16 {%0,%1,%2,%3}, [%4];\n"
                         : "=r"(o[0]), "=r"(o[1]), "=r"(o[2]), "=r"(o[3]) : "r"(src) : "memory");
            asm volatile("ldmatrix.sync.aligned.m8n8.x2.trans.shared.b16 {%0,%1}, [%2];\n"
                         : "=r"(o[4]), "=r"(o[5]) : "r"(src + 2048) : "memory");
            p2_unpack(u0, o[0], o[1], o[2]);
            p2_unpack(u1, o[3], o[4], o[5]);
#pragma unroll
            for (int i = 0; i < 4; i++) {
                u0[i] = bf2_fma(u0[i], t[i >> 1], u0[i]);
                u1[i] = bf2_fma(u1[i], t[2 + (i >> 1)], u1[i]);
            }
            if (dn) {
#pragma unroll
                for (int i = 0; i < 4; i++) {
                    u0[i] = bf2_mul(u0[i], dn);
                    u1[i] = bf2_mul(u1[i], dn);
                }
            }
            a[0] = make_uint4(bf2_as_h2(u0[0]), bf2_as_h2(u0[1]), bf2_as_h2(u0[2]), bf2_as_h2(u0[3]));
            a[1] = make_uint4(bf2_as_h2(u1[0]), bf2_as_h2(u1[1]), bf2_as_h2(u1[2]), bf2_as_h2(u1[3]));
            if (++kt == 48) kt = 0;
            if (!ok_b) mbar_wait(bar_bfull + st * 8, ph);
        };
        auto step = [&](const uint4 (&a)[2], uint4 (&an)[2], int thr) {
            TR2(0);
            const uint64_t db = make_desc(sbase + st * P2_B, 128, 256);
            wg_fence();
            mma_rs_n192(acc0, a[0], db);
            mma_rs_n192(acc1, a[0], db + 384);
            mma_rs_n192(acc0, a[1], db + 768);
            mma_rs_n192(acc1, a[1], db + 768 + 384);
            wg_commit();
            next_rel(who < thr);
            if (++st == P2_NB) { st = 0; ph ^= 1; }
            wg_wait<1>();
            if (!ok_a) {
                if (who < thr) mbar_arrive_cluster(rel);
                if (thr == 1 && pend) publish();
                thr = 0;
                mbar_wait(abar, pa >> 31);
            }
            if (who < thr) mbar_arrive_cluster(rel);
            fetch(an);
            pos++;
        };
        seek(first);
        mbar_wait(af, 0);
        fetch(a0);
#pragma unroll 1
        for (int n = wg == 2 && head ? -1 : wg;; n += 3) {
            TSTAMP(1, 2 + n);
            const uint64_t ones = make_desc(sbase + P2_OFF_ONES + (n == P2_ITEMS ? 128 : 0), n == P2_ITEMS ? 0 : 128, 0);
            wg_fence();
            mma_ss_n192_init(acc0, ones, make_desc(sbase + P2_OFF_BIAS, 0, 128));
            mma_ss_n192_init(acc1, ones, make_desc(sbase + P2_OFF_BIAS + 3072, 0, 128));
            wg_commit();
            const int p0 = n < 0 || n == P2_ITEMS ? 12 : 0;
            const bool more = n + 3 < P2_ITEMS + tail;
#pragma unroll 1
            for (int p = p0; p < 24; p++) {
                step(a0, a1, p == p0 ? 1 : 2);
                step(a1, a0, 2);
            }
            if (n == P2_ITEMS) {
                flag_wait<true>(&g_half[pair][rank], 1);
                TR2(1);
                wg_wait<0>();
                TR2(2);
                release_b();
                uint8_t* o = reinterpret_cast<uint8_t*>(out) + (size_t)((2 * p2_tile(cl, -1) + rank) * 64 + (g & 1) * 32 + w * 8 + (g >> 1)) * P2_XROW + q * 16;
                p2_epilogue_add(acc0, o, up, zero);
                p2_epilogue_add(acc1, o + 384, up, zero);
                TR2(3);
                break;
            }
            mbar_wait(bar_xfull, (n + head) & 1);
            TR2(1);
            wg_wait<0>();
            TR2(2);
            release_b();
            __syncwarp();
            p2_epilogue(acc0, acc1, sx, up, zero);
            TR2(3);
            if (!more) {
                publish();
                break;
            }
            pend = true;
            ok_a = false;
            if (n < 0 || n + 3 == P2_ITEMS) {
                publish();
                pend = false;
                seek(n < 0 ? 2 * P2_LAG : P2_POS - 24);
                if (abar == af) { abar = af + P2_NA * 8; pa ^= 0x80000000u; }
                abar -= 8;
                kt += 7;
                if (kt >= 48) kt -= 48;
                fetch(a0);
                pos += 8;
            }
        }
        TSTAMP(1, 30);
    }
}

}

extern "C" void kernel_launch(void* const* d_in, const int* in_sizes, int n_in, void* d_out, int out_size) {
    const __nv_bfloat16* x = (const __nv_bfloat16*)d_in[0];
    const __nv_bfloat16* dw = (const __nv_bfloat16*)d_in[1];
    const __nv_bfloat16* w1 = (const __nv_bfloat16*)d_in[2];
    const __nv_bfloat16* w2 = (const __nv_bfloat16*)d_in[3];
    const __nv_bfloat16* grn_g = (const __nv_bfloat16*)d_in[4];
    const __nv_bfloat16* grn_b = (const __nv_bfloat16*)d_in[5];
    __nv_bfloat16* out = (__nv_bfloat16*)d_out;

    cudaFuncSetAttribute(pass1_kernel, cudaFuncAttributeMaxDynamicSharedMemorySize, P1_SMEM);
    cudaFuncSetAttribute(pass2_kernel, cudaFuncAttributeMaxDynamicSharedMemorySize, P2_SMEM);

    typedef CUresult (*EncodeFn)(CUtensorMap*, CUtensorMapDataType, cuuint32_t, void*, const cuuint64_t*, const cuuint64_t*,
                                 const cuuint32_t*, const cuuint32_t*, CUtensorMapInterleave, CUtensorMapSwizzle,
                                 CUtensorMapL2promotion, CUtensorMapFloatOOBfill);
    static EncodeFn encode = nullptr;
    if (!encode) {
        cudaDriverEntryPointQueryResult qres;
        cudaGetDriverEntryPoint("cuTensorMapEncodeTiled", (void**)&encode, cudaEnableDefault, &qres);
    }
    CUtensorMap wmap;
    const cuuint64_t gdim[2] = {HID, C_DIM};
    const cuuint64_t gstr[1] = {HID * 2};
    const cuuint32_t box[2] = {64, 192}, estr[2] = {1, 1};
    CUresult er = encode(&wmap, CU_TENSOR_MAP_DATA_TYPE_BFLOAT16, 2, (void*)w1, gdim, gstr, box, estr, CU_TENSOR_MAP_INTERLEAVE_NONE,
           CU_TENSOR_MAP_SWIZZLE_128B, CU_TENSOR_MAP_L2_PROMOTION_L2_128B, CU_TENSOR_MAP_FLOAT_OOB_FILL_NONE);
    if (er != CUDA_SUCCESS) printf("tensor map encode failed %d\n", (int)er);

    pass1_kernel<<<NUM_CTAS, 512, P1_SMEM>>>(wmap, x, dw, w2, grn_b, 0);

    cudaLaunchAttribute attr[1];
    attr[0].id = cudaLaunchAttributeProgrammaticStreamSerialization;
    attr[0].val.programmaticStreamSerializationAllowed = 1;
    cudaLaunchConfig_t cfg = {};
    cfg.gridDim = dim3(NUM_CTAS);
    cfg.stream = 0;
    cfg.attrs = attr;
    cfg.numAttrs = 1;
    cfg.blockDim = dim3(512);
    cfg.dynamicSmemBytes = P2_SMEM;
    cudaLaunchKernelEx(&cfg, pass2_kernel, x, grn_g, out, 0);
}
```

```cpp
#include <cuda.h>
#include <cuda_runtime.h>
#include <cuda_bf16.h>
#include <stdint.h>
#include <stdio.h>

namespace {

constexpr int M_TOTAL = 384 * 384;
constexpr int C_DIM   = 384;
constexpr int HID     = 1536;
constexpr int NT128   = M_TOTAL / 128;
constexpr int NUM_CTAS = 132;

constexpr int NGRP = 11, GRP_CTAS = 12;
constexpr int LN_STEP = NUM_CTAS / 4, LN_RING = 2 * LN_STEP;
constexpr int NT_RING = NT128 - NGRP;
constexpr int LN_TILE = 128 * C_DIM * 2;
constexpr int H_TILE = 64 * HID * 3 / 2;
constexpr int H_HALF = 3072, H_STEP = 6144;

__device__ __align__(1024) uint4 g_h[(size_t)M_TOTAL * HID * 3 / 32];
__device__ __align__(1024) uint4 g_ln[LN_RING * LN_TILE / 16];
__device__ __align__(1024) uint4 g_w2img[HID * C_DIM * 2 / 16];
__device__ __align__(16) float g_sums[2][HID + 2 * C_DIM];
__device__ unsigned g_ex[HID];
__device__ unsigned g_epoch, g_par;
__device__ __align__(128) unsigned g_img;
__device__ __align__(128) unsigned g_prog;
__device__ __align__(128) unsigned g_half[32][2];
__device__ unsigned g_flag[LN_RING + 4][2][8];
#define TSTAMP(k, i)
#define TRACE(wg, pos, i)
#define TRACEW(pos, i)

#define TR2(i)
#define TR2P(pos, i)
__host__ __device__ __forceinline__ int perm32(int n) {
    return (n & ~31) | (((n >> 1) & 3) << 3) | (((n >> 3) & 3) << 1) | (n & 1);
}

__device__ __forceinline__ uint32_t smem_u32(const void* p) { return (uint32_t)__cvta_generic_to_shared(p); }

__device__ __forceinline__ void mbar_init(uint32_t bar, uint32_t count) {
    asm volatile("mbarrier.init.shared::cta.b64 [%0], %1;\n" ::"r"(bar), "r"(count) : "memory");
}
__device__ __forceinline__ void mbar_expect_tx(uint32_t bar, uint32_t bytes) {
    asm volatile("mbarrier.arrive.expect_tx.shared::cta.b64 _, [%0], %1;\n" ::"r"(bar), "r"(bytes) : "memory");
}
__device__ __forceinline__ void mbar_arrive(uint32_t bar) {
    asm volatile("mbarrier.arrive.shared::cta.b64 _, [%0];\n" ::"r"(bar) : "memory");
}
__device__ __forceinline__ void mbar_arrive_cluster(uint32_t bar_cluster_addr) {
    asm volatile("mbarrier.arrive.shared::cluster.b64 _, [%0];\n" ::"r"(bar_cluster_addr) : "memory");
}
#define SAFE_BREAK
__device__ __forceinline__ void mbar_wait(uint32_t bar, uint32_t parity) {
    asm volatile(
        "{\n"
        ".reg .pred p;\n"
        "LAB_WAIT:\n"
        "mbarrier.try_wait.parity.shared::cta.b64 p, [%0], %1;\n"
        "@!p bra LAB_WAIT;\n"
        "}\n" ::"r"(bar), "r"(parity) : "memory");
}
__device__ __forceinline__ bool mbar_test(uint32_t bar, uint32_t parity) {
    uint32_t ok;
    asm volatile("{\n.reg .pred p;\n"
                 "mbarrier.test_wait.parity.shared::cta.b64 p, [%1], %2;\n"
                 "selp.u32 %0, 1, 0, p;\n}\n" : "=r"(ok) : "r"(bar), "r"(parity) : "memory");
    return ok != 0;
}
__device__ __forceinline__ uint32_t mapa(uint32_t addr, uint32_t rank) {
    uint32_t r;
    asm volatile("mapa.shared::cluster.u32 %0, %1, %2;\n" : "=r"(r) : "r"(addr), "r"(rank));
    return r;
}
__device__ __forceinline__ void bulk_g2s(uint32_t dst, const void* src, uint32_t bytes, uint32_t bar) {
    asm volatile("cp.async.bulk.shared::cluster.global.mbarrier::complete_tx::bytes [%0], [%1], %2, [%3];\n"
                 ::"r"(dst), "l"(src), "r"(bytes), "r"(bar) : "memory");
}
__device__ __forceinline__ void bulk_g2s_mc(uint32_t dst, const void* src, uint32_t bytes, uint32_t bar, uint16_t mask) {
    asm volatile("cp.async.bulk.shared::cluster.global.mbarrier::complete_tx::bytes.multicast::cluster [%0], [%1], %2, [%3], %4;\n"
                 ::"r"(dst), "l"(src), "r"(bytes), "r"(bar), "h"(mask) : "memory");
}
__device__ __forceinline__ void tma2(uint32_t dst, const CUtensorMap* map, int c0, int c1, uint32_t bar) {
    asm volatile("cp.async.bulk.tensor.2d.shared::cluster.global.tile.mbarrier::complete_tx::bytes [%0], [%1, {%2, %3}], [%4];\n"
                 ::"r"(dst), "l"(map), "r"(c0), "r"(c1), "r"(bar) : "memory");
}
template <bool ACQ>
__device__ __forceinline__ uint32_t flag_wait(const unsigned* p, unsigned target) {
    unsigned v, n = 0;
    do {
        if (ACQ) asm volatile("ld.acquire.gpu.global.u32 %0, [%1];\n" : "=r"(v) : "l"(p) : "memory");
        else asm volatile("ld.relaxed.gpu.global.u32 %0, [%1];\n" : "=r"(v) : "l"(p) : "memory");
        n++;
    } while (v < target);
    return n == 1;
}
__device__ __forceinline__ void ldsm4t(uint32_t (&r)[4], uint32_t addr) {
    asm volatile("ldmatrix.sync.aligned.m8n8.x4.trans.shared.b16 {%0,%1,%2,%3}, [%4];\n"
                 : "=r"(r[0]), "=r"(r[1]), "=r"(r[2]), "=r"(r[3]) : "r"(addr) : "memory");
}
__device__ __forceinline__ void bulk_s2g(void* dst, uint32_t src, uint32_t bytes) {
    asm volatile("cp.async.bulk.global.shared::cta.bulk_group [%0], [%1], %2;\n" ::"l"(dst), "r"(src), "r"(bytes) : "memory");
}
__device__ __forceinline__ void cluster_sync_relaxed() {
    asm volatile("barrier.cluster.arrive.relaxed.aligned;\nbarrier.cluster.wait.aligned;\n" ::: "memory");
}
__device__ __forceinline__ void gdc_wait() { asm volatile("griddepcontrol.wait;\n" ::: "memory"); }
__device__ __forceinline__ void gdc_launch() { asm volatile("griddepcontrol.launch_dependents;\n" ::: "memory"); }
__device__ __forceinline__ uint32_t cluster_rank() {
    uint32_t r;
    asm volatile("mov.u32 %0, %%cluster_ctarank;\n" : "=r"(r));
    return r;
}
__device__ __forceinline__ bool elect_one() {
    uint32_t pred;
    asm volatile("{\n.reg .pred p;\nelect.sync _|p, 0xffffffff;\nselp.u32 %0, 1, 0, p;\n}\n" : "=r"(pred));
    return pred != 0;
}
__device__ __forceinline__ void wg_fence() { asm volatile("wgmma.fence.sync.aligned;\n" ::: "memory"); }
__device__ __forceinline__ void wg_commit() { asm volatile("wgmma.commit_group.sync.aligned;\n" ::: "memory"); }
template <int N> __device__ __forceinline__ void wg_wait() {
    asm volatile("wgmma.wait_group.sync.aligned %0;\n" ::"n"(N) : "memory");
}
template <int R> __device__ __forceinline__ void reg_inc() { asm volatile("setmaxnreg.inc.sync.aligned.u32 %0;\n" ::"n"(R)); }
template <int R> __device__ __forceinline__ void reg_dec() { asm volatile("setmaxnreg.dec.sync.aligned.u32 %0;\n" ::"n"(R)); }
__device__ __forceinline__ void bar_sync(int id, int n) { asm volatile("bar.sync %0, %1;\n" ::"r"(id), "r"(n) : "memory"); }
__device__ __forceinline__ void bar_arrive(int id, int n) { asm volatile("bar.arrive %0, %1;\n" ::"r"(id), "r"(n) : "memory"); }

__device__ __forceinline__ uint64_t make_desc(uint32_t saddr, uint32_t lbo, uint32_t sbo) {
    return (uint64_t)((saddr & 0x3FFFF) >> 4) | ((uint64_t)(lbo >> 4) << 16) | ((uint64_t)(sbo >> 4) << 32);
}

__device__ __forceinline__ void stg128_cs(void* p, uint32_t a, uint32_t b, uint32_t c, uint32_t d) {
    asm volatile("st.global.cs.v4.u32 [%0], {%1,%2,%3,%4};\n" ::"l"(p), "r"(a), "r"(b), "r"(c), "r"(d) : "memory");
}
__device__ __forceinline__ uint32_t pack_bf16(float lo, float hi) {
    uint32_t r;
    asm("cvt.rn.bf16x2.f32 %0, %1, %2;\n" : "=r"(r) : "f"(hi), "f"(lo));
    return r;
}
__device__ __forceinline__ float bf_lo(uint32_t v) { return __uint_as_float(v << 16); }
__device__ __forceinline__ float bf_hi(uint32_t v) { return __uint_as_float(v & 0xffff0000u); }
__device__ __forceinline__ uint32_t bf2_mul(uint32_t a, uint32_t b) {
    uint32_t r;
    asm("mul.rn.bf16x2 %0, %1, %2;\n" : "=r"(r) : "r"(a), "r"(b));
    return r;
}
__device__ __forceinline__ uint32_t bf2_fma(uint32_t a, uint32_t b, uint32_t c) {
    uint32_t r;
    asm("fma.rn.bf16x2 %0, %1, %2, %3;\n" : "=r"(r) : "r"(a), "r"(b), "r"(c));
    return r;
}
__device__ __forceinline__ uint32_t bf2_add(uint32_t a, uint32_t b) {
    uint32_t r;
    asm("add.rn.bf16x2 %0, %1, %2;\n" : "=r"(r) : "r"(a), "r"(b));
    return r;
}
constexpr float KAPPA = 0.3292034911525734f;
constexpr float GELU_C = 2.423681954311584f;
constexpr float HSCALE = 1.0f / (2.0f * KAPPA);
__device__ __forceinline__ uint32_t acc_exp(float z) { return max(__float_as_uint(z) >> 23, 10u); }
__device__ __forceinline__ void sched_break(int zero) {
    asm volatile("{\n.reg .pred p;\nsetp.ne.s32 p, %0, 0;\nSB_LOOP:\n@p nanosleep.u32 1;\n@p bra SB_LOOP;\n}\n" ::"r"(zero));
}

#define ACC8(d, o) "+f"(d[o + 0]), "+f"(d[o + 1]), "+f"(d[o + 2]), "+f"(d[o + 3]), "+f"(d[o + 4]), "+f"(d[o + 5]), "+f"(d[o + 6]), "+f"(d[o + 7])

#define ACCR8(d, o) "+r"(d[o + 0]), "+r"(d[o + 1]), "+r"(d[o + 2]), "+r"(d[o + 3]), "+r"(d[o + 4]), "+r"(d[o + 5]), "+r"(d[o + 6]), "+r"(d[o + 7])
__device__ __forceinline__ void mma_rs_n128(uint32_t (&d)[32], const uint32_t (&a)[4], uint64_t desc, int scale_d) {
    asm volatile(
        "{\n.reg .pred p;\nsetp.ne.b32 p, %37, 0;\n"
        "wgmma.mma_async.sync.aligned.m64n128k16.f16.f16.f16 "
        "{%0,%1,%2,%3,%4,%5,%6,%7,%8,%9,%10,%11,%12,%13,%14,%15,"
        "%16,%17,%18,%19,%20,%21,%22,%23,%24,%25,%26,%27,%28,%29,%30,%31},"
        "{%32,%33,%34,%35}, %36, p, 1, 1, 0;\n}\n"
        : ACCR8(d, 0), ACCR8(d, 8), ACCR8(d, 16), ACCR8(d, 24)
        : "r"(a[0]), "r"(a[1]), "r"(a[2]), "r"(a[3]), "l"(desc), "r"(scale_d));
}
__device__ __forceinline__ uint32_t bf2_as_h2(uint32_t v) { return (v & 0x0fff0fffu) * 7u + v; }
__device__ __forceinline__ float h_lo(uint32_t v) {
    float r;
    asm("{\n.reg .b16 l, h;\nmov.b32 {l, h}, %1;\ncvt.f32.f16 %0, l;\n}\n" : "=f"(r) : "r"(v));
    return r;
}
__device__ __forceinline__ float h_hi(uint32_t v) {
    float r;
    asm("{\n.reg .b16 l, h;\nmov.b32 {l, h}, %1;\ncvt.f32.f16 %0, h;\n}\n" : "=f"(r) : "r"(v));
    return r;
}

__device__ __forceinline__ void mma_rs_n192(uint32_t (&d)[48], const uint4& a, uint64_t db, int scale_d) {
    asm volatile(
        "{\n.reg .pred p;\nsetp.ne.b32 p, %53, 0;\n"
        "wgmma.mma_async.sync.aligned.m64n192k16.f16.f16.f16 "
        "{%0,%1,%2,%3,%4,%5,%6,%7,%8,%9,%10,%11,%12,%13,%14,%15,"
        "%16,%17,%18,%19,%20,%21,%22,%23,%24,%25,%26,%27,%28,%29,%30,%31,"
        "%32,%33,%34,%35,%36,%37,%38,%39,%40,%41,%42,%43,%44,%45,%46,%47},"
        "{%48,%49,%50,%51}, %52, p, 1, 1, 0;\n}\n"
        : ACCR8(d, 0), ACCR8(d, 8), ACCR8(d, 16), ACCR8(d, 24), ACCR8(d, 32), ACCR8(d, 40)
        : "r"(a.x), "r"(a.y), "r"(a.z), "r"(a.w), "l"(db), "r"(scale_d));
}

__device__ __forceinline__ uint32_t pack_f16(float lo, float hi) {
    uint32_t r;
    asm("cvt.rn.f16x2.f32 %0, %1, %2;\n" : "=r"(r) : "f"(hi), "f"(lo));
    return r;
}

#define P1_REGS 192
#define P1_WARM 0
#define P1_DEF 3
#define P1_DMID 0
#define P1_ARR 23
constexpr int P1_SLOT = LN_TILE / 2, P1_NST = 4;
constexpr int P1_X = 32 * C_DIM * 2;
constexpr int P1_OFF_X = P1_SLOT * P1_NST;
constexpr int P1_OFF_BAR = P1_OFF_X + P1_X;
constexpr int P1_OFF_TILE = P1_OFF_BAR + (2 * P1_NST + 2 + 4) * 8;
constexpr int P1_OFF_RAW = P1_OFF_TILE + 64;
constexpr int P1_OFF_DW = P1_OFF_RAW + 32;
constexpr int P1_SMEM = P1_OFF_DW + C_DIM * 2;

__device__ __forceinline__ float rsqrt_fast(float x) {
    float r;
    asm("rsqrt.approx.ftz.f32 %0, %1;\n" : "=f"(r) : "f"(x));
    return r;
}
__device__ __forceinline__ float row_sum(const uint32_t (&c)[4]) {
    const uint32_t u = bf2_add(bf2_add(c[0], c[1]), bf2_add(c[2], c[3]));
    float s = bf_lo(u) + bf_hi(u);
#pragma unroll
    for (int o = 1; o < 8; o <<= 1) s += __shfl_xor_sync(0xffffffffu, s, o);
    return s;
}
__device__ __forceinline__ void ln_row(uint32_t (&v)[6][4], const uint32_t (&d)[6][4], int zero, uint32_t bar_read) {
    uint32_t c[4];
#pragma unroll
    for (int i = 0; i < 6; i++)
#pragma unroll
        for (int k = 0; k < 4; k++) c[k] = bf2_fma(v[i][k], d[i][k], i ? c[k] : 0);
    const float inv = 1.0f / C_DIM;
    const float m = row_sum(c) * inv;
    const uint32_t nm = pack_bf16(-m, -m);
    const float e = m + bf_lo(nm);
    if (bar_read) mbar_arrive(bar_read + (nm & zero));
#pragma unroll
    for (int i = 0; i < 6; i++) {
#pragma unroll
        for (int k = 0; k < 4; k++) {
            v[i][k] = bf2_fma(v[i][k], d[i][k], nm);
            c[k] = i ? bf2_fma(v[i][k], v[i][k], c[k]) : bf2_mul(v[i][k], v[i][k]);
        }
    }
    float r = KAPPA * rsqrt_fast(fmaxf(fmaf(-e, e, row_sum(c) * inv), 0.f) + 1e-5f);
    const uint32_t sh = pack_bf16(-e * r * 0x1p-112f, -e * r * 0x1p-112f);
    if (__any_sync(0xffffffffu, r < 0x1p-14f)) {
        const uint32_t f = r < 0x1p-14f ? 0x23802380u : 0x3f803f80u;
        if (r < 0x1p-14f) r *= 0x1p56f;
#pragma unroll
        for (int i = 0; i < 6; i++)
#pragma unroll
            for (int k = 0; k < 4; k++) v[i][k] = bf2_mul(v[i][k], f);
    }
    const uint32_t rs = pack_bf16(r * 0x1p-112f, r * 0x1p-112f);
#pragma unroll
    for (int i = 0; i < 6; i++)
#pragma unroll
        for (int k = 0; k < 4; k++) v[i][k] = bf2_as_h2(bf2_fma(v[i][k], rs, sh));
}

__device__ __forceinline__ void load_dw(uint32_t (&d)[6][4], uint32_t sbase, int lane) {
    mbar_wait(sbase + P1_OFF_RAW + 16, 0);
#pragma unroll
    for (int j = 0; j < 6; j++)
        asm volatile("ld.shared.v4.u32 {%0,%1,%2,%3}, [%4];\n" : "=r"(d[j][0]), "=r"(d[j][1]), "=r"(d[j][2]), "=r"(d[j][3])
                     : "r"(sbase + P1_OFF_DW + j * 128 + (lane & 7) * 16) : "memory");
}

__device__ __forceinline__ float gelu_s(float y) {
    float u = y * fmaf(y, y, GELU_C);
    float t;
    asm volatile("tanh.approx.f32 %0, %1;\n" : "=f"(t) : "f"(u));
    return fmaf(y, t, y);
}
__device__ __forceinline__ constexpr int p1_reg(int c, int u) { return 16 * (c >> 1) + 4 * (u >> 1) + 2 * (c & 1) + (u & 1); }
template <bool BIG>
__device__ __forceinline__ void p1_pack(int c, uint32_t (&p)[4], uint32_t (&dd)[4], uint32_t (&sq)[4], uint32_t sc2) {
    uint32_t& s = sq[(c >> 2) * 2 + (c & 1)];
    s = (c & 2) ? bf2_fma(p[0], p[0], s) : bf2_mul(p[0], p[0]);
    s = bf2_fma(p[3], p[3], bf2_fma(p[2], p[2], bf2_fma(p[1], p[1], s)));
#pragma unroll
    for (int u = 0; u < 4; u++) {
        uint32_t v;
        if (c & 1) asm("{\n.reg .b16 l, h;\n.reg .b32 f;\nmov.b32 {l, h}, %2;\nmov.b32 f, {h, h};\nmul.rn.bf16x2 %0, %1, f;\n}\n" : "=r"(v) : "r"(p[u]), "r"(sc2));
        else asm("{\n.reg .b16 l, h;\n.reg .b32 f;\nmov.b32 {l, h}, %2;\nmov.b32 f, {l, l};\nmul.rn.bf16x2 %0, %1, f;\n}\n" : "=r"(v) : "r"(p[u]), "r"(sc2));
        if (BIG) v = bf2_mul(v, 0x07800780u);
        if ((c & 3) == 0) dd[u] = v;
        else {
            uint32_t n = dd[u];
            if ((c & 3) == 1) { n <<= 4; dd[u] = __byte_perm(dd[u], 0, 0x2301); }
            if ((c & 3) == 2) dd[u] <<= 4;
            asm("lop3.b32 %0, %1, %2, 0x78007800, 0xd8;\n" : "=r"(p[u]) : "r"(v), "r"(n));
        }
    }
}
__device__ __forceinline__ void p1_store(int c, const uint32_t (&p)[4], uint8_t* hptr) {
    if (c & 3) stg128_cs(hptr + (c >> 2) * H_HALF + ((c & 3) - 1) * 512, p[0], p[1], p[2], p[3]);
}

__device__ __forceinline__ uint32_t p1_parity(uint32_t sbase) {
    uint32_t v;
    asm volatile("ld.shared.u32 %0, [%1];\n" : "=r"(v) : "r"(sbase + P1_OFF_TILE - 4) : "memory");
    return v;
}
template <bool GEN>
__device__ __forceinline__ uint32_t gelu2(uint32_t y, float fs) {
    if (GEN) return pack_bf16(gelu_s(h_lo(y) * fs), gelu_s(h_hi(y) * fs));
    uint32_t g;
    asm("{\n.reg .b32 w;\n"
        "fma.rn.f16x2 w, %1, %1, %2;\n"
        "mul.rn.f16x2 w, w, %1;\n"
        "tanh.approx.f16x2 w, w;\n"
        "fma.rn.f16x2 %0, %1, w, %1;\n}\n" : "=r"(g) : "r"(y), "r"(0x40d940d9u));
    return pack_bf16(h_lo(g), h_hi(g));
}
template <bool GEN, int C0, int C1, class F>
__device__ __forceinline__ void p1_epilogue(F v, uint32_t (&sq)[4], uint32_t (&dd)[4], float (&ssq)[2], uint32_t sc2, uint8_t* hp) {
    const float fs[2] = {__uint_as_float(0x78000000u - (sc2 << 16)), __uint_as_float(0x78000000u - (sc2 & 0xffff0000u))};
#pragma unroll
    for (int c = C0; c < C1; c++) {
        uint32_t p[4];
#pragma unroll
        for (int u = 0; u < 4; u++) p[u] = gelu2<GEN>(v(c, u), fs[c & 1]);
        p1_pack<GEN>(c, p, dd, sq, sc2);
        p1_store(c, p, hp);
    }
    if (C1 == 8) {
#pragma unroll
        for (int r = 0; r < 2; r++) {
            const uint32_t u = bf2_add(sq[r], sq[2 + r]);
            ssq[r] += bf_lo(u) + bf_hi(u);
        }
    }
}
__device__ __forceinline__ void p1_consumer(const uint32_t (&a)[24][4], uint32_t sc2, bool gen, uint32_t sbase, int wg, int w, int lane) {
    const uint32_t bar_full = sbase + P1_OFF_BAR, bar_empty = bar_full + P1_NST * 8;
    const uint32_t empty_remote = mapa(bar_empty, lane & 1);
    const int g = lane >> 2, q = lane & 3, cb = (blockIdx.x % GRP_CTAS) * 2 + wg;
    float ssq[2] = {0.f, 0.f};
    uint32_t acc[32], sq[4] = {}, dd[4] = {}, dfr[P1_DEF * 4 + 1] = {};
    auto from_acc = [&](int c, int u) { return acc[8 * (c >> 1) + 2 * u + (c & 1)]; };
    auto from_dfr = [&](int c, int u) { return dfr[(c - 8 + P1_DEF) * 4 + u]; };
    bool pend = false;
    TSTAMP(0, 1);

    uint8_t* hp = reinterpret_cast<uint8_t*>(g_h) + (size_t)(blockIdx.x / GRP_CTAS) * (2 * H_TILE) + ((cb * 2 + (w >> 1)) * H_STEP + (w & 1) * 1536) + g * 64 + (q ^ (g >> 1)) * 16;
    const uint64_t desc_base = make_desc(sbase, 16, 1024) | (1ull << 62);
#pragma unroll 1
    for (int i = 0;; i++) {
        const int s0 = (i & 1) * 16, par = (i >> 1) & 1;
        const uint64_t d0 = desc_base + (uint64_t)((i & 1) * (LN_TILE / 16));
        TRACE(wg, i, 0);
        mbar_wait(bar_full + s0, par);
        bar_sync(1 + wg, 256);
        TRACE(wg, i, 1);
        uint32_t step, more;
        wg_fence();
#pragma unroll
        for (int k = 0; k < 24; k++) {
            if (k == 12) mbar_wait(bar_full + s0 + 8, par);
            mma_rs_n128(acc, a[k], d0 + (uint64_t)((k >> 2) * 1024 + (k & 3) * 2), k != 0);
            if (k == P1_ARR) bar_arrive(2 - wg, 256);
            if (k % 12 == 11) wg_commit();
            if (P1_DMID && k == 11 && pend) p1_epilogue<false, 8 - P1_DEF, 8 - P1_DEF + P1_DMID>(from_dfr, sq, dd, ssq, sc2, hp);
        }
        asm volatile("ld.shared.v2.u32 {%0, %1}, [%2];\n" : "=r"(step), "=r"(more) : "r"(sbase + P1_OFF_TILE + (i & 3) * 16) : "memory");
        TRACE(wg, i, 2);
        wg_wait<1>();
        if (lane < 2) mbar_arrive_cluster(empty_remote + s0);
        if (P1_DEF > P1_DMID && pend) p1_epilogue<false, 8 - P1_DEF + P1_DMID, 8>(from_dfr, sq, dd, ssq, sc2, hp);
        hp += step;
        TRACE(wg, i, 3);
        wg_wait<0>();
        TRACE(wg, i, 4);
        if (lane < 2) mbar_arrive_cluster(empty_remote + s0 + 8);
        if (gen) p1_epilogue<true, 0, 8>(from_acc, sq, dd, ssq, sc2, hp);
        else {
#pragma unroll
            for (int j = 0; j < P1_DEF * 4; j++) asm volatile("mov.b32 %0, %1;\n" : "=r"(dfr[j]) : "r"(from_acc(8 - P1_DEF + j / 4, j % 4)));
            p1_epilogue<false, 0, 8 - P1_DEF>(from_acc, sq, dd, ssq, sc2, hp);
            pend = true;
        }
        if (!more) break;
    }
    if (P1_DEF && pend) p1_epilogue<false, 8 - P1_DEF, 8>(from_dfr, sq, dd, ssq, sc2, hp);
    TSTAMP(0, 21);
    if (wg == 0) bar_sync(1, 256);
#pragma unroll
    for (int r = 0; r < 2; r++) {
        ssq[r] += __shfl_xor_sync(0xffffffffu, ssq[r], 1);
        ssq[r] += __shfl_xor_sync(0xffffffffu, ssq[r], 2);
        if (q == 0) atomicAdd(&g_sums[p1_parity(sbase)][cb * 64 + w * 16 + r * 8 + g], ssq[r]);
    }
}

__global__ void __cluster_dims__(2, 1, 1) __launch_bounds__(512, 1)
pass1_kernel(const __grid_constant__ CUtensorMap wmap, const __nv_bfloat16* __restrict__ x, const __nv_bfloat16* __restrict__ dw,
             const __nv_bfloat16* __restrict__ w2, const __nv_bfloat16* __restrict__ grn_b, int zero) {
    extern __shared__ __align__(1024) uint8_t smem[];
    const uint32_t sbase = smem_u32(smem);
    const uint32_t bar_full = sbase + P1_OFF_BAR, bar_empty = bar_full + P1_NST * 8, bar_w = bar_empty + P1_NST * 8;
    const int tid = threadIdx.x;
    const int warp = __shfl_sync(0xffffffffu, tid >> 5, 0), lane = tid & 31;
    const uint32_t rank = cluster_rank();
    const int cig = blockIdx.x % GRP_CTAS;
    uint8_t* const ring = reinterpret_cast<uint8_t*>(g_ln);

    TSTAMP(0, 0);
    TRACEW(110 + warp, 0);
    const uint32_t bar_xfull = bar_w + 16, bar_xempty = bar_xfull + 8, bar_done = bar_xfull + 16;
    const uint32_t bar_raw = sbase + P1_OFF_RAW;
    const int ln0 = blockIdx.x >> 2, first = blockIdx.x / GRP_CTAS;
    const uint8_t* xsrc = reinterpret_cast<const uint8_t*>(x) + (size_t)(NGRP * 4 + blockIdx.x) * P1_X;

    if (warp >= 12) {
        reg_dec<40>();
        asm volatile("barrier.cluster.arrive.relaxed.aligned;\n" ::: "memory");
        asm volatile("barrier.cluster.wait.aligned;\n" ::: "memory");
        if (warp == 12) {
            int prev = first - NGRP, t = first, next = t + NGRP;
            const uint32_t rbase = mapa(sbase, lane & 1);
            int i = 1;
#pragma unroll 1
            for (; t < NT_RING; i++) {
                const int s0 = (i & 1) * 2, par = ((i + 1) >> 1 & 1) ^ 1;
                const int round = t / LN_RING, slot = t - round * LN_RING;
                const uint8_t* src = ring + slot * LN_TILE + rank * (P1_SLOT / 2);
                int draw = 0;
                if (rank == 0 && lane == 0) draw = atomicAdd(&g_flag[LN_RING + (cig >> 2)][(cig >> 1) & 1][0], 1u);
                flag_wait<true>(&g_flag[slot][0][0], 4 * round + 4);
                TRACEW(i, 2);
                asm volatile("fence.proxy.async.global;\n" ::: "memory");
                draw = 2 * NGRP + __shfl_sync(0xffffffffu, draw, 0);
#pragma unroll
                for (int h = 0; h < 2; h++) {
                    mbar_wait(bar_empty + (s0 + h) * 8, par);
                    TRACEW(i, 4 + h);
                    if (elect_one()) {
                        mbar_expect_tx(bar_full + (s0 + h) * 8, P1_SLOT + 16 - 16 * h);
                        bulk_g2s_mc(sbase + (s0 + h) * P1_SLOT + rank * (P1_SLOT / 2), src + h * P1_SLOT, P1_SLOT / 2, bar_full + (s0 + h) * 8, (uint16_t)3);
                    }
                    __syncwarp();
                    if (h == 0 && rank == 0 && lane < 2)
                        asm volatile("st.async.shared::cluster.mbarrier::complete_tx::bytes.v4.u32 [%0], {%1, %2, %3, %3}, [%4];\n"
                                     ::"r"(rbase + P1_OFF_TILE + (i & 3) * 16), "r"((t - prev) * (2 * H_TILE)), "r"((int)(next < NT_RING)), "r"(draw),
                                       "r"(rbase + P1_OFF_BAR + s0 * 8) : "memory");
                }
                prev = t;
                t = next;
                next = draw;
                if (rank != 0) {
                    mbar_wait(bar_full + (s0 ^ 2) * 8, ((i - 1) >> 1) & 1);
                    asm volatile("ld.shared.u32 %0, [%1];\n" : "=r"(t) : "r"(sbase + P1_OFF_TILE + ((i - 1) & 3) * 16 + 8) : "memory");
                }
            }
#pragma unroll 1
            for (int j = 2 * i; j < 2 * i + 4; j++) mbar_wait(bar_empty + (j & 3) * 8, ((j + 2) >> 2 & 1) ^ 1);
        } else if (warp == 13) {
            int ph = 0;
            unsigned target = 0;
#pragma unroll 1
            for (int i = ln0 + LN_STEP; i < NT_RING; i += LN_STEP, ph ^= 1) {
                target += ph * (GRP_CTAS / 2);
                xsrc += (size_t)NUM_CTAS * P1_X;
                mbar_wait(bar_xempty, ph);
                if (elect_one()) {
                    mbar_expect_tx(bar_xfull, P1_X);
                    bulk_g2s(sbase + P1_OFF_X, xsrc, P1_X, bar_xfull);
                }
                __syncwarp();
                flag_wait<false>(&g_flag[ln0 + (ph ^ 1) * LN_STEP][1][0], target);
                mbar_wait(bar_done, ph);
                if (elect_one()) mbar_arrive(bar_xfull);
                __syncwarp();
            }
        } else if (warp == 15) {
            if (rank == 1 && lane < 2) mbar_arrive(bar_empty + (2 + lane) * 8);
            const uint32_t par = g_epoch & 1;
            asm volatile("st.shared.u32 [%0], %1;\n" ::"r"(sbase + P1_OFF_TILE - 4), "r"(par) : "memory");
            if (blockIdx.x == 18) g_par = par;
            if (blockIdx.x < 18) reinterpret_cast<float4*>(g_sums[par ^ 1])[blockIdx.x * 32 + lane] = make_float4(0.f, 0.f, 0.f, 0.f);
            bar_arrive(3, 160);
            {
                bar_sync(4, 288);
                mbar_wait(bar_raw + 8, 0);
                const uint32_t o = lane * 16384 + rank * 8192, peer = mapa(sbase, rank ^ 1);
                if (lane < 6)
                    asm volatile("cp.async.bulk.shared::cluster.shared::cta.mbarrier::complete_tx::bytes [%0], [%1], 8192, [%2];\n"
                                 ::"r"(peer + o), "r"(sbase + o), "r"(peer + P1_OFF_BAR + (lane >= 3 ? 8 : 0)) : "memory");
                __syncwarp();
            }
            if (rank == 0) {
                flag_wait<true>(&g_flag[40][1][0], GRP_CTAS / 2);
                const int col = (cig >> 1) * 64 + lane * 2;
                float bsum[2] = {0.f, 0.f}, asum[2] = {0.f, 0.f};
#pragma unroll 2
                for (int k = first * 140; k < min(first * 140 + 140, HID); k++) {
                    const uint32_t v = *reinterpret_cast<const uint32_t*>(w2 + k * C_DIM + col);
                    const float b = __bfloat162float(grn_b[k]), f = __uint_as_float(__ldcg(&g_ex[k]) << 23);
                    bsum[0] = fmaf(b, bf_lo(v), bsum[0]);
                    bsum[1] = fmaf(b, bf_hi(v), bsum[1]);
                    asum[0] = fmaf(f, fabsf(bf_lo(v)), asum[0]);
                    asum[1] = fmaf(f, fabsf(bf_hi(v)), asum[1]);
                }
                float* sums = g_sums[par] + HID + col;
#pragma unroll
                for (int j = 0; j < 2; j++) {
                    atomicAdd(sums + j, bsum[j]);
                    atomicAdd(sums + C_DIM + j, asum[j]);
                }
                __threadfence();
                __syncwarp();
                if (lane == 0) asm volatile("red.release.gpu.global.add.u32 [%0], 1;\n" ::"l"(&g_flag[LN_RING + 3][0][0]) : "memory");
            }
            int t = first, next = t + NGRP;
            if (rank == 1) {
                mbar_wait(bar_full, 0);
                mbar_wait(bar_full + 8, 0);
                if (lane < 2) mbar_arrive(bar_empty + lane * 8);
            }
#pragma unroll 1
            for (int i = 1; rank == 1 && t < NT_RING; i++) {
                const int s0 = (i & 1) * 16;
                mbar_wait(bar_full + s0, (i >> 1) & 1);
                mbar_wait(bar_full + s0 + 8, (i >> 1) & 1);
                if (lane == 0) asm volatile("red.relaxed.gpu.global.add.u32 [%0], 1;\n" ::"l"(&g_flag[t % LN_RING][1][0]) : "memory");
                t = next;
                asm volatile("ld.shared.u32 %0, [%1];\n" : "=r"(next) : "r"(sbase + P1_OFF_TILE + (i & 3) * 16 + 8) : "memory");
                if (lane < 2) mbar_arrive(bar_empty + s0 + lane * 8);
                TRACEW(i, 3);
            }
        } else if (warp == 14) {
            int ph = 0;
#pragma unroll 1
            for (int i = ln0; i < NT_RING; i += LN_STEP, ph ^= 1) {
                mbar_wait(bar_done, ph);
                TRACEW(i / LN_STEP, 0);
                asm volatile("fence.proxy.async.global;\n" ::: "memory");
                if (elect_one()) asm volatile("red.release.gpu.global.add.u32 [%0], 1;\n" ::"l"(&g_flag[ln0 + ph * LN_STEP][0][0]) : "memory");
                __syncwarp();
                TRACEW(i / LN_STEP, 1);
            }
        }
    } else if (warp >= 8) {
        reg_dec<88>();
        asm volatile("barrier.cluster.arrive.relaxed.aligned;\n" ::: "memory");
        {
            const int l8 = lane & 7, row = (warp - 8) * 4 + (lane >> 3), px = (blockIdx.x & 3) * 32 + row;
            uint32_t d[6][4] = {};
            const int n = (px & 64) + perm32(2 * row + ((px >> 5) & 1));
            uint8_t* const dst0 = ring + ln0 * LN_TILE + n * 128 + ((l8 ^ (n & 7)) << 4);
            const uint32_t src = sbase + P1_OFF_X + ((warp - 8) * 8 + (lane >> 3)) * (C_DIM * 2) + l8 * 16;
            int ph = 0;
            asm volatile("barrier.cluster.wait.aligned;\n" ::: "memory");
#pragma unroll 1
            for (int i = ln0; i < NT_RING; i += LN_STEP, ph ^= 1) {
                TRACE(2, i / LN_STEP, 0);
#pragma unroll 1
                for (int ps = i == ln0 ? -1 : 0; ps < 2; ps++) {
                    if (ps == 0) {
                        if (i == ln0) load_dw(d, sbase, lane);
                        mbar_wait(bar_xfull, ph);
                        TRACE(2, i / LN_STEP, 1);
                    }
                    uint32_t v[6][4];
#pragma unroll
                    for (int j = 0; j < 6; j++)
                        asm volatile("ld.shared.v4.u32 {%0,%1,%2,%3}, [%4];\n"
                                     : "=r"(v[j][0]), "=r"(v[j][1]), "=r"(v[j][2]), "=r"(v[j][3]) : "r"(src + (ps & 1) * (4 * C_DIM * 2) + j * 128) : "memory");
                    ln_row(v, d, zero, ps == 1 && lane == 0 ? bar_xempty : 0);
                    uint8_t* dst = dst0 + ph * (LN_STEP * LN_TILE) + ps * 4096;
#pragma unroll
                    for (int j = 0; j < 6; j++)
                        asm volatile("{\n.reg .pred p;\nsetp.ge.s32 p, %5, 0;\n@p st.global.v4.u32 [%0], {%1,%2,%3,%4};\n}\n"
                                     ::"l"(dst + j * 16384), "r"(v[j][0]), "r"(v[j][1]), "r"(v[j][2]), "r"(v[j][3]), "r"(ps) : "memory");
                    TRACE(2, i / LN_STEP, 3 + (ps & 1));
                }
                asm volatile("fence.proxy.async.global;\nfence.acq_rel.cta;\n" ::: "memory");
                __syncwarp();
                if (lane == 0) mbar_arrive(bar_done);
                TRACE(2, i / LN_STEP, 5);
                TRACE(2, i / LN_STEP, 2);
            }
        }
        const int gw = (warp - 8) * NUM_CTAS + blockIdx.x;
        bar_sync(3, 160);
        if (gw < 288) {
            const int np = (gw % 12) * 32 + lane, kb = gw / 12;
            const __nv_bfloat16* wc = w2 + (size_t)kb * 64 * C_DIM + perm32(np);
            const float* sums = g_sums[p1_parity(sbase)] + HID;
            flag_wait<true>(&g_flag[LN_RING + 3][0][0], NUM_CTAS / 2);
            float z = 0.f;
#pragma unroll
            for (int j = 0; j < C_DIM / 32; j++) z = fmaxf(z, __ldcg(sums + C_DIM + j * 32 + lane));
            const float sc = __uint_as_float((263u - acc_exp(__uint_as_float(__reduce_max_sync(0xffffffffu, __float_as_uint(z))))) << 23);
#pragma unroll 2
            for (int c = 0; c < 8; c++) {
                float f[8];
#pragma unroll
                for (int e = 0; e < 8; e++)
                    f[e] = __bfloat162float(wc[(c * 8 + e) * C_DIM]) * __uint_as_float(__ldcg(&g_ex[kb * 64 + c * 8 + e]) << 23) * sc;
                g_w2img[(((kb * 4 + (c >> 1)) * 48 + (np >> 3)) * 2 + (c & 1)) * 8 + (np & 7)] =
                    make_uint4(pack_f16(f[0], f[1]), pack_f16(f[2], f[3]), pack_f16(f[4], f[5]), pack_f16(f[6], f[7]));
            }
            asm volatile("fence.proxy.async.global;\n" ::: "memory");
            __threadfence();
            __syncwarp();
            if (lane == 0) asm volatile("red.release.gpu.global.add.u32 [%0], 1;\n" ::"l"(&g_img) : "memory");
        }
    } else {
        if (tid == 0) {
            mbar_init(bar_raw, 1);
            mbar_init(bar_raw + 8, 8);
            asm volatile("fence.mbarrier_init.release.cluster;\n" ::: "memory");
            mbar_expect_tx(bar_raw, P1_SLOT);
            for (int i = 0; i < 6; i++)
                bulk_g2s(sbase + i * 16384 + (rank ^ 1) * 8192, x + (size_t)(first * 128 + rank * 64) * C_DIM + i * 4096, 8192, bar_raw);
        }
        if (tid == 32) {
            mbar_init(bar_raw + 16, 1);
            mbar_init(bar_xfull, 2);
            mbar_init(bar_xempty, 4);
            mbar_init(bar_done, 4);
            asm volatile("fence.mbarrier_init.release.cluster;\n" ::: "memory");
            mbar_expect_tx(bar_raw + 16, C_DIM * 2);
            bulk_g2s(sbase + P1_OFF_DW, dw, C_DIM * 2, bar_raw + 16);
            mbar_expect_tx(bar_xfull, P1_X);
            bulk_g2s(sbase + P1_OFF_X, xsrc, P1_X, bar_xfull);
            mbar_arrive(bar_xfull);
        }
        if (tid == 64) {
            asm volatile("st.shared.v4.u32 [%0], {0, 1, %1, %1};\n" ::"r"(sbase + P1_OFF_TILE), "r"(first + NGRP) : "memory");
            for (int i = 0; i < P1_NST; i++) {
                mbar_init(bar_full + i * 8, 1);
                mbar_init(bar_empty + i * 8, 16 + rank);
                if (i < 2) mbar_expect_tx(bar_full + i * 8, P1_SLOT / 2);
            }
            asm volatile("fence.mbarrier_init.release.cluster;\n" ::: "memory");
            if (blockIdx.x < 64) (&g_half[0][0])[blockIdx.x] = 0;
            else if (blockIdx.x == 64) g_prog = 0;
            else if (blockIdx.x == 65) g_img = 0;
        }
        if (tid == 96) {
            for (int i = 0; i < 2; i++) mbar_init(bar_w + i * 8, 1);
            asm volatile("fence.mbarrier_init.release.cluster;\n" ::: "memory");
        }
        __syncwarp();
        asm volatile("barrier.cluster.arrive.relaxed.aligned;\n" ::: "memory");
        if (tid == 96)
            for (int i = 0; i < 2; i++) {
                mbar_expect_tx(bar_w + i * 8, P1_SLOT);
                tma2(sbase + (2 + i) * P1_SLOT, &wmap, cig * 128 + i * 64, 0, bar_w + i * 8);
                tma2(sbase + (2 + i) * P1_SLOT + P1_SLOT / 2, &wmap, cig * 128 + i * 64, 192, bar_w + i * 8);
            }
        __syncwarp();
        reg_inc<P1_REGS>();
        TRACEW(110 + warp, 1);
        const int wg = warp >> 2, w = warp & 3;
        uint32_t a[24][4], ex[2], gen;
        const uint32_t wsrc = sbase + (2 + wg) * P1_SLOT + ((lane >> 4) * 8 + (lane & 7)) * 128 + (((2 * w + ((lane >> 3) & 1)) ^ (lane & 7)) << 4);
        gdc_launch();
        asm volatile("barrier.cluster.wait.aligned;\n" ::: "memory");
#pragma unroll 1
        for (int it = P1_WARM ? 1 - wg : 1; it < 2; it++) {
            if (it) {
                const int n = warp * 8 + (lane >> 3), px = (n & 1) * 32 + (n >> 5) * 4 + ((n >> 1) & 1) * 8 + ((n >> 3) & 3);
                uint32_t d[6][4] = {};
#pragma unroll 1
                for (int ps = P1_WARM ? wg - 1 : -1; ps < 2; ps++) {
                    if (ps == 0) {
                        load_dw(d, sbase, lane);
                        mbar_wait(bar_raw, 0);
                    }
                    TRACEW(110 + warp, 2 + (ps == 0));
                    uint32_t v[6][4];
#pragma unroll
                    for (int j = 0; j < 6; j++) {
                        const uint32_t o = (px + (ps & 1) * 16) * (C_DIM * 2) + j * 128;
                        asm volatile("ld.shared.v4.u32 {%0,%1,%2,%3}, [%4];\n" : "=r"(v[j][0]), "=r"(v[j][1]), "=r"(v[j][2]), "=r"(v[j][3])
                                     : "r"(sbase + (rank ^ 1) * 8192 + (lane & 7) * 16 + o + (o & ~8191u)) : "memory");
                    }
                    ln_row(v, d, zero, 0);
                    const uint32_t p = sbase + (rank * 64 + n + (ps & 1) * 4) * 128 + (((lane ^ n ^ (ps & 1) * 4) & 7) << 4);
#pragma unroll
                    for (int j = 0; j < 6; j++)
                        asm volatile("st.shared.v4.u32 [%4], {%0,%1,%2,%3};\n"
                                     ::"r"(v[j][0]), "r"(v[j][1]), "r"(v[j][2]), "r"(v[j][3]), "r"(p + j * 16384) : "memory");
                }
                asm volatile("fence.proxy.async.shared::cta;\n" ::: "memory");
                __syncwarp();
                if (lane == 0) mbar_arrive_cluster(mapa(bar_raw + 8, rank ^ 1));
                bar_arrive(4, 288);
                if (wg == 1) bar_arrive(1, 256);
                TRACEW(110 + warp, 4);
                mbar_wait(bar_w + wg * 8, 0);
                TRACEW(110 + warp, 5);
            }
#pragma unroll
            for (int k = 0; k < 24; k++) ldsm4t(a[k], wsrc + k * 2048);
#pragma unroll
            for (int r = 0; r < 2; r++) {
                float t = 0.f;
#pragma unroll
                for (int j = 0; j < 6; j++) {
                    uint32_t c = bf2_mul(a[4 * j][r], a[4 * j][r]);
#pragma unroll
                    for (int k = 1; k < 8; k++) c = bf2_fma(a[4 * j + k / 2][r + (k & 1) * 2], a[4 * j + k / 2][r + (k & 1) * 2], c);
                    t += bf_lo(c) + bf_hi(c);
                }
                t += __shfl_xor_sync(0xffffffffu, t, 1);
                t += __shfl_xor_sync(0xffffffffu, t, 2);
                ex[r] = min(max(__float_as_uint(13.9f * __fsqrt_rn(t)) >> 23, 72u), 198u);
            }
            asm volatile("{\n.reg .pred p;\nsetp.gt.u32 p, %1, 16;\nbar.red.or.pred p, %2, 128, p;\nselp.u32 %0, 1, 0, p;\n}\n"
                         : "=r"(gen) : "r"(max(ex[0] - 125u, ex[1] - 125u)), "r"(5 + wg) : "memory");
            gen = __shfl_sync(0xffffffffu, gen, 0);
            if (gen) {
#pragma unroll
                for (int k = 0; k < 24; k++)
#pragma unroll
                    for (int j = 0; j < 4; j++) a[k][j] = bf2_mul(a[k][j], (268u - ex[j & 1]) * 0x00800080u);
            }
#pragma unroll
            for (int k = 0; k < 24; k++)
#pragma unroll
                for (int j = 0; j < 4; j++) {
                    a[k][j] = bf2_as_h2(bf2_mul(a[k][j], 0x07800780u));
                    asm volatile("" : "+r"(a[k][j]));
                }
            TRACEW(110 + warp, 6);
        }
        if ((lane & 3) < 2) g_ex[cig * 128 + wg * 64 + w * 16 + (lane & 1) * 8 + (lane >> 2)] = lane & 1 ? ex[1] : ex[0];
        if (lane < 4) mbar_arrive_cluster(mapa(bar_empty, lane & 1) + (2 + (lane >> 1)) * 8);
        TRACEW(110 + warp, 7);
        p1_consumer(a, (gen ? 0x7f007f00u : 0x47004700u) - ((ex[0] | ex[1] << 16) << 7), gen, sbase, wg, w, lane);
        TSTAMP(0, 30);
    }
}

#define P2_NB_ 5
#define P2_NA_ 5
#define P2_DELTA_ 7
#define P2_EXTRA 0
#define P2_HSLEEP 64
#define P2_PSLEEP 100
#define P2_T0 5
#define P2_TS 11
constexpr int P2_B = 24576, P2_NB = P2_NB_;
constexpr int P2_A = 3072, P2_NA = P2_NA_;
constexpr int P2_XROW = C_DIM * 2;
constexpr int P2_OFF_A = P2_B * P2_NB;
constexpr int P2_OFF_X = P2_OFF_A + 3 * P2_NA * P2_A;
constexpr int P2_XHALF = 32 * P2_XROW + 64;
constexpr int P2_OFF_BIAS = P2_OFF_X + 64 * P2_XROW + 64;
constexpr int P2_OFF_GRN = P2_OFF_BIAS + C_DIM * 4;
constexpr int P2_OFF_BAR = P2_OFF_GRN + HID * 2;
constexpr int P2_SMEM = P2_OFF_BAR + (2 * P2_NB + 6 * P2_NA + 3) * 8;
#define P2_LAG_ 17
constexpr int P2_LAG = P2_LAG_;
constexpr int P2_NCL = NUM_CTAS / 2, P2_ITEMS = NT128 / P2_NCL, P2_SHARED = NT128 - P2_ITEMS * P2_NCL;
constexpr int P2_POS = P2_LAG * (P2_ITEMS - 1) + 48;
__device__ __forceinline__ int p2_start(int n) { return n < 0 ? 0 : n == P2_ITEMS ? P2_POS - 24 : P2_LAG * n; }
constexpr int P2_XC = 8 * P2_XROW;
constexpr int P2_DELTA = P2_DELTA_;
__device__ __forceinline__ int p2_tile(int cl, int n) {
    return n == 0 ? NT128 - 1 - cl : n < 0 || n == P2_ITEMS ? NT128 - 1 - P2_NCL - (cl >> 1) : cl + P2_NCL * (n - 1);
}

constexpr int P2_EG = 2;
__device__ __forceinline__ void p2_epilogue(const uint32_t (&acc0)[48], const uint32_t (&acc1)[48], uint32_t sx, uint32_t sb, float up, int zero) {
    uint32_t v[2][P2_EG][4];
    float b[2][8];
    auto load = [&](int c, uint32_t a) {
#pragma unroll
        for (int j = 0; j < 2; j++)
            asm volatile("ld.shared.v4.f32 {%0,%1,%2,%3}, [%4];\n" : "=f"(b[c & 1][4 * j]), "=f"(b[c & 1][4 * j + 1]), "=f"(b[c & 1][4 * j + 2]), "=f"(b[c & 1][4 * j + 3])
                         : "r"(sb + c * 128 + j * 16) : "memory");
#pragma unroll
        for (int j = 0; j < P2_EG; j++) {
            const int u = c * P2_EG + j;
            asm volatile("ld.shared.v4.u32 {%0,%1,%2,%3}, [%4];\n" : "=r"(v[c & 1][j][0]), "=r"(v[c & 1][j][1]), "=r"(v[c & 1][j][2]), "=r"(v[c & 1][j][3])
                         : "r"(a + (u >> 1) * 64 + (u & 1) * 4 * P2_XROW) : "memory");
        }
    };
    load(0, sx);
#pragma unroll
    for (int c = 0; c < 24 / P2_EG; c++) {
        if (c + 1 < 24 / P2_EG) load(c + 1, sx + (v[c & 1][P2_EG - 1][0] & zero));
#pragma unroll
        for (int j = 0; j < P2_EG; j++) {
            const int u = c * P2_EG + j, i = 8 * ((u >> 1) % 6) + (u & 1);
            const uint32_t (&acc)[48] = u < 12 ? acc0 : acc1;
            uint32_t (&w)[4] = v[c & 1][j];
#pragma unroll
            for (int e = 0; e < 4; e++)
                w[e] = bf2_add(pack_bf16(fmaf(h_lo(acc[i + 2 * e]), up, b[c & 1][2 * e]), fmaf(h_hi(acc[i + 2 * e]), up, b[c & 1][2 * e + 1])), w[e]);
            asm volatile("st.shared.v4.u32 [%4], {%0,%1,%2,%3};\n" ::"r"(w[0]), "r"(w[1]), "r"(w[2]), "r"(w[3]),
                         "r"(sx + (u >> 1) * 64 + (u & 1) * 4 * P2_XROW) : "memory");
        }
    }
}

__device__ __forceinline__ void p2_unpack(uint32_t (&u)[4], uint32_t o1, uint32_t o2, uint32_t o3) {
    u[2] = o1 & 0x87ff87ffu;
    u[1] = o2 & 0x87ff87ffu;
    u[3] = o3 & 0x87ff87ffu;
    u[0] = __byte_perm((o2 & 0x78007800u) | ((o3 >> 4) & 0x07800780u), 0, 0x2301) | ((o1 >> 4) & 0x07800780u);
}
__device__ __forceinline__ void p2_epilogue_add(const uint32_t (&acc)[48], uint8_t* o, float f, int zero) {
#pragma unroll
    for (int t = 0; t < 12; t++) {
        uint32_t v[4];
#pragma unroll
        for (int e = 0; e < 4; e++) {
            v[e] = acc[8 * (t >> 1) + (t & 1) + 2 * e];
            asm volatile("" : "+r"(v[e]));
            v[e] = pack_bf16(h_lo(v[e]) * f, h_hi(v[e]) * f);
        }
        asm volatile("red.global.add.noftz.v4.bf16x2 [%0], {%1,%2,%3,%4};\n" ::"l"(o + (t >> 1) * 64 + (t & 1) * 4 * P2_XROW),
                     "r"(v[0]), "r"(v[1]), "r"(v[2]), "r"(v[3]) : "memory");
        if (t % 3 == 2) sched_break(zero);
    }
}

__global__ void __cluster_dims__(2, 1, 1) __launch_bounds__(512, 1)
pass2_kernel(const __nv_bfloat16* __restrict__ x, const __nv_bfloat16* __restrict__ grn_g, __nv_bfloat16* __restrict__ out, int zero) {
    extern __shared__ __align__(1024) uint8_t smem[];
    const uint32_t sbase = smem_u32(smem);
    const uint32_t bar_bfull = sbase + P2_OFF_BAR, bar_bempty = bar_bfull + P2_NB * 8;
    const uint32_t bar_afull = bar_bempty + P2_NB * 8, bar_aempty = bar_afull + 3 * P2_NA * 8;
    const uint32_t bar_xfull = bar_aempty + 3 * P2_NA * 8, bar_oready = bar_xfull + 8, s_pos = bar_xfull + 16;
    int tid;
    asm volatile("mov.u32 %0, %%tid.x;\n" : "=r"(tid));
    const int warp = __shfl_sync(0xffffffffu, tid >> 5, 0), lane = tid & 31;
    const uint32_t rank = cluster_rank();
    const int cl = blockIdx.x >> 1, pair = cl >> 1;
    const int k0 = (4 * pair + (cl & 1) * (48 - P2_POS % 48)) % 48;
    const int head = pair < P2_SHARED && !(cl & 1), tail = pair < P2_SHARED && (cl & 1);

    uint32_t par, gg[4];
    float pre[4];
    if (warp < 12) {
        asm volatile("ld.global.cg.u32 %0, [%1];\n" : "=r"(par) : "l"(&g_par) : "memory");
#pragma unroll
        for (int i = 0; i < 4; i++) {
            asm volatile("ld.global.cg.f32 %0, [%1];\n" : "=f"(pre[i]) : "l"(&g_sums[i & 1][HID + (i >> 1) * C_DIM + tid]) : "memory");
            asm volatile("ld.global.nc.u16 %0, [%1];\n" : "=r"(gg[i]) : "l"(grn_g + tid + 384 * i) : "memory");
        }
    }
    TSTAMP(1, 0);
    if (tid == 384) {
        for (int i = 0; i < P2_NB; i++) {
            mbar_init(bar_bfull + i * 8, 1);
            mbar_init(bar_bempty + i * 8, 24);
        }
        for (int i = 0; i < 3 * P2_NA; i++) {
            mbar_init(bar_afull + i * 8, 1);
            mbar_init(bar_aempty + i * 8, 4);
        }
        mbar_init(bar_xfull, 2);
        mbar_init(bar_oready, 4);
        asm volatile("st.shared.u32 [%0], 0;\n" ::"r"(s_pos) : "memory");
        asm volatile("fence.mbarrier_init.release.cluster;\n" ::: "memory");
    }
    __syncthreads();
    cluster_sync_relaxed();

    if (warp >= 12) {
        reg_dec<32>();
        if (warp == 12) {
            const uint8_t* wsrc = reinterpret_cast<const uint8_t*>(g_w2img) + rank * (P2_B / 2);
            int st = 0, ph = 1, kb = k0, m = 0, r = 0;
            const int busy = head ? 0 : tail ? P2_POS - 24 : P2_POS;
            flag_wait<true>(&g_img, 288);
            asm volatile("fence.proxy.async.global;\n" ::: "memory");
#pragma unroll 1
            for (int p = 0; p < P2_POS; p++) {
                mbar_wait(bar_bempty + st * 8, ph);
                TR2P(p, 0);
                if (elect_one()) {
                    mbar_expect_tx(bar_bfull + st * 8, P2_B);
                    bulk_g2s_mc(sbase + st * P2_B + rank * (P2_B / 2), wsrc + kb * P2_B, P2_B / 2, bar_bfull + st * 8, (uint16_t)3);
                    asm volatile("st.volatile.shared.u32 [%0], %1;\n" ::"r"(s_pos), "r"(p) : "memory");
                    const int idle = 2 - min(m, P2_ITEMS - 1) + max(m - 2 + (r >= 48 - 2 * P2_LAG), 0) - ((unsigned)(p - busy) < 24);
                    if (idle) asm volatile("mbarrier.arrive.shared::cta.b64 _, [%0], %1;\n" ::"r"(bar_bempty + st * 8), "r"(idle * 8) : "memory");
                    if (rank == 0) asm volatile("red.relaxed.gpu.global.add.u32 [%0], 1;\n" ::"l"(&g_prog) : "memory");
                }
                __syncwarp();
                if (++st == P2_NB) { st = 0; ph ^= 1; }
                if (++kb == 48) kb = 0;
                if (++r == P2_LAG) { r = 0; m++; }
            }
            mbar_wait(bar_bempty + st * 8, ph);
            if (lane == 0) mbar_arrive(bar_bfull + st * 8);
#pragma unroll 1
            for (int p = 1; p < P2_NB; p++) {
                if (++st == P2_NB) { st = 0; ph ^= 1; }
                mbar_wait(bar_bempty + st * 8, ph);
            }
        } else if (warp == 13) {
            const uint8_t* src[3];
            int n[3], left[3], wrap[3];
            uint32_t st[3];
            auto item = [&](int w) {
                const int u = (k0 + p2_start(n[w])) % 48;
                left[w] = n[w] < 0 || n[w] == P2_ITEMS ? 24 : 48;
                wrap[w] = left[w] - (48 - u);
                src[w] = reinterpret_cast<const uint8_t*>(g_h) + (size_t)p2_tile(cl, n[w]) * (2 * H_TILE) + rank * H_HALF + u * H_STEP;
            };
#pragma unroll
            for (int w = 0; w < 3; w++) {
                n[w] = w == 2 && head ? -1 : w;
                st[w] = 0x80000000u;
                item(w);
            }
            gdc_wait();
#pragma unroll 1
            for (int done = 0; done < 3;) {
                bool idle = true;
#pragma unroll
                for (int w = 0; w < 3; w++) {
                    const uint32_t o = (st[w] & 0xff) + w * P2_NA * 8;
                    if (left[w] >= 0 && mbar_test(bar_aempty + o, st[w] >> 31)) {
                        idle = false;
                        if (left[w] == 0) {
                            if (lane == 0) mbar_arrive(bar_afull + o);
                            left[w] = -1;
                            done++;
                        } else {
                            if (elect_one()) {
                                mbar_expect_tx(bar_afull + o, P2_A);
                                bulk_g2s(sbase + P2_OFF_A + o * (P2_A / 8), src[w], P2_A, bar_afull + o);
                            }
                            __syncwarp();
                            src[w] += H_STEP;
                            st[w] += 8;
                            if ((st[w] & 0xff) == P2_NA * 8) st[w] ^= 0x80000000u | (P2_NA * 8);
                            if (--left[w] == wrap[w]) src[w] -= 48 * H_STEP;
                            if (left[w] == 0 && (n[w] += 3) < P2_ITEMS + tail) item(w);
                        }
                    }
                }
                if (idle) __nanosleep(P2_HSLEEP);
                SAFE_BREAK
            }
        } else if (warp == 14) {
            const uint32_t sx = sbase + P2_OFF_X;
            size_t o = 0;
            auto pace = [&](int target) {
                int v;
                while (true) {
                    asm volatile("ld.volatile.shared.u32 %0, [%1];\n" : "=r"(v) : "r"(s_pos) : "memory");
                    if (v * 16 >= target) break;
                    __nanosleep(P2_PSLEEP);
                    SAFE_BREAK
                }
            };
#pragma unroll 1
            for (int n = -head; n <= P2_ITEMS; n++) {
                const size_t on = (size_t)(2 * p2_tile(cl, n) + rank) * (64 * C_DIM * 2);
                const bool st = n + head > 0, ld = n < P2_ITEMS;
                if (st) mbar_wait(bar_oready, (n - 1 + head) & 1);
                TR2P(n + 1, 1);
                if (lane == 0) {
                    if (n == 1 && head) {
                        asm volatile("cp.async.bulk.wait_group 0;\nfence.proxy.async.global;\n" ::: "memory");
                        asm volatile("st.release.gpu.global.u32 [%0], 1;\n" ::"l"(&g_half[pair][rank]) : "memory");
                    }
                    if (ld) mbar_expect_tx(bar_xfull, 64 * C_DIM * 2);
                    int t = st && n < P2_ITEMS - 1 ? (P2_LAG * (n - 1) + 48 + P2_T0 - 1) * 16 : -1024;
#pragma unroll 1
                    for (int c = 0; st && c < 64 * P2_XROW; c += P2_XC) {
                        pace(t += P2_TS);
                        bulk_s2g(reinterpret_cast<uint8_t*>(out) + o + c, sx + c + (c >= 32 * P2_XROW ? 64 : 0), P2_XC);
                    }
                    asm volatile("cp.async.bulk.commit_group;\ncp.async.bulk.wait_group.read 0;\n" ::: "memory");
#pragma unroll 1
                    for (int c = 0; ld && c < 64 * P2_XROW; c += P2_XC) {
                        pace(t += P2_TS);
                        bulk_g2s(sx + c + (c >= 32 * P2_XROW ? 64 : 0), reinterpret_cast<const uint8_t*>(x) + on + c, P2_XC, bar_xfull);
                    }
                    TR2P(n + 1, 2);
                    if (rank == 0 && n > 0 && n < P2_ITEMS - 2)
                        flag_wait<false>(&g_prog, P2_NCL * (P2_LAG * n + 48 + P2_EXTRA) + (tail ? P2_SHARED - P2_NCL : P2_SHARED) * P2_DELTA);
                    if (ld) mbar_arrive(bar_xfull);
                    TR2P(n + 1, 3);
                }
                __syncwarp();
                o = on;
            }
            asm volatile("cp.async.bulk.wait_group 0;\n" ::: "memory");
            TR2P(30, 1);
        }
    } else {
        reg_inc<160>();
        const int wg = warp >> 2, w = warp & 3, g = lane >> 2, q = lane & 3;
        const uint32_t sx = sbase + P2_OFF_X + (g & 1) * P2_XHALF + (w * 8 + (g >> 1)) * P2_XROW + q * 16;
        const uint32_t af = bar_afull + wg * P2_NA * 8, ae = bar_aempty + wg * P2_NA * 8;
        const uint32_t s_a = sbase + P2_OFF_A - bar_afull * (P2_A / 8) + (lane >> 3) * 512 + (lane & 7) * 64 +
                             ((w ^ ((lane & 7) >> 1)) << 4);
        uint32_t acc0[48], acc1[48], dn;
        float up;
        uint4 a0[2], a1[2];
        int st = 0, ph = 0;

        {
            float4* s_red = reinterpret_cast<float4*>(smem + P2_OFF_BIAS);
            const float* sums = g_sums[par];
            float gx[4], part = 0.f, mx = 0.f;
            TSTAMP(1, 27);
            gdc_wait();
            TSTAMP(1, 1);
#pragma unroll
            for (int i = 0; i < 4; i++) gx[i] = __ldcg(sums + tid + 384 * i);
            if (blockIdx.x == 120 && tid < (LN_RING + 4) * 2) (&g_flag[0][0][0])[tid * 8] = 0;
            if (blockIdx.x == 121 && tid == 0) atomicAdd(&g_epoch, 1u);
            float z = __uint_as_float(__reduce_max_sync(0xffffffffu, __float_as_uint(pre[2] + pre[3])));
#pragma unroll
            for (int i = 0; i < 4; i++) {
                asm("sqrt.approx.f32 %0, %1;\n" : "=f"(gx[i]) : "f"(fmaf(gx[i], HSCALE * HSCALE, 1e-6f)));
                part += gx[i];
                gx[i] *= bf_lo(gg[i]);
                mx = fmaxf(mx, fabsf(gx[i]));
            }
#pragma unroll
            for (int o = 16; o > 0; o >>= 1) part += __shfl_xor_sync(0xffffffffu, part, o);
            mx = __uint_as_float(__reduce_max_sync(0xffffffffu, __float_as_uint(mx)));
            TSTAMP(1, 26);
            if (lane == 0) s_red[warp] = make_float4(part, mx, z, 0.f);
            bar_sync(1, 384);
            float tot = 0.f;
            {
                const float4 t = s_red[min(lane & 15, 11)];
                tot = (lane & 15) < 12 ? t.x : 0.f;
#pragma unroll
                for (int o = 8; o > 0; o >>= 1) tot += __shfl_xor_sync(0xffffffffu, tot, o);
                mx = __uint_as_float(__reduce_max_sync(0xffffffffu, __float_as_uint(t.y)));
                z = __uint_as_float(__reduce_max_sync(0xffffffffu, __float_as_uint(t.z)));
            }
            const float inv = __fdividef(1.0f, fmaf(tot, 1.0f / HID, 1e-6f));
#pragma unroll
            for (int i = 0; i < 4; i++) {
                const int k = tid + 384 * i;
                *reinterpret_cast<__nv_bfloat16*>(smem + P2_OFF_GRN + (k >> 5) * 64 + ((k >> 1) & 3) * 16 + ((k >> 3) & 3) * 4 + (k & 1) * 2) =
                    __float2bfloat16(gx[i] * inv);
            }
            const uint32_t j = max(__float_as_uint(fmaf(mx, inv, 1.0f) * 1.01f) >> 23, 130u) - 130u;
            dn = __shfl_sync(0xffffffffu, j ? (127u - j) * 0x00800080u : 0u, 0);
            up = HSCALE * __uint_as_float(min(acc_exp(z) - 9u + j, 253u) << 23);
            TSTAMP(1, 25);
            bar_sync(1, 384);
            reinterpret_cast<float*>(smem + P2_OFF_BIAS)[tid] = pre[0] + pre[1];
        }
        TSTAMP(1, 28);
        const uint32_t s_t = sbase + P2_OFF_GRN + q * 16;
        int kt, pos;
        const int who = __shfl_sync(0xffffffffu, lane == 2 ? 0 : lane < 2 ? 1 : 2, lane);
        const uint32_t rel0 = who ? mapa(bar_bempty, lane & 1) : mapa(ae, rank), rel1 = rel0 + (who ? P2_NB : P2_NA) * 8;
        uint32_t rel = rel1 - 8;
        auto next_rel = [&](bool go) {
            if (go) rel += 8;
            if (rel == rel1) rel = rel0;
        };
        auto release_b = [&]() {
            next_rel(who == 1);
            if (who == 1) mbar_arrive_cluster(rel);
        };
        auto seek = [&](int p) {
            pos = p;
            kt = (k0 + p) % 48;
            st = p % P2_NB;
            ph = p / P2_NB & 1;
            if (who == 1) rel = (st ? rel0 + st * 8 : rel1) - 8;
            int v;
            while (true) {
                asm volatile("ld.volatile.shared.u32 %0, [%1];\n" : "=r"(v) : "r"(s_pos) : "memory");
                if (v >= p) break;
                __nanosleep(200);
                SAFE_BREAK
            }
        };
        auto publish = [&]() {
            asm volatile("fence.proxy.async.shared::cta;\n" ::: "memory");
            __syncwarp();
            if (who == 0) mbar_arrive(bar_oready);
        };
        bool ok_a;
        uint32_t abar = af, pa = 0;
        auto fetch = [&](uint4 (&a)[2]) {
            uint32_t u0[4], u1[4];
            const uint32_t src = s_a + abar * (P2_A / 8);
            abar += 8;
            if (abar == af + P2_NA * 8) { abar = af; pa ^= 0x80000000u; }
            uint32_t t[4];
            asm volatile("ld.shared.v4.u32 {%0,%1,%2,%3}, [%4];\n" : "=r"(t[0]), "=r"(t[1]), "=r"(t[2]), "=r"(t[3]) : "r"(s_t + kt * 64) : "memory");
            const bool ok_b = mbar_test(bar_bfull + st * 8, ph);
            ok_a = mbar_test(abar, pa >> 31);
            uint32_t o[6];
            asm volatile("ldmatrix.sync.aligned.m8n8.x4.trans.shared.b16 {%0,%1,%2,%3}, [%4];\n"
                         : "=r"(o[0]), "=r"(o[1]), "=r"(o[2]), "=r"(o[3]) : "r"(src) : "memory");
            asm volatile("ldmatrix.sync.aligned.m8n8.x2.trans.shared.b16 {%0,%1}, [%2];\n"
                         : "=r"(o[4]), "=r"(o[5]) : "r"(src + 2048) : "memory");
            p2_unpack(u0, o[0], o[1], o[2]);
            p2_unpack(u1, o[3], o[4], o[5]);
#pragma unroll
            for (int i = 0; i < 4; i++) {
                u0[i] = bf2_fma(u0[i], t[i >> 1], u0[i]);
                u1[i] = bf2_fma(u1[i], t[2 + (i >> 1)], u1[i]);
            }
            if (dn) {
#pragma unroll
                for (int i = 0; i < 4; i++) {
                    u0[i] = bf2_mul(u0[i], dn);
                    u1[i] = bf2_mul(u1[i], dn);
                }
            }
            a[0] = make_uint4(bf2_as_h2(u0[0]), bf2_as_h2(u0[1]), bf2_as_h2(u0[2]), bf2_as_h2(u0[3]));
            a[1] = make_uint4(bf2_as_h2(u1[0]), bf2_as_h2(u1[1]), bf2_as_h2(u1[2]), bf2_as_h2(u1[3]));
            if (++kt == 48) kt = 0;
            if (!ok_b) mbar_wait(bar_bfull + st * 8, ph);
        };
        auto step = [&](const uint4 (&a)[2], uint4 (&an)[2], int thr) {
            TR2(0);
            const uint64_t db = make_desc(sbase + st * P2_B, 128, 256);
            wg_fence();
            mma_rs_n192(acc0, a[0], db, thr - 1);
            mma_rs_n192(acc1, a[0], db + 384, thr - 1);
            mma_rs_n192(acc0, a[1], db + 768, 1);
            mma_rs_n192(acc1, a[1], db + 768 + 384, 1);
            wg_commit();
            next_rel(who < thr);
            if (++st == P2_NB) { st = 0; ph ^= 1; }
            wg_wait<1>();
            if (!ok_a) {
                if (who < thr) mbar_arrive_cluster(rel);
                thr = 0;
                mbar_wait(abar, pa >> 31);
            }
            if (who < thr) mbar_arrive_cluster(rel);
            fetch(an);
            pos++;
        };
        mbar_wait(af, 0);
#pragma unroll 1
        for (int n = wg == 2 && head ? -1 : wg;; n += 3) {
            seek(p2_start(n));
            fetch(a0);
            TSTAMP(1, 2 + n);
            const int p0 = n < 0 || n == P2_ITEMS ? 12 : 0;
            const bool more = n + 3 < P2_ITEMS + tail;
#pragma unroll 1
            for (int p = p0; p < 24; p++) {
                step(a0, a1, p == p0 ? 1 : 2);
                step(a1, a0, 2);
            }
            if (n == P2_ITEMS) {
                flag_wait<true>(&g_half[pair][rank], 1);
                TR2(1);
                wg_wait<0>();
                TR2(2);
                release_b();
                uint8_t* o = reinterpret_cast<uint8_t*>(out) + (size_t)((2 * p2_tile(cl, -1) + rank) * 64 + (g & 1) * 32 + w * 8 + (g >> 1)) * P2_XROW + q * 16;
                p2_epilogue_add(acc0, o, up, zero);
                p2_epilogue_add(acc1, o + 384, up, zero);
                TR2(3);
                break;
            }
            mbar_wait(bar_xfull, (n + head) & 1);
            TR2(1);
            wg_wait<0>();
            TR2(2);
            release_b();
            __syncwarp();
            p2_epilogue(acc0, acc1, sx, sbase + P2_OFF_BIAS + q * 32, up, zero);
            TR2(3);
            publish();
            if (!more) break;
            if (abar == af) { abar = af + P2_NA * 8; pa ^= 0x80000000u; }
            abar -= 8;
        }
        TSTAMP(1, 30);
    }
}

}

extern "C" void kernel_launch(void* const* d_in, const int* in_sizes, int n_in, void* d_out, int out_size) {
    const __nv_bfloat16* x = (const __nv_bfloat16*)d_in[0];
    const __nv_bfloat16* dw = (const __nv_bfloat16*)d_in[1];
    const __nv_bfloat16* w1 = (const __nv_bfloat16*)d_in[2];
    const __nv_bfloat16* w2 = (const __nv_bfloat16*)d_in[3];
    const __nv_bfloat16* grn_g = (const __nv_bfloat16*)d_in[4];
    const __nv_bfloat16* grn_b = (const __nv_bfloat16*)d_in[5];
    __nv_bfloat16* out = (__nv_bfloat16*)d_out;

    cudaFuncSetAttribute(pass1_kernel, cudaFuncAttributeMaxDynamicSharedMemorySize, P1_SMEM);
    cudaFuncSetAttribute(pass2_kernel, cudaFuncAttributeMaxDynamicSharedMemorySize, P2_SMEM);

    typedef CUresult (*EncodeFn)(CUtensorMap*, CUtensorMapDataType, cuuint32_t, void*, const cuuint64_t*, const cuuint64_t*,
                                 const cuuint32_t*, const cuuint32_t*, CUtensorMapInterleave, CUtensorMapSwizzle,
                                 CUtensorMapL2promotion, CUtensorMapFloatOOBfill);
    static EncodeFn encode = nullptr;
    if (!encode) {
        cudaDriverEntryPointQueryResult qres;
        cudaGetDriverEntryPoint("cuTensorMapEncodeTiled", (void**)&encode, cudaEnableDefault, &qres);
    }
    CUtensorMap wmap;
    const cuuint64_t gdim[2] = {HID, C_DIM};
    const cuuint64_t gstr[1] = {HID * 2};
    const cuuint32_t box[2] = {64, 192}, estr[2] = {1, 1};
    CUresult er = encode(&wmap, CU_TENSOR_MAP_DATA_TYPE_BFLOAT16, 2, (void*)w1, gdim, gstr, box, estr, CU_TENSOR_MAP_INTERLEAVE_NONE,
           CU_TENSOR_MAP_SWIZZLE_128B, CU_TENSOR_MAP_L2_PROMOTION_L2_128B, CU_TENSOR_MAP_FLOAT_OOB_FILL_NONE);
    if (er != CUDA_SUCCESS) printf("tensor map encode failed %d\n", (int)er);

    pass1_kernel<<<NUM_CTAS, 512, P1_SMEM>>>(wmap, x, dw, w2, grn_b, 0);

    cudaLaunchAttribute attr[1];
    attr[0].id = cudaLaunchAttributeProgrammaticStreamSerialization;
    attr[0].val.programmaticStreamSerializationAllowed = 1;
    cudaLaunchConfig_t cfg = {};
    cfg.gridDim = dim3(NUM_CTAS);
    cfg.stream = 0;
    cfg.attrs = attr;
    cfg.numAttrs = 1;
    cfg.blockDim = dim3(512);
    cfg.dynamicSmemBytes = P2_SMEM;
    cudaLaunchKernelEx(&cfg, pass2_kernel, x, grn_g, out, 0);
}
```

```cpp
#include <cuda.h>
#include <cuda_runtime.h>
#include <cuda_bf16.h>
#include <stdint.h>
#include <stdio.h>

namespace {

constexpr int M_TOTAL = 384 * 384;
constexpr int C_DIM   = 384;
constexpr int HID     = 1536;
constexpr int NT128   = M_TOTAL / 128;
constexpr int NUM_CTAS = 132;

constexpr int NGRP = 11, GRP_CTAS = 12;
constexpr int LN_STEP = NUM_CTAS / 4, LN_RING = 2 * LN_STEP;
constexpr int NT_RING = NT128 - NGRP;
constexpr int LN_TILE = 128 * C_DIM * 2;
constexpr int H_TILE = 64 * HID * 3 / 2;
constexpr int H_HALF = 3072, H_STEP = 6144;

__device__ __align__(1024) uint4 g_h[(size_t)M_TOTAL * HID * 3 / 32];
__device__ __align__(1024) uint4 g_ln[LN_RING * LN_TILE / 16];
__device__ __align__(1024) uint4 g_w2img[2][HID * C_DIM * 2 / 16];
__device__ __align__(16) float g_sums[2][HID + 2 * C_DIM];
__device__ unsigned g_ex[HID];
__device__ unsigned g_epoch, g_par;
__device__ __align__(128) unsigned g_img[2];
__device__ __align__(128) unsigned g_prog;
__device__ __align__(128) unsigned g_half[32][2];
__device__ unsigned g_flag[LN_RING + 4][2][8];
#define TSTAMP(k, i)
#define TRACE(wg, pos, i)
#define TRACEW(pos, i)

#define TR2(i)
#define TR2P(pos, i)
__host__ __device__ __forceinline__ int perm32(int n) {
    return (n & ~31) | (((n >> 1) & 3) << 3) | (((n >> 3) & 3) << 1) | (n & 1);
}

__device__ __forceinline__ uint32_t smem_u32(const void* p) { return (uint32_t)__cvta_generic_to_shared(p); }

__device__ __forceinline__ void mbar_init(uint32_t bar, uint32_t count) {
    asm volatile("mbarrier.init.shared::cta.b64 [%0], %1;\n" ::"r"(bar), "r"(count) : "memory");
}
__device__ __forceinline__ void mbar_expect_tx(uint32_t bar, uint32_t bytes) {
    asm volatile("mbarrier.arrive.expect_tx.shared::cta.b64 _, [%0], %1;\n" ::"r"(bar), "r"(bytes) : "memory");
}
__device__ __forceinline__ void mbar_arrive(uint32_t bar) {
    asm volatile("mbarrier.arrive.shared::cta.b64 _, [%0];\n" ::"r"(bar) : "memory");
}
__device__ __forceinline__ void mbar_arrive_cluster(uint32_t bar_cluster_addr) {
    asm volatile("mbarrier.arrive.shared::cluster.b64 _, [%0];\n" ::"r"(bar_cluster_addr) : "memory");
}
#define SAFE_BREAK
__device__ __forceinline__ void mbar_wait(uint32_t bar, uint32_t parity) {
    asm volatile(
        "{\n"
        ".reg .pred p;\n"
        "LAB_WAIT:\n"
        "mbarrier.try_wait.parity.shared::cta.b64 p, [%0], %1;\n"
        "@!p bra LAB_WAIT;\n"
        "}\n" ::"r"(bar), "r"(parity) : "memory");
}
__device__ __forceinline__ bool mbar_test(uint32_t bar, uint32_t parity) {
    uint32_t ok;
    asm volatile("{\n.reg .pred p;\n"
                 "mbarrier.test_wait.parity.shared::cta.b64 p, [%1], %2;\n"
                 "selp.u32 %0, 1, 0, p;\n}\n" : "=r"(ok) : "r"(bar), "r"(parity) : "memory");
    return ok != 0;
}
__device__ __forceinline__ uint32_t mapa(uint32_t addr, uint32_t rank) {
    uint32_t r;
    asm volatile("mapa.shared::cluster.u32 %0, %1, %2;\n" : "=r"(r) : "r"(addr), "r"(rank));
    return r;
}
__device__ __forceinline__ void bulk_g2s(uint32_t dst, const void* src, uint32_t bytes, uint32_t bar) {
    asm volatile("cp.async.bulk.shared::cluster.global.mbarrier::complete_tx::bytes [%0], [%1], %2, [%3];\n"
                 ::"r"(dst), "l"(src), "r"(bytes), "r"(bar) : "memory");
}
__device__ __forceinline__ void bulk_g2s_mc(uint32_t dst, const void* src, uint32_t bytes, uint32_t bar, uint16_t mask) {
    asm volatile("cp.async.bulk.shared::cluster.global.mbarrier::complete_tx::bytes.multicast::cluster [%0], [%1], %2, [%3], %4;\n"
                 ::"r"(dst), "l"(src), "r"(bytes), "r"(bar), "h"(mask) : "memory");
}
__device__ __forceinline__ void tma2(uint32_t dst, const CUtensorMap* map, int c0, int c1, uint32_t bar) {
    asm volatile("cp.async.bulk.tensor.2d.shared::cluster.global.tile.mbarrier::complete_tx::bytes [%0], [%1, {%2, %3}], [%4];\n"
                 ::"r"(dst), "l"(map), "r"(c0), "r"(c1), "r"(bar) : "memory");
}
template <bool ACQ>
__device__ __forceinline__ uint32_t flag_wait(const unsigned* p, unsigned target) {
    unsigned v, n = 0;
    do {
        if (ACQ) asm volatile("ld.acquire.gpu.global.u32 %0, [%1];\n" : "=r"(v) : "l"(p) : "memory");
        else asm volatile("ld.relaxed.gpu.global.u32 %0, [%1];\n" : "=r"(v) : "l"(p) : "memory");
        n++;
    } while (v < target);
    return n == 1;
}
__device__ __forceinline__ void ldsm4t(uint32_t (&r)[4], uint32_t addr) {
    asm volatile("ldmatrix.sync.aligned.m8n8.x4.trans.shared.b16 {%0,%1,%2,%3}, [%4];\n"
                 : "=r"(r[0]), "=r"(r[1]), "=r"(r[2]), "=r"(r[3]) : "r"(addr) : "memory");
}
__device__ __forceinline__ void bulk_s2g(void* dst, uint32_t src, uint32_t bytes) {
    asm volatile("cp.async.bulk.global.shared::cta.bulk_group [%0], [%1], %2;\n" ::"l"(dst), "r"(src), "r"(bytes) : "memory");
}
__device__ __forceinline__ void cluster_sync_relaxed() {
    asm volatile("barrier.cluster.arrive.relaxed.aligned;\nbarrier.cluster.wait.aligned;\n" ::: "memory");
}
__device__ __forceinline__ void gdc_wait() { asm volatile("griddepcontrol.wait;\n" ::: "memory"); }
__device__ __forceinline__ void gdc_launch() { asm volatile("griddepcontrol.launch_dependents;\n" ::: "memory"); }
__device__ __forceinline__ uint32_t cluster_rank() {
    uint32_t r;
    asm volatile("mov.u32 %0, %%cluster_ctarank;\n" : "=r"(r));
    return r;
}
__device__ __forceinline__ bool elect_one() {
    uint32_t pred;
    asm volatile("{\n.reg .pred p;\nelect.sync _|p, 0xffffffff;\nselp.u32 %0, 1, 0, p;\n}\n" : "=r"(pred));
    return pred != 0;
}
__device__ __forceinline__ void wg_fence() { asm volatile("wgmma.fence.sync.aligned;\n" ::: "memory"); }
__device__ __forceinline__ void wg_commit() { asm volatile("wgmma.commit_group.sync.aligned;\n" ::: "memory"); }
template <int N> __device__ __forceinline__ void wg_wait() {
    asm volatile("wgmma.wait_group.sync.aligned %0;\n" ::"n"(N) : "memory");
}
template <int R> __device__ __forceinline__ void reg_inc() { asm volatile("setmaxnreg.inc.sync.aligned.u32 %0;\n" ::"n"(R)); }
template <int R> __device__ __forceinline__ void reg_dec() { asm volatile("setmaxnreg.dec.sync.aligned.u32 %0;\n" ::"n"(R)); }
__device__ __forceinline__ void bar_sync(int id, int n) { asm volatile("bar.sync %0, %1;\n" ::"r"(id), "r"(n) : "memory"); }
__device__ __forceinline__ void bar_arrive(int id, int n) { asm volatile("bar.arrive %0, %1;\n" ::"r"(id), "r"(n) : "memory"); }

__device__ __forceinline__ uint64_t make_desc(uint32_t saddr, uint32_t lbo, uint32_t sbo) {
    return (uint64_t)((saddr & 0x3FFFF) >> 4) | ((uint64_t)(lbo >> 4) << 16) | ((uint64_t)(sbo >> 4) << 32);
}

__device__ __forceinline__ void stg128_cs(void* p, uint32_t a, uint32_t b, uint32_t c, uint32_t d) {
    asm volatile("st.global.cs.v4.u32 [%0], {%1,%2,%3,%4};\n" ::"l"(p), "r"(a), "r"(b), "r"(c), "r"(d) : "memory");
}
__device__ __forceinline__ uint32_t pack_bf16(float lo, float hi) {
    uint32_t r;
    asm("cvt.rn.bf16x2.f32 %0, %1, %2;\n" : "=r"(r) : "f"(hi), "f"(lo));
    return r;
}
__device__ __forceinline__ float bf_lo(uint32_t v) { return __uint_as_float(v << 16); }
__device__ __forceinline__ float bf_hi(uint32_t v) { return __uint_as_float(v & 0xffff0000u); }
__device__ __forceinline__ uint32_t bf2_mul(uint32_t a, uint32_t b) {
    uint32_t r;
    asm("mul.rn.bf16x2 %0, %1, %2;\n" : "=r"(r) : "r"(a), "r"(b));
    return r;
}
__device__ __forceinline__ uint32_t bf2_fma(uint32_t a, uint32_t b, uint32_t c) {
    uint32_t r;
    asm("fma.rn.bf16x2 %0, %1, %2, %3;\n" : "=r"(r) : "r"(a), "r"(b), "r"(c));
    return r;
}
__device__ __forceinline__ uint32_t bf2_add(uint32_t a, uint32_t b) {
    uint32_t r;
    asm("add.rn.bf16x2 %0, %1, %2;\n" : "=r"(r) : "r"(a), "r"(b));
    return r;
}
constexpr float KAPPA = 0.3292034911525734f;
constexpr float GELU_C = 2.423681954311584f;
constexpr float HSCALE = 1.0f / (2.0f * KAPPA);
__device__ __forceinline__ uint32_t acc_exp(float z) { return max(__float_as_uint(z) >> 23, 10u); }
__device__ __forceinline__ void sched_break(int zero) {
    asm volatile("{\n.reg .pred p;\nsetp.ne.s32 p, %0, 0;\nSB_LOOP:\n@p nanosleep.u32 1;\n@p bra SB_LOOP;\n}\n" ::"r"(zero));
}

#define ACC8(d, o) "+f"(d[o + 0]), "+f"(d[o + 1]), "+f"(d[o + 2]), "+f"(d[o + 3]), "+f"(d[o + 4]), "+f"(d[o + 5]), "+f"(d[o + 6]), "+f"(d[o + 7])

#define ACCR8(d, o) "+r"(d[o + 0]), "+r"(d[o + 1]), "+r"(d[o + 2]), "+r"(d[o + 3]), "+r"(d[o + 4]), "+r"(d[o + 5]), "+r"(d[o + 6]), "+r"(d[o + 7])
__device__ __forceinline__ void mma_rs_n128(uint32_t (&d)[32], const uint32_t (&a)[4], uint64_t desc, int scale_d) {
    asm volatile(
        "{\n.reg .pred p;\nsetp.ne.b32 p, %37, 0;\n"
        "wgmma.mma_async.sync.aligned.m64n128k16.f16.f16.f16 "
        "{%0,%1,%2,%3,%4,%5,%6,%7,%8,%9,%10,%11,%12,%13,%14,%15,"
        "%16,%17,%18,%19,%20,%21,%22,%23,%24,%25,%26,%27,%28,%29,%30,%31},"
        "{%32,%33,%34,%35}, %36, p, 1, 1, 0;\n}\n"
        : ACCR8(d, 0), ACCR8(d, 8), ACCR8(d, 16), ACCR8(d, 24)
        : "r"(a[0]), "r"(a[1]), "r"(a[2]), "r"(a[3]), "l"(desc), "r"(scale_d));
}
__device__ __forceinline__ uint32_t bf2_as_h2(uint32_t v) { return (v & 0x0fff0fffu) * 7u + v; }
__device__ __forceinline__ float h_lo(uint32_t v) {
    float r;
    asm("{\n.reg .b16 l, h;\nmov.b32 {l, h}, %1;\ncvt.f32.f16 %0, l;\n}\n" : "=f"(r) : "r"(v));
    return r;
}
__device__ __forceinline__ float h_hi(uint32_t v) {
    float r;
    asm("{\n.reg .b16 l, h;\nmov.b32 {l, h}, %1;\ncvt.f32.f16 %0, h;\n}\n" : "=f"(r) : "r"(v));
    return r;
}

__device__ __forceinline__ void mma_rs_n192(uint32_t (&d)[48], const uint4& a, uint64_t db, int scale_d) {
    asm volatile(
        "{\n.reg .pred p;\nsetp.ne.b32 p, %53, 0;\n"
        "wgmma.mma_async.sync.aligned.m64n192k16.f16.f16.f16 "
        "{%0,%1,%2,%3,%4,%5,%6,%7,%8,%9,%10,%11,%12,%13,%14,%15,"
        "%16,%17,%18,%19,%20,%21,%22,%23,%24,%25,%26,%27,%28,%29,%30,%31,"
        "%32,%33,%34,%35,%36,%37,%38,%39,%40,%41,%42,%43,%44,%45,%46,%47},"
        "{%48,%49,%50,%51}, %52, p, 1, 1, 0;\n}\n"
        : ACCR8(d, 0), ACCR8(d, 8), ACCR8(d, 16), ACCR8(d, 24), ACCR8(d, 32), ACCR8(d, 40)
        : "r"(a.x), "r"(a.y), "r"(a.z), "r"(a.w), "l"(db), "r"(scale_d));
}

__device__ __forceinline__ uint32_t pack_f16(float lo, float hi) {
    uint32_t r;
    asm("cvt.rn.f16x2.f32 %0, %1, %2;\n" : "=r"(r) : "f"(hi), "f"(lo));
    return r;
}

#define P1_REGS 192
#define P1_WARM 0
#define P1_DEF 3
#define P1_ARR 23
constexpr int P1_SLOT = LN_TILE / 2, P1_NST = 4;
constexpr int P1_X = 32 * C_DIM * 2;
constexpr int P1_OFF_X = P1_SLOT * P1_NST;
constexpr int P1_OFF_BAR = P1_OFF_X + P1_X;
constexpr int P1_OFF_TILE = P1_OFF_BAR + (2 * P1_NST + 2 + 4) * 8;
constexpr int P1_OFF_RAW = P1_OFF_TILE + 64;
constexpr int P1_OFF_DW = P1_OFF_RAW + 32;
constexpr int P1_SMEM = P1_OFF_DW + C_DIM * 2;

__device__ __forceinline__ float rsqrt_fast(float x) {
    float r;
    asm("rsqrt.approx.ftz.f32 %0, %1;\n" : "=f"(r) : "f"(x));
    return r;
}
__device__ __forceinline__ float row_sum(const uint32_t (&c)[4]) {
    const uint32_t u = bf2_add(bf2_add(c[0], c[1]), bf2_add(c[2], c[3]));
    float s = bf_lo(u) + bf_hi(u);
#pragma unroll
    for (int o = 1; o < 8; o <<= 1) s += __shfl_xor_sync(0xffffffffu, s, o);
    return s;
}
__device__ __forceinline__ void ln_row(uint32_t (&v)[6][4], const uint32_t (&d)[6][4], int zero, uint32_t bar_read) {
    uint32_t c[4];
#pragma unroll
    for (int i = 0; i < 6; i++)
#pragma unroll
        for (int k = 0; k < 4; k++) c[k] = bf2_fma(v[i][k], d[i][k], i ? c[k] : 0);
    const float inv = 1.0f / C_DIM;
    const float m = row_sum(c) * inv;
    const uint32_t nm = pack_bf16(-m, -m);
    const float e = m + bf_lo(nm);
    if (bar_read) mbar_arrive(bar_read + (nm & zero));
#pragma unroll
    for (int i = 0; i < 6; i++) {
#pragma unroll
        for (int k = 0; k < 4; k++) {
            v[i][k] = bf2_fma(v[i][k], d[i][k], nm);
            c[k] = i ? bf2_fma(v[i][k], v[i][k], c[k]) : bf2_mul(v[i][k], v[i][k]);
        }
    }
    float r = KAPPA * rsqrt_fast(fmaxf(fmaf(-e, e, row_sum(c) * inv), 0.f) + 1e-5f);
    const uint32_t sh = pack_bf16(-e * r * 0x1p-112f, -e * r * 0x1p-112f);
    if (__any_sync(0xffffffffu, r < 0x1p-14f)) {
        const uint32_t f = r < 0x1p-14f ? 0x23802380u : 0x3f803f80u;
        if (r < 0x1p-14f) r *= 0x1p56f;
#pragma unroll
        for (int i = 0; i < 6; i++)
#pragma unroll
            for (int k = 0; k < 4; k++) v[i][k] = bf2_mul(v[i][k], f);
    }
    const uint32_t rs = pack_bf16(r * 0x1p-112f, r * 0x1p-112f);
#pragma unroll
    for (int i = 0; i < 6; i++)
#pragma unroll
        for (int k = 0; k < 4; k++) v[i][k] = bf2_as_h2(bf2_fma(v[i][k], rs, sh));
}

__device__ __forceinline__ void load_dw(uint32_t (&d)[6][4], uint32_t sbase, int lane) {
    mbar_wait(sbase + P1_OFF_RAW + 16, 0);
#pragma unroll
    for (int j = 0; j < 6; j++)
        asm volatile("ld.shared.v4.u32 {%0,%1,%2,%3}, [%4];\n" : "=r"(d[j][0]), "=r"(d[j][1]), "=r"(d[j][2]), "=r"(d[j][3])
                     : "r"(sbase + P1_OFF_DW + j * 128 + (lane & 7) * 16) : "memory");
}

__device__ __forceinline__ float gelu_s(float y) {
    float u = y * fmaf(y, y, GELU_C);
    float t;
    asm volatile("tanh.approx.f32 %0, %1;\n" : "=f"(t) : "f"(u));
    return fmaf(y, t, y);
}
__device__ __forceinline__ void p1_pack(int c, uint32_t (&p)[4], uint32_t (&dd)[4]) {
#pragma unroll
    for (int u = 0; u < 4; u++) {
        if ((c & 3) == 0) dd[u] = p[u];
        else {
            uint32_t n = dd[u];
            if ((c & 3) == 1) n = __byte_perm(n, 0, 0x2301);
            if ((c & 3) == 2) {
                dd[u] = __byte_perm(n >> 3, n >> 1, 0x6341);
                n = __byte_perm(n >> 3, n >> 1, 0x7250);
            }
            asm("lop3.b32 %0, %0, %1, 0x40074007, 0xd8;\n" : "+r"(p[u]) : "r"(n));
        }
    }
}
__device__ __forceinline__ void p1_store(int c, const uint32_t (&p)[4], uint8_t* hptr) {
    if (c & 3) stg128_cs(hptr + (c >> 2) * H_HALF + ((c & 3) - 1) * 512, p[0], p[1], p[2], p[3]);
}

__device__ __forceinline__ uint32_t p1_parity(uint32_t sbase) {
    uint32_t v;
    asm volatile("ld.shared.u32 %0, [%1];\n" : "=r"(v) : "r"(sbase + P1_OFF_TILE - 4) : "memory");
    return v;
}
template <bool GEN, int C0, int C1, class F>
__device__ __forceinline__ void p1_epilogue(F v, uint32_t (&sq)[2], uint32_t (&dd)[4], float (&ssq)[2], uint32_t sc2, uint8_t* hp, int zero) {
#pragma unroll
    for (int c = C0; c < C1; c++) {
        if (GEN) sched_break(zero);
        uint32_t p[4];
#pragma unroll
        for (int u = 0; u < 4; u++) {
            const uint32_t y = v(c, u);
            if (GEN) {
                const float sc = c & 1 ? bf_hi(sc2) : bf_lo(sc2), fs = __uint_as_float(0x78000000u - __float_as_uint(sc));
                const float g0 = gelu_s(h_lo(y) * fs), g1 = gelu_s(h_hi(y) * fs);
                ssq[c & 1] = fmaf(g1, g1, fmaf(g0, g0, ssq[c & 1]));
                p[u] = pack_f16(g0 * sc, g1 * sc);
            } else {
                uint32_t g;
                asm("{\n.reg .b32 w;\n"
                    "fma.rn.f16x2 w, %1, %1, %2;\n"
                    "mul.rn.f16x2 w, w, %1;\n"
                    "tanh.approx.f16x2 w, w;\n"
                    "fma.rn.f16x2 %0, %1, w, %1;\n}\n" : "=r"(g) : "r"(y), "r"(0x40d940d9u));
                if (c < 2 && u == 0) asm("mul.rn.f16x2 %0, %1, %1;\n" : "=r"(sq[c & 1]) : "r"(g));
                else asm("fma.rn.f16x2 %0, %1, %1, %0;\n" : "+r"(sq[c & 1]) : "r"(g));
                if (c & 1) asm("{\n.reg .b16 l, h;\n.reg .b32 f;\nmov.b32 {l, h}, %2;\nmov.b32 f, {h, h};\nmul.rn.f16x2 %0, %1, f;\n}\n" : "=r"(p[u]) : "r"(g), "r"(sc2));
                else asm("{\n.reg .b16 l, h;\n.reg .b32 f;\nmov.b32 {l, h}, %2;\nmov.b32 f, {l, l};\nmul.rn.f16x2 %0, %1, f;\n}\n" : "=r"(p[u]) : "r"(g), "r"(sc2));
            }
        }
        p1_pack(c, p, dd);
        p1_store(c, p, hp);
    }
    if (!GEN && C1 == 8) {
#pragma unroll
        for (int r = 0; r < 2; r++) ssq[r] += h_lo(sq[r]) + h_hi(sq[r]);
    }
}
__device__ __forceinline__ void p1_consumer(const uint32_t (&a)[24][4], uint32_t sc2, bool gen, uint32_t sbase, int wg, int w, int lane, int zero) {
    const uint32_t bar_full = sbase + P1_OFF_BAR, bar_empty = bar_full + P1_NST * 8;
    const uint32_t empty_remote = mapa(bar_empty, lane & 1);
    const int g = lane >> 2, q = lane & 3, cb = (blockIdx.x % GRP_CTAS) * 2 + wg;
    float ssq[2] = {0.f, 0.f};
    uint32_t acc[32], sq[2] = {}, dd[4] = {}, dfr[P1_DEF * 4 + 1] = {};
    auto from_acc = [&](int c, int u) { return acc[8 * (c >> 1) + 2 * u + (c & 1)]; };
    auto from_dfr = [&](int c, int u) { return dfr[(c - 8 + P1_DEF) * 4 + u]; };
    TSTAMP(0, 1);

    uint8_t* hp = reinterpret_cast<uint8_t*>(g_h) + (size_t)(blockIdx.x / GRP_CTAS) * (2 * H_TILE) + ((cb * 2 + (w >> 1)) * H_STEP + (w & 1) * 1536) + g * 64 + (q ^ (g >> 1)) * 16;
    const uint64_t desc_base = make_desc(sbase, 16, 1024) | (1ull << 62);
#pragma unroll 1
    for (int i = 0;; i++) {
        const int s0 = (i & 1) * 16, par = (i >> 1) & 1;
        const uint64_t d0 = desc_base + (uint64_t)((i & 1) * (LN_TILE / 16));
        TRACE(wg, i, 0);
        mbar_wait(bar_full + s0, par);
        bar_sync(1 + wg, 256);
        TRACE(wg, i, 1);
        uint32_t step, more;
        wg_fence();
#pragma unroll
        for (int k = 0; k < 24; k++) {
            if (k == 12) mbar_wait(bar_full + s0 + 8, par);
            mma_rs_n128(acc, a[k], d0 + (uint64_t)((k >> 2) * 1024 + (k & 3) * 2), k != 0);
            if (k == P1_ARR) bar_arrive(2 - wg, 256);
            if (k % 12 == 11) wg_commit();
        }
        asm volatile("ld.shared.v2.u32 {%0, %1}, [%2];\n" : "=r"(step), "=r"(more) : "r"(sbase + P1_OFF_TILE + (i & 3) * 16) : "memory");
        TRACE(wg, i, 2);
        wg_wait<1>();
        if (lane < 2) mbar_arrive_cluster(empty_remote + s0);
        if (P1_DEF && i && !gen) p1_epilogue<false, 8 - P1_DEF, 8>(from_dfr, sq, dd, ssq, sc2, hp, zero);
        hp += step;
        TRACE(wg, i, 3);
        wg_wait<0>();
        TRACE(wg, i, 4);
        if (lane < 2) mbar_arrive_cluster(empty_remote + s0 + 8);
        if (gen) p1_epilogue<true, 0, 8>(from_acc, sq, dd, ssq, sc2, hp, zero);
        else {
#pragma unroll
            for (int j = 0; j < P1_DEF * 4; j++) asm volatile("mov.b32 %0, %1;\n" : "=r"(dfr[j]) : "r"(from_acc(8 - P1_DEF + j / 4, j % 4)));
            p1_epilogue<false, 0, 8 - P1_DEF>(from_acc, sq, dd, ssq, sc2, hp, zero);
        }
        if (!more) break;
    }
    if (P1_DEF && !gen) p1_epilogue<false, 8 - P1_DEF, 8>(from_dfr, sq, dd, ssq, sc2, hp, zero);
    TSTAMP(0, 21);
    if (wg == 0) bar_sync(1, 256);
#pragma unroll
    for (int r = 0; r < 2; r++) {
        ssq[r] += __shfl_xor_sync(0xffffffffu, ssq[r], 1);
        ssq[r] += __shfl_xor_sync(0xffffffffu, ssq[r], 2);
        if (q == 0) atomicAdd(&g_sums[p1_parity(sbase)][cb * 64 + w * 16 + r * 8 + g], ssq[r]);
    }
}

__global__ void __cluster_dims__(2, 1, 1) __launch_bounds__(512, 1)
pass1_kernel(const __grid_constant__ CUtensorMap wmap, const __nv_bfloat16* __restrict__ x, const __nv_bfloat16* __restrict__ dw,
             const __nv_bfloat16* __restrict__ w2, const __nv_bfloat16* __restrict__ grn_b, int zero) {
    extern __shared__ __align__(1024) uint8_t smem[];
    const uint32_t sbase = smem_u32(smem);
    const uint32_t bar_full = sbase + P1_OFF_BAR, bar_empty = bar_full + P1_NST * 8, bar_w = bar_empty + P1_NST * 8;
    const int tid = threadIdx.x;
    const int warp = __shfl_sync(0xffffffffu, tid >> 5, 0), lane = tid & 31;
    const uint32_t rank = cluster_rank();
    const int cig = blockIdx.x % GRP_CTAS;
    uint8_t* const ring = reinterpret_cast<uint8_t*>(g_ln);

    TSTAMP(0, 0);
    TRACEW(110 + warp, 0);
    const uint32_t bar_xfull = bar_w + 16, bar_xempty = bar_xfull + 8, bar_done = bar_xfull + 16;
    const uint32_t bar_raw = sbase + P1_OFF_RAW;
    const int ln0 = blockIdx.x >> 2, first = blockIdx.x / GRP_CTAS;
    const uint8_t* xsrc = reinterpret_cast<const uint8_t*>(x) + (size_t)(NGRP * 4 + blockIdx.x) * P1_X;

    if (warp >= 12) {
        reg_dec<40>();
        asm volatile("barrier.cluster.arrive.relaxed.aligned;\n" ::: "memory");
        asm volatile("barrier.cluster.wait.aligned;\n" ::: "memory");
        if (warp == 12) {
            int prev = first - NGRP, t = first, next = t + NGRP;
            const uint32_t rbase = mapa(sbase, lane & 1);
            int i = 1;
#pragma unroll 1
            for (; t < NT_RING; i++) {
                const int s0 = (i & 1) * 2, par = ((i + 1) >> 1 & 1) ^ 1;
                const int round = t / LN_RING, slot = t - round * LN_RING;
                const uint8_t* src = ring + slot * LN_TILE + rank * (P1_SLOT / 2);
                int draw = 0;
                if (rank == 0 && lane == 0) draw = atomicAdd(&g_flag[LN_RING + (cig >> 2)][(cig >> 1) & 1][0], 1u);
                flag_wait<true>(&g_flag[slot][0][0], 4 * round + 4);
                TRACEW(i, 2);
                asm volatile("fence.proxy.async.global;\n" ::: "memory");
                draw = 2 * NGRP + __shfl_sync(0xffffffffu, draw, 0);
#pragma unroll
                for (int h = 0; h < 2; h++) {
                    mbar_wait(bar_empty + (s0 + h) * 8, par);
                    TRACEW(i, 4 + h);
                    if (elect_one()) {
                        mbar_expect_tx(bar_full + (s0 + h) * 8, P1_SLOT + 16 - 16 * h);
                        bulk_g2s_mc(sbase + (s0 + h) * P1_SLOT + rank * (P1_SLOT / 2), src + h * P1_SLOT, P1_SLOT / 2, bar_full + (s0 + h) * 8, (uint16_t)3);
                    }
                    __syncwarp();
                    if (h == 0 && rank == 0 && lane < 2)
                        asm volatile("st.async.shared::cluster.mbarrier::complete_tx::bytes.v4.u32 [%0], {%1, %2, %3, %3}, [%4];\n"
                                     ::"r"(rbase + P1_OFF_TILE + (i & 3) * 16), "r"((t - prev) * (2 * H_TILE)), "r"((int)(next < NT_RING)), "r"(draw),
                                       "r"(rbase + P1_OFF_BAR + s0 * 8) : "memory");
                }
                prev = t;
                t = next;
                next = draw;
                if (rank != 0) {
                    mbar_wait(bar_full + (s0 ^ 2) * 8, ((i - 1) >> 1) & 1);
                    asm volatile("ld.shared.u32 %0, [%1];\n" : "=r"(t) : "r"(sbase + P1_OFF_TILE + ((i - 1) & 3) * 16 + 8) : "memory");
                }
            }
#pragma unroll 1
            for (int j = 2 * i; j < 2 * i + 4; j++) mbar_wait(bar_empty + (j & 3) * 8, ((j + 2) >> 2 & 1) ^ 1);
        } else if (warp == 13) {
            int ph = 0;
            unsigned target = 0;
#pragma unroll 1
            for (int i = ln0 + LN_STEP; i < NT_RING; i += LN_STEP, ph ^= 1) {
                target += ph * (GRP_CTAS / 2);
                xsrc += (size_t)NUM_CTAS * P1_X;
                mbar_wait(bar_xempty, ph);
                if (elect_one()) {
                    mbar_expect_tx(bar_xfull, P1_X);
                    bulk_g2s(sbase + P1_OFF_X, xsrc, P1_X, bar_xfull);
                }
                __syncwarp();
                flag_wait<false>(&g_flag[ln0 + (ph ^ 1) * LN_STEP][1][0], target);
                mbar_wait(bar_done, ph);
                if (elect_one()) mbar_arrive(bar_xfull);
                __syncwarp();
            }
        } else if (warp == 15) {
            if (rank == 1 && lane < 2) mbar_arrive(bar_empty + (2 + lane) * 8);
            const uint32_t par = g_epoch & 1;
            asm volatile("st.shared.u32 [%0], %1;\n" ::"r"(sbase + P1_OFF_TILE - 4), "r"(par) : "memory");
            if (blockIdx.x == 18) g_par = par;
            if (blockIdx.x < 18) reinterpret_cast<float4*>(g_sums[par ^ 1])[blockIdx.x * 32 + lane] = make_float4(0.f, 0.f, 0.f, 0.f);
            bar_arrive(3, 160);
            {
                bar_sync(4, 288);
                mbar_wait(bar_raw + 8, 0);
                const uint32_t o = lane * 16384 + rank * 8192, peer = mapa(sbase, rank ^ 1);
                if (lane < 6)
                    asm volatile("cp.async.bulk.shared::cluster.shared::cta.mbarrier::complete_tx::bytes [%0], [%1], 8192, [%2];\n"
                                 ::"r"(peer + o), "r"(sbase + o), "r"(peer + P1_OFF_BAR + (lane >= 3 ? 8 : 0)) : "memory");
                __syncwarp();
            }
            if (rank == 0) {
                flag_wait<true>(&g_flag[40][1][0], GRP_CTAS / 2);
                const int col = (cig >> 1) * 64 + lane * 2;
                float bsum[2] = {0.f, 0.f}, asum[2] = {0.f, 0.f};
#pragma unroll 2
                for (int k = first * 140; k < min(first * 140 + 140, HID); k++) {
                    const uint32_t v = *reinterpret_cast<const uint32_t*>(w2 + k * C_DIM + col);
                    const float b = __bfloat162float(grn_b[k]), f = __uint_as_float(__ldcg(&g_ex[k]) << 23);
                    bsum[0] = fmaf(b, bf_lo(v), bsum[0]);
                    bsum[1] = fmaf(b, bf_hi(v), bsum[1]);
                    asum[0] = fmaf(f, fabsf(bf_lo(v)), asum[0]);
                    asum[1] = fmaf(f, fabsf(bf_hi(v)), asum[1]);
                }
                float* sums = g_sums[par] + HID + col;
#pragma unroll
                for (int j = 0; j < 2; j++) {
                    atomicAdd(sums + j, bsum[j]);
                    atomicAdd(sums + C_DIM + j, asum[j]);
                }
                __threadfence();
                __syncwarp();
                if (lane == 0) asm volatile("red.release.gpu.global.add.u32 [%0], 1;\n" ::"l"(&g_flag[LN_RING + 3][0][0]) : "memory");
            }
            int t = first, next = t + NGRP;
            if (rank == 1) {
                mbar_wait(bar_full, 0);
                mbar_wait(bar_full + 8, 0);
                if (lane < 2) mbar_arrive(bar_empty + lane * 8);
            }
#pragma unroll 1
            for (int i = 1; rank == 1 && t < NT_RING; i++) {
                const int s0 = (i & 1) * 16;
                mbar_wait(bar_full + s0, (i >> 1) & 1);
                mbar_wait(bar_full + s0 + 8, (i >> 1) & 1);
                if (lane == 0) asm volatile("red.relaxed.gpu.global.add.u32 [%0], 1;\n" ::"l"(&g_flag[t % LN_RING][1][0]) : "memory");
                t = next;
                asm volatile("ld.shared.u32 %0, [%1];\n" : "=r"(next) : "r"(sbase + P1_OFF_TILE + (i & 3) * 16 + 8) : "memory");
                if (lane < 2) mbar_arrive(bar_empty + s0 + lane * 8);
                TRACEW(i, 3);
            }
        } else if (warp == 14) {
            int ph = 0;
#pragma unroll 1
            for (int i = ln0; i < NT_RING; i += LN_STEP, ph ^= 1) {
                mbar_wait(bar_done, ph);
                TRACEW(i / LN_STEP, 0);
                asm volatile("fence.proxy.async.global;\n" ::: "memory");
                if (elect_one()) asm volatile("red.release.gpu.global.add.u32 [%0], 1;\n" ::"l"(&g_flag[ln0 + ph * LN_STEP][0][0]) : "memory");
                __syncwarp();
                TRACEW(i / LN_STEP, 1);
            }
        }
    } else if (warp >= 8) {
        reg_dec<88>();
        asm volatile("barrier.cluster.arrive.relaxed.aligned;\n" ::: "memory");
        {
            const int l8 = lane & 7, row = (warp - 8) * 4 + (lane >> 3), px = (blockIdx.x & 3) * 32 + row;
            uint32_t d[6][4] = {};
            const int n = (px & 64) + perm32(2 * row + ((px >> 5) & 1));
            uint8_t* const dst0 = ring + ln0 * LN_TILE + n * 128 + ((l8 ^ (n & 7)) << 4);
            const uint32_t src = sbase + P1_OFF_X + ((warp - 8) * 8 + (lane >> 3)) * (C_DIM * 2) + l8 * 16;
            int ph = 0;
            asm volatile("barrier.cluster.wait.aligned;\n" ::: "memory");
#pragma unroll 1
            for (int i = ln0; i < NT_RING; i += LN_STEP, ph ^= 1) {
                TRACE(2, i / LN_STEP, 0);
#pragma unroll 1
                for (int ps = i == ln0 ? -1 : 0; ps < 2; ps++) {
                    if (ps == 0) {
                        if (i == ln0) load_dw(d, sbase, lane);
                        mbar_wait(bar_xfull, ph);
                        TRACE(2, i / LN_STEP, 1);
                    }
                    uint32_t v[6][4];
#pragma unroll
                    for (int j = 0; j < 6; j++)
                        asm volatile("ld.shared.v4.u32 {%0,%1,%2,%3}, [%4];\n"
                                     : "=r"(v[j][0]), "=r"(v[j][1]), "=r"(v[j][2]), "=r"(v[j][3]) : "r"(src + (ps & 1) * (4 * C_DIM * 2) + j * 128) : "memory");
                    ln_row(v, d, zero, ps == 1 && lane == 0 ? bar_xempty : 0);
                    uint8_t* dst = dst0 + ph * (LN_STEP * LN_TILE) + ps * 4096;
#pragma unroll
                    for (int j = 0; j < 6; j++)
                        asm volatile("{\n.reg .pred p;\nsetp.ge.s32 p, %5, 0;\n@p st.global.v4.u32 [%0], {%1,%2,%3,%4};\n}\n"
                                     ::"l"(dst + j * 16384), "r"(v[j][0]), "r"(v[j][1]), "r"(v[j][2]), "r"(v[j][3]), "r"(ps) : "memory");
                    TRACE(2, i / LN_STEP, 3 + (ps & 1));
                }
                asm volatile("fence.proxy.async.global;\nfence.acq_rel.cta;\n" ::: "memory");
                __syncwarp();
                if (lane == 0) mbar_arrive(bar_done);
                TRACE(2, i / LN_STEP, 5);
                TRACE(2, i / LN_STEP, 2);
            }
        }
        const int gw = (warp - 8) * NUM_CTAS + blockIdx.x;
        bar_sync(3, 160);
        if (gw < 288) {
            const int np = (gw % 12) * 32 + lane, kb = gw / 12;
            const __nv_bfloat16* wc = w2 + (size_t)kb * 64 * C_DIM + perm32(np);
            const float* sums = g_sums[p1_parity(sbase)] + HID;
            flag_wait<true>(&g_flag[LN_RING + 3][0][0], NUM_CTAS / 2);
            float z = 0.f;
#pragma unroll
            for (int j = 0; j < C_DIM / 32; j++) z = fmaxf(z, __ldcg(sums + C_DIM + j * 32 + lane));
            const float sc = __uint_as_float((263u - acc_exp(__uint_as_float(__reduce_max_sync(0xffffffffu, __float_as_uint(z))))) << 23);
#pragma unroll 2
            for (int c = 0; c < 8; c++) {
                float f[8];
#pragma unroll
                for (int e = 0; e < 8; e++)
                    f[e] = __bfloat162float(wc[(c * 8 + e) * C_DIM]) * __uint_as_float(__ldcg(&g_ex[kb * 64 + c * 8 + e]) << 23) * sc;
                g_w2img[0][(((kb * 4 + (c >> 1)) * 48 + (np >> 3)) * 2 + (c & 1)) * 8 + (np & 7)] =
                    make_uint4(pack_f16(f[0], f[1]), pack_f16(f[2], f[3]), pack_f16(f[4], f[5]), pack_f16(f[6], f[7]));
            }
            asm volatile("fence.proxy.async.global;\n" ::: "memory");
            __threadfence();
            __syncwarp();
            if (lane == 0) asm volatile("red.release.gpu.global.add.u32 [%0], 1;\n" ::"l"(&g_img[0]) : "memory");
        }
    } else {
        if (tid == 0) {
            mbar_init(bar_raw, 1);
            mbar_init(bar_raw + 8, 8);
            asm volatile("fence.mbarrier_init.release.cluster;\n" ::: "memory");
            mbar_expect_tx(bar_raw, P1_SLOT);
            for (int i = 0; i < 6; i++)
                bulk_g2s(sbase + i * 16384 + (rank ^ 1) * 8192, x + (size_t)(first * 128 + rank * 64) * C_DIM + i * 4096, 8192, bar_raw);
        }
        if (tid == 32) {
            mbar_init(bar_raw + 16, 1);
            mbar_init(bar_xfull, 2);
            mbar_init(bar_xempty, 4);
            mbar_init(bar_done, 4);
            asm volatile("fence.mbarrier_init.release.cluster;\n" ::: "memory");
            mbar_expect_tx(bar_raw + 16, C_DIM * 2);
            bulk_g2s(sbase + P1_OFF_DW, dw, C_DIM * 2, bar_raw + 16);
            mbar_expect_tx(bar_xfull, P1_X);
            bulk_g2s(sbase + P1_OFF_X, xsrc, P1_X, bar_xfull);
            mbar_arrive(bar_xfull);
        }
        if (tid == 64) {
            asm volatile("st.shared.v4.u32 [%0], {0, 1, %1, %1};\n" ::"r"(sbase + P1_OFF_TILE), "r"(first + NGRP) : "memory");
            for (int i = 0; i < P1_NST; i++) {
                mbar_init(bar_full + i * 8, 1);
                mbar_init(bar_empty + i * 8, 16 + rank);
                if (i < 2) mbar_expect_tx(bar_full + i * 8, P1_SLOT / 2);
            }
            asm volatile("fence.mbarrier_init.release.cluster;\n" ::: "memory");
            if (blockIdx.x < 64) (&g_half[0][0])[blockIdx.x] = 0;
            else if (blockIdx.x == 64) g_prog = 0;
            else if (blockIdx.x < 67) g_img[blockIdx.x - 65] = 0;
        }
        if (tid == 96) {
            for (int i = 0; i < 2; i++) mbar_init(bar_w + i * 8, 1);
            asm volatile("fence.mbarrier_init.release.cluster;\n" ::: "memory");
        }
        __syncwarp();
        asm volatile("barrier.cluster.arrive.relaxed.aligned;\n" ::: "memory");
        if (tid == 96)
            for (int i = 0; i < 2; i++) {
                mbar_expect_tx(bar_w + i * 8, P1_SLOT);
                tma2(sbase + (2 + i) * P1_SLOT, &wmap, cig * 128 + i * 64, 0, bar_w + i * 8);
                tma2(sbase + (2 + i) * P1_SLOT + P1_SLOT / 2, &wmap, cig * 128 + i * 64, 192, bar_w + i * 8);
            }
        __syncwarp();
        reg_inc<P1_REGS>();
        TRACEW(110 + warp, 1);
        const int wg = warp >> 2, w = warp & 3;
        uint32_t a[24][4], ex[2], gen;
        const uint32_t wsrc = sbase + (2 + wg) * P1_SLOT + ((lane >> 4) * 8 + (lane & 7)) * 128 + (((2 * w + ((lane >> 3) & 1)) ^ (lane & 7)) << 4);
        gdc_launch();
        asm volatile("barrier.cluster.wait.aligned;\n" ::: "memory");
#pragma unroll 1
        for (int it = P1_WARM ? 1 - wg : 1; it < 2; it++) {
            if (it) {
                const int n = warp * 8 + (lane >> 3), px = (n & 1) * 32 + (n >> 5) * 4 + ((n >> 1) & 1) * 8 + ((n >> 3) & 3);
                uint32_t d[6][4] = {};
#pragma unroll 1
                for (int ps = P1_WARM ? wg - 1 : -1; ps < 2; ps++) {
                    if (ps == 0) {
                        load_dw(d, sbase, lane);
                        mbar_wait(bar_raw, 0);
                    }
                    TRACEW(110 + warp, 2 + (ps == 0));
                    uint32_t v[6][4];
#pragma unroll
                    for (int j = 0; j < 6; j++) {
                        const uint32_t o = (px + (ps & 1) * 16) * (C_DIM * 2) + j * 128;
                        asm volatile("ld.shared.v4.u32 {%0,%1,%2,%3}, [%4];\n" : "=r"(v[j][0]), "=r"(v[j][1]), "=r"(v[j][2]), "=r"(v[j][3])
                                     : "r"(sbase + (rank ^ 1) * 8192 + (lane & 7) * 16 + o + (o & ~8191u)) : "memory");
                    }
                    ln_row(v, d, zero, 0);
                    const uint32_t p = sbase + (rank * 64 + n + (ps & 1) * 4) * 128 + (((lane ^ n ^ (ps & 1) * 4) & 7) << 4);
#pragma unroll
                    for (int j = 0; j < 6; j++)
                        asm volatile("st.shared.v4.u32 [%4], {%0,%1,%2,%3};\n"
                                     ::"r"(v[j][0]), "r"(v[j][1]), "r"(v[j][2]), "r"(v[j][3]), "r"(p + j * 16384) : "memory");
                }
                asm volatile("fence.proxy.async.shared::cta;\n" ::: "memory");
                __syncwarp();
                if (lane == 0) mbar_arrive_cluster(mapa(bar_raw + 8, rank ^ 1));
                bar_arrive(4, 288);
                if (wg == 1) bar_arrive(1, 256);
                TRACEW(110 + warp, 4);
                mbar_wait(bar_w + wg * 8, 0);
                TRACEW(110 + warp, 5);
            }
#pragma unroll
            for (int k = 0; k < 24; k++) ldsm4t(a[k], wsrc + k * 2048);
#pragma unroll
            for (int r = 0; r < 2; r++) {
                float t = 0.f;
#pragma unroll
                for (int j = 0; j < 6; j++) {
                    uint32_t c = bf2_mul(a[4 * j][r], a[4 * j][r]);
#pragma unroll
                    for (int k = 1; k < 8; k++) c = bf2_fma(a[4 * j + k / 2][r + (k & 1) * 2], a[4 * j + k / 2][r + (k & 1) * 2], c);
                    t += bf_lo(c) + bf_hi(c);
                }
                t += __shfl_xor_sync(0xffffffffu, t, 1);
                t += __shfl_xor_sync(0xffffffffu, t, 2);
                ex[r] = min(max(__float_as_uint(13.9f * __fsqrt_rn(t)) >> 23, 72u), 198u);
            }
            asm volatile("{\n.reg .pred p;\nsetp.gt.u32 p, %1, 7;\nbar.red.or.pred p, %2, 128, p;\nselp.u32 %0, 1, 0, p;\n}\n"
                         : "=r"(gen) : "r"(max(ex[0] - 125u, ex[1] - 125u)), "r"(5 + wg) : "memory");
            gen = __shfl_sync(0xffffffffu, gen, 0);
            if (gen) {
#pragma unroll
                for (int k = 0; k < 24; k++)
#pragma unroll
                    for (int j = 0; j < 4; j++) a[k][j] = bf2_mul(a[k][j], (268u - ex[j & 1]) * 0x00800080u);
            }
#pragma unroll
            for (int k = 0; k < 24; k++)
#pragma unroll
                for (int j = 0; j < 4; j++) {
                    a[k][j] = bf2_as_h2(bf2_mul(a[k][j], 0x07800780u));
                    asm volatile("" : "+r"(a[k][j]));
                }
            TRACEW(110 + warp, 6);
        }
        if ((lane & 3) < 2) g_ex[cig * 128 + wg * 64 + w * 16 + (lane & 1) * 8 + (lane >> 2)] = lane & 1 ? ex[1] : ex[0];
        if (lane < 4) mbar_arrive_cluster(mapa(bar_empty, lane & 1) + (2 + (lane >> 1)) * 8);
        TRACEW(110 + warp, 7);
        const uint32_t ex2 = ex[0] | ex[1] << 16;
        p1_consumer(a, gen ? 0x7f007f00u - (ex2 << 7) : (0x008e008eu - ex2) << 10, gen, sbase, wg, w, lane, zero);
        TSTAMP(0, 30);
    }
}

#define P2_NB_ 5
#define P2_NA_ 5
#define P2_DELTA_ 7
#define P2_EXTRA 0
#define P2_HSLEEP 64
#define P2_PSLEEP 100
#define P2_T0 5
#define P2_TS 11
constexpr int P2_B = 24576, P2_NB = P2_NB_;
constexpr int P2_A = 3072, P2_NA = P2_NA_;
constexpr int P2_XROW = C_DIM * 2;
constexpr int P2_OFF_A = P2_B * P2_NB;
constexpr int P2_OFF_X = P2_OFF_A + 3 * P2_NA * P2_A;
constexpr int P2_XHALF = 32 * P2_XROW + 64;
constexpr int P2_OFF_BIAS = P2_OFF_X + 64 * P2_XROW + 64;
constexpr int P2_OFF_GRN = P2_OFF_BIAS + C_DIM * 4;
constexpr int P2_OFF_BAR = P2_OFF_GRN + HID * 2;
constexpr int P2_SMEM = P2_OFF_BAR + (2 * P2_NB + 6 * P2_NA + 3) * 8;
#define P2_LAG_ 17
constexpr int P2_LAG = P2_LAG_;
constexpr int P2_NCL = NUM_CTAS / 2, P2_ITEMS = NT128 / P2_NCL, P2_SHARED = NT128 - P2_ITEMS * P2_NCL;
constexpr int P2_POS = P2_LAG * (P2_ITEMS - 1) + 48;
__device__ __forceinline__ int p2_start(int n) { return n < 0 ? 0 : n == P2_ITEMS ? P2_POS - 24 : P2_LAG * n; }
constexpr int P2_FOLD = 17;
constexpr int P2_XC = 8 * P2_XROW;
constexpr int P2_DELTA = P2_DELTA_;
__device__ __forceinline__ int p2_tile(int cl, int n) {
    return n == 0 ? NT128 - 1 - cl : n < 0 || n == P2_ITEMS ? NT128 - 1 - P2_NCL - (cl >> 1) : cl + P2_NCL * (n - 1);
}

constexpr int P2_EG = 2;
__device__ __forceinline__ void p2_epilogue(const uint32_t (&acc0)[48], const uint32_t (&acc1)[48], uint32_t sx, uint32_t sb, float up, int zero) {
    uint32_t v[2][P2_EG][4];
    float b[2][8];
    auto load = [&](int c, uint32_t a) {
#pragma unroll
        for (int j = 0; j < 2; j++)
            asm volatile("ld.shared.v4.f32 {%0,%1,%2,%3}, [%4];\n" : "=f"(b[c & 1][4 * j]), "=f"(b[c & 1][4 * j + 1]), "=f"(b[c & 1][4 * j + 2]), "=f"(b[c & 1][4 * j + 3])
                         : "r"(sb + c * 128 + j * 16) : "memory");
#pragma unroll
        for (int j = 0; j < P2_EG; j++) {
            const int u = c * P2_EG + j;
            asm volatile("ld.shared.v4.u32 {%0,%1,%2,%3}, [%4];\n" : "=r"(v[c & 1][j][0]), "=r"(v[c & 1][j][1]), "=r"(v[c & 1][j][2]), "=r"(v[c & 1][j][3])
                         : "r"(a + (u >> 1) * 64 + (u & 1) * 4 * P2_XROW) : "memory");
        }
    };
    load(0, sx);
#pragma unroll
    for (int c = 0; c < 24 / P2_EG; c++) {
        if (c + 1 < 24 / P2_EG) load(c + 1, sx + (v[c & 1][P2_EG - 1][0] & zero));
#pragma unroll
        for (int j = 0; j < P2_EG; j++) {
            const int u = c * P2_EG + j, i = 8 * ((u >> 1) % 6) + (u & 1);
            const uint32_t (&acc)[48] = u < 12 ? acc0 : acc1;
            uint32_t (&w)[4] = v[c & 1][j];
#pragma unroll
            for (int e = 0; e < 4; e++)
                w[e] = bf2_add(pack_bf16(fmaf(h_lo(acc[i + 2 * e]), up, b[c & 1][2 * e]), fmaf(h_hi(acc[i + 2 * e]), up, b[c & 1][2 * e + 1])), w[e]);
            asm volatile("st.shared.v4.u32 [%4], {%0,%1,%2,%3};\n" ::"r"(w[0]), "r"(w[1]), "r"(w[2]), "r"(w[3]),
                         "r"(sx + (u >> 1) * 64 + (u & 1) * 4 * P2_XROW) : "memory");
        }
    }
}

__device__ __forceinline__ void p2_unpack(uint4& u, uint32_t o1, uint32_t o2, uint32_t o3) {
    u.z = o1 & 0xbff8bff8u;
    u.y = o2 & 0xbff8bff8u;
    u.w = o3 & 0xbff8bff8u;
    u.x = (__byte_perm(o1, 0, 0x2301) & 0x07400740u) | ((__byte_perm(o2, o3, 0x6240) << 3) & 0x38383838u) | ((__byte_perm(o2, o3, 0x3715) << 1) & 0x80808080u);
}
__device__ __forceinline__ uint32_t h2_mul(uint32_t a, uint32_t b) {
    uint32_t r;
    asm("mul.rn.f16x2 %0, %1, %2;\n" : "=r"(r) : "r"(a), "r"(b));
    return r;
}
__device__ __forceinline__ void p2_epilogue_add(const uint32_t (&acc)[48], uint8_t* o, float f, int zero) {
#pragma unroll
    for (int t = 0; t < 12; t++) {
        uint32_t v[4];
#pragma unroll
        for (int e = 0; e < 4; e++) {
            v[e] = acc[8 * (t >> 1) + (t & 1) + 2 * e];
            asm volatile("" : "+r"(v[e]));
            v[e] = pack_bf16(h_lo(v[e]) * f, h_hi(v[e]) * f);
        }
        asm volatile("red.global.add.noftz.v4.bf16x2 [%0], {%1,%2,%3,%4};\n" ::"l"(o + (t >> 1) * 64 + (t & 1) * 4 * P2_XROW),
                     "r"(v[0]), "r"(v[1]), "r"(v[2]), "r"(v[3]) : "memory");
        if (t % 3 == 2) sched_break(zero);
    }
}

__global__ void __cluster_dims__(2, 1, 1) __launch_bounds__(512, 1)
pass2_kernel(const __nv_bfloat16* __restrict__ x, const __nv_bfloat16* __restrict__ grn_g, __nv_bfloat16* __restrict__ out, int zero) {
    extern __shared__ __align__(1024) uint8_t smem[];
    const uint32_t sbase = smem_u32(smem);
    const uint32_t bar_bfull = sbase + P2_OFF_BAR, bar_bempty = bar_bfull + P2_NB * 8;
    const uint32_t bar_afull = bar_bempty + P2_NB * 8, bar_aempty = bar_afull + 3 * P2_NA * 8;
    const uint32_t bar_xfull = bar_aempty + 3 * P2_NA * 8, bar_oready = bar_xfull + 8, s_pos = bar_xfull + 16;
    int tid;
    asm volatile("mov.u32 %0, %%tid.x;\n" : "=r"(tid));
    const int warp = __shfl_sync(0xffffffffu, tid >> 5, 0), lane = tid & 31;
    const uint32_t rank = cluster_rank();
    const int cl = blockIdx.x >> 1, pair = cl >> 1;
    const int k0 = (4 * pair + (cl & 1) * (48 - P2_POS % 48)) % 48;
    const int head = pair < P2_SHARED && !(cl & 1), tail = pair < P2_SHARED && (cl & 1);

    uint32_t par, gg[4];
    float pre[4];
    if (warp < 12) {
        asm volatile("ld.global.cg.u32 %0, [%1];\n" : "=r"(par) : "l"(&g_par) : "memory");
#pragma unroll
        for (int i = 0; i < 4; i++) {
            asm volatile("ld.global.cg.f32 %0, [%1];\n" : "=f"(pre[i]) : "l"(&g_sums[i & 1][HID + (i >> 1) * C_DIM + tid]) : "memory");
            asm volatile("ld.global.nc.u16 %0, [%1];\n" : "=r"(gg[i]) : "l"(grn_g + tid + 384 * i) : "memory");
        }
    }
    TSTAMP(1, 0);
    if (tid == 384) {
        for (int i = 0; i < P2_NB; i++) {
            mbar_init(bar_bfull + i * 8, 1);
            mbar_init(bar_bempty + i * 8, 24);
        }
        for (int i = 0; i < 3 * P2_NA; i++) {
            mbar_init(bar_afull + i * 8, 1);
            mbar_init(bar_aempty + i * 8, 4);
        }
        mbar_init(bar_xfull, 2);
        mbar_init(bar_oready, 4);
        asm volatile("st.shared.u32 [%0], 0;\n" ::"r"(s_pos) : "memory");
        asm volatile("fence.mbarrier_init.release.cluster;\n" ::: "memory");
    }
    __syncthreads();
    cluster_sync_relaxed();

    if (warp >= 12) {
        reg_dec<32>();
        if (warp == 12) {
            const uint8_t* wsrc = reinterpret_cast<const uint8_t*>(g_w2img) + rank * (P2_B / 2);
            int st = 0, ph = 1, kb = k0, m = 0, r = 0;
            const int busy = head ? 0 : tail ? P2_POS - 24 : P2_POS;
#pragma unroll 1
            for (int p = 0; p < P2_POS; p++) {
                if (p == 0 || p == P2_FOLD) {
                    flag_wait<true>(&g_img[p != 0], p ? 96 * 4 : 288);
                    asm volatile("fence.proxy.async.global;\n" ::: "memory");
                    if (p) wsrc += sizeof(g_w2img[0]);
                }
                mbar_wait(bar_bempty + st * 8, ph);
                TR2P(p, 0);
                if (elect_one()) {
                    mbar_expect_tx(bar_bfull + st * 8, P2_B);
                    bulk_g2s_mc(sbase + st * P2_B + rank * (P2_B / 2), wsrc + kb * P2_B, P2_B / 2, bar_bfull + st * 8, (uint16_t)3);
                    asm volatile("st.volatile.shared.u32 [%0], %1;\n" ::"r"(s_pos), "r"(p) : "memory");
                    const int idle = 2 - min(m, P2_ITEMS - 1) + max(m - 2 + (r >= 48 - 2 * P2_LAG), 0) - ((unsigned)(p - busy) < 24);
                    if (idle) asm volatile("mbarrier.arrive.shared::cta.b64 _, [%0], %1;\n" ::"r"(bar_bempty + st * 8), "r"(idle * 8) : "memory");
                    if (rank == 0) asm volatile("red.relaxed.gpu.global.add.u32 [%0], 1;\n" ::"l"(&g_prog) : "memory");
                }
                __syncwarp();
                if (++st == P2_NB) { st = 0; ph ^= 1; }
                if (++kb == 48) kb = 0;
                if (++r == P2_LAG) { r = 0; m++; }
            }
            mbar_wait(bar_bempty + st * 8, ph);
            if (lane == 0) mbar_arrive(bar_bfull + st * 8);
#pragma unroll 1
            for (int p = 1; p < P2_NB; p++) {
                if (++st == P2_NB) { st = 0; ph ^= 1; }
                mbar_wait(bar_bempty + st * 8, ph);
            }
        } else if (warp == 13) {
            const uint8_t* src[3];
            int n[3], left[3], wrap[3];
            uint32_t st[3];
            auto item = [&](int w) {
                const int u = (k0 + p2_start(n[w])) % 48;
                left[w] = n[w] < 0 || n[w] == P2_ITEMS ? 24 : 48;
                wrap[w] = left[w] - (48 - u);
                src[w] = reinterpret_cast<const uint8_t*>(g_h) + (size_t)p2_tile(cl, n[w]) * (2 * H_TILE) + rank * H_HALF + u * H_STEP;
            };
#pragma unroll
            for (int w = 0; w < 3; w++) {
                n[w] = w == 2 && head ? -1 : w;
                st[w] = 0x80000000u;
                item(w);
            }
            gdc_wait();
#pragma unroll 1
            for (int done = 0; done < 3;) {
                bool idle = true;
#pragma unroll
                for (int w = 0; w < 3; w++) {
                    const uint32_t o = (st[w] & 0xff) + w * P2_NA * 8;
                    if (left[w] >= 0 && mbar_test(bar_aempty + o, st[w] >> 31)) {
                        idle = false;
                        if (left[w] == 0) {
                            if (lane == 0) mbar_arrive(bar_afull + o);
                            left[w] = -1;
                            done++;
                        } else {
                            if (elect_one()) {
                                mbar_expect_tx(bar_afull + o, P2_A);
                                bulk_g2s(sbase + P2_OFF_A + o * (P2_A / 8), src[w], P2_A, bar_afull + o);
                            }
                            __syncwarp();
                            src[w] += H_STEP;
                            st[w] += 8;
                            if ((st[w] & 0xff) == P2_NA * 8) st[w] ^= 0x80000000u | (P2_NA * 8);
                            if (--left[w] == wrap[w]) src[w] -= 48 * H_STEP;
                            if (left[w] == 0 && (n[w] += 3) < P2_ITEMS + tail) item(w);
                        }
                    }
                }
                if (idle) __nanosleep(P2_HSLEEP);
                SAFE_BREAK
            }
        } else if (warp == 14) {
            const uint32_t sx = sbase + P2_OFF_X;
            size_t o = 0;
            auto pace = [&](int target) {
                int v;
                while (true) {
                    asm volatile("ld.volatile.shared.u32 %0, [%1];\n" : "=r"(v) : "r"(s_pos) : "memory");
                    if (v * 16 >= target) break;
                    __nanosleep(P2_PSLEEP);
                    SAFE_BREAK
                }
            };
#pragma unroll 1
            for (int n = -head; n <= P2_ITEMS; n++) {
                const size_t on = (size_t)(2 * p2_tile(cl, n) + rank) * (64 * C_DIM * 2);
                const bool st = n + head > 0, ld = n < P2_ITEMS;
                if (st) mbar_wait(bar_oready, (n - 1 + head) & 1);
                TR2P(n + 1, 1);
                if (lane == 0) {
                    if (n == 1 && head) {
                        asm volatile("cp.async.bulk.wait_group 0;\nfence.proxy.async.global;\n" ::: "memory");
                        asm volatile("st.release.gpu.global.u32 [%0], 1;\n" ::"l"(&g_half[pair][rank]) : "memory");
                    }
                    if (ld) mbar_expect_tx(bar_xfull, 64 * C_DIM * 2);
                    int t = st && n < P2_ITEMS - 1 ? (P2_LAG * (n - 1) + 48 + P2_T0 - 1) * 16 : -1024;
#pragma unroll 1
                    for (int c = 0; st && c < 64 * P2_XROW; c += P2_XC) {
                        pace(t += P2_TS);
                        bulk_s2g(reinterpret_cast<uint8_t*>(out) + o + c, sx + c + (c >= 32 * P2_XROW ? 64 : 0), P2_XC);
                    }
                    asm volatile("cp.async.bulk.commit_group;\ncp.async.bulk.wait_group.read 0;\n" ::: "memory");
#pragma unroll 1
                    for (int c = 0; ld && c < 64 * P2_XROW; c += P2_XC) {
                        pace(t += P2_TS);
                        bulk_g2s(sx + c + (c >= 32 * P2_XROW ? 64 : 0), reinterpret_cast<const uint8_t*>(x) + on + c, P2_XC, bar_xfull);
                    }
                    TR2P(n + 1, 2);
                    if (rank == 0 && n > 0 && n < P2_ITEMS - 2)
                        flag_wait<false>(&g_prog, P2_NCL * (P2_LAG * n + 48 + P2_EXTRA) + (tail ? P2_SHARED - P2_NCL : P2_SHARED) * P2_DELTA);
                    if (ld) mbar_arrive(bar_xfull);
                    TR2P(n + 1, 3);
                }
                __syncwarp();
                o = on;
            }
            asm volatile("cp.async.bulk.wait_group 0;\n" ::: "memory");
            TR2P(30, 1);
        }
    } else {
        reg_inc<160>();
        const int wg = warp >> 2, w = warp & 3, g = lane >> 2, q = lane & 3;
        const uint32_t sx = sbase + P2_OFF_X + (g & 1) * P2_XHALF + (w * 8 + (g >> 1)) * P2_XROW + q * 16;
        const uint32_t af = bar_afull + wg * P2_NA * 8, ae = bar_aempty + wg * P2_NA * 8;
        const uint32_t s_a = sbase + P2_OFF_A - bar_afull * (P2_A / 8) + (lane >> 3) * 512 + (lane & 7) * 64 +
                             ((w ^ ((lane & 7) >> 1)) << 4);
        uint32_t acc0[48], acc1[48];
        float up;
        uint4 a0[2], a1[2];
        int st = 0, ph = 0;

        {
            float4* s_red = reinterpret_cast<float4*>(smem + P2_OFF_BIAS);
            const float* sums = g_sums[par];
            float gx[4], part = 0.f, mx = 0.f;
            TSTAMP(1, 27);
            gdc_wait();
            TSTAMP(1, 1);
#pragma unroll
            for (int i = 0; i < 4; i++) gx[i] = __ldcg(sums + tid + 384 * i);
            if (blockIdx.x == 120 && tid < (LN_RING + 4) * 2) (&g_flag[0][0][0])[tid * 8] = 0;
            if (blockIdx.x == 121 && tid == 0) atomicAdd(&g_epoch, 1u);
            float z = __uint_as_float(__reduce_max_sync(0xffffffffu, __float_as_uint(pre[2] + pre[3])));
#pragma unroll
            for (int i = 0; i < 4; i++) {
                asm("sqrt.approx.f32 %0, %1;\n" : "=f"(gx[i]) : "f"(fmaf(gx[i], HSCALE * HSCALE, 1e-6f)));
                part += gx[i];
                gx[i] *= bf_lo(gg[i]);
                mx = fmaxf(mx, fabsf(gx[i]));
            }
#pragma unroll
            for (int o = 16; o > 0; o >>= 1) part += __shfl_xor_sync(0xffffffffu, part, o);
            mx = __uint_as_float(__reduce_max_sync(0xffffffffu, __float_as_uint(mx)));
            TSTAMP(1, 26);
            if (lane == 0) s_red[warp] = make_float4(part, mx, z, 0.f);
            bar_sync(1, 384);
            float tot = 0.f;
            {
                const float4 t = s_red[min(lane & 15, 11)];
                tot = (lane & 15) < 12 ? t.x : 0.f;
#pragma unroll
                for (int o = 8; o > 0; o >>= 1) tot += __shfl_xor_sync(0xffffffffu, tot, o);
                mx = __uint_as_float(__reduce_max_sync(0xffffffffu, __float_as_uint(t.y)));
                z = __uint_as_float(__reduce_max_sync(0xffffffffu, __float_as_uint(t.z)));
            }
            const float inv = __fdividef(1.0f, fmaf(tot, 1.0f / HID, 1e-6f));
            const uint32_t j = max(__float_as_uint(fmaf(mx, inv, 1.0f) * 1.01f) >> 23, 130u) - 130u;
            const float dn = __uint_as_float((127u - j) << 23);
#pragma unroll
            for (int i = 0; i < 4; i++)
                *reinterpret_cast<uint16_t*>(smem + P2_OFF_GRN + (tid + 384 * i) * 2) = pack_f16(fmaf(gx[i], inv, 1.0f) * dn, 0.f);
            up = (HSCALE * 1.00235f) * __uint_as_float(min(acc_exp(z) - 9u + j, 253u) << 23);
            TSTAMP(1, 25);
            bar_sync(1, 384);
            reinterpret_cast<float*>(smem + P2_OFF_BIAS)[tid] = pre[0] + pre[1];
            if (wg == 1 && blockIdx.x < 96) {
                const uint4* src = g_w2img[0] + blockIdx.x * 768 + tid - 128;
                const uint4 fk = *reinterpret_cast<const uint4*>(smem + P2_OFF_GRN + blockIdx.x * 32 + (tid & 8) * 2);
                uint4 v[6];
#pragma unroll
                for (int i = 0; i < 6; i++) v[i] = __ldcg(src + i * 128);
                auto fold = [&](uint32_t b, uint32_t f) { return (h2_mul(b, f) + 0x00040004u) & 0xfff8fff8u; };
#pragma unroll
                for (int i = 0; i < 6; i++)
                    g_w2img[1][blockIdx.x * 768 + tid - 128 + i * 128] = make_uint4(fold(v[i].x, fk.x), fold(v[i].y, fk.y), fold(v[i].z, fk.z), fold(v[i].w, fk.w));
                asm volatile("fence.proxy.async.global;\n" ::: "memory");
                __threadfence();
                __syncwarp();
                if (lane == 0) asm volatile("red.release.gpu.global.add.u32 [%0], 1;\n" ::"l"(&g_img[1]) : "memory");
            }
        }
        TSTAMP(1, 28);
        int kt = k0, pos;
        const int who = __shfl_sync(0xffffffffu, lane == 2 ? 0 : lane < 2 ? 1 : 2, lane);
        const uint32_t rel0 = who ? mapa(bar_bempty, lane & 1) : mapa(ae, rank), rel1 = rel0 + (who ? P2_NB : P2_NA) * 8;
        uint32_t rel = rel1 - 8;
        auto next_rel = [&](bool go) {
            if (go) rel += 8;
            if (rel == rel1) rel = rel0;
        };
        auto release_b = [&]() {
            next_rel(who == 1);
            if (who == 1) mbar_arrive_cluster(rel);
        };
        auto seek = [&](int p) {
            pos = p;
            st = p % P2_NB;
            ph = p / P2_NB & 1;
            if (who == 1) rel = (st ? rel0 + st * 8 : rel1) - 8;
            int v;
            while (true) {
                asm volatile("ld.volatile.shared.u32 %0, [%1];\n" : "=r"(v) : "r"(s_pos) : "memory");
                if (v >= p) break;
                __nanosleep(200);
                SAFE_BREAK
            }
        };
        auto publish = [&]() {
            asm volatile("fence.proxy.async.shared::cta;\n" ::: "memory");
            __syncwarp();
            if (who == 0) mbar_arrive(bar_oready);
        };
        bool ok_a;
        uint32_t abar = af, pa = 0;
        auto fetch = [&](uint4 (&a)[2], bool early) {
            const uint32_t src = s_a + abar * (P2_A / 8);
            abar += 8;
            if (abar == af + P2_NA * 8) { abar = af; pa ^= 0x80000000u; }
            const bool ok_b = mbar_test(bar_bfull + st * 8, ph);
            ok_a = mbar_test(abar, pa >> 31);
            uint32_t o[6];
            asm volatile("ldmatrix.sync.aligned.m8n8.x4.trans.shared.b16 {%0,%1,%2,%3}, [%4];\n"
                         : "=r"(o[0]), "=r"(o[1]), "=r"(o[2]), "=r"(o[3]) : "r"(src) : "memory");
            asm volatile("ldmatrix.sync.aligned.m8n8.x2.trans.shared.b16 {%0,%1}, [%2];\n"
                         : "=r"(o[4]), "=r"(o[5]) : "r"(src + 2048) : "memory");
            p2_unpack(a[0], o[0], o[1], o[2]);
            p2_unpack(a[1], o[3], o[4], o[5]);
            if (early) {
                const uint32_t* t = reinterpret_cast<const uint32_t*>(smem + P2_OFF_GRN) + kt * 16 + q;
#pragma unroll
                for (int i = 0; i < 2; i++)
                    a[i] = make_uint4(h2_mul(a[i].x, t[8 * i]), h2_mul(a[i].y, t[8 * i]), h2_mul(a[i].z, t[8 * i + 4]), h2_mul(a[i].w, t[8 * i + 4]));
                if (++kt == 48) kt = 0;
            }
            if (!ok_b) mbar_wait(bar_bfull + st * 8, ph);
        };
        auto step = [&](const uint4 (&a)[2], uint4 (&an)[2], int thr, bool early) {
            TR2(0);
            const uint64_t db = make_desc(sbase + st * P2_B, 128, 256);
            wg_fence();
            mma_rs_n192(acc0, a[0], db, thr - 1);
            mma_rs_n192(acc1, a[0], db + 384, thr - 1);
            mma_rs_n192(acc0, a[1], db + 768, 1);
            mma_rs_n192(acc1, a[1], db + 768 + 384, 1);
            wg_commit();
            next_rel(who < thr);
            if (++st == P2_NB) { st = 0; ph ^= 1; }
            wg_wait<1>();
            if (!ok_a) {
                if (who < thr) mbar_arrive_cluster(rel);
                thr = 0;
                mbar_wait(abar, pa >> 31);
            }
            if (who < thr) mbar_arrive_cluster(rel);
            fetch(an, early);
            pos++;
        };
        int n = wg == 2 && head ? -1 : wg;
        mbar_wait(af, 0);
        seek(p2_start(n));
        fetch(a0, n <= 0);
#pragma unroll 1
        for (;; n += 3) {
            TSTAMP(1, 2 + n);
            const int p0 = n < 0 || n == P2_ITEMS ? 12 : 0, pe = n <= 0 ? p0 + P2_FOLD / 2 : 0;
            const bool more = n + 3 < P2_ITEMS + tail;
#pragma unroll 1
            for (int p = p0; p < 24; p++) {
                step(a0, a1, p == p0 ? 1 : 2, p < pe);
                step(a1, a0, 2, p < pe);
            }
            if (n == P2_ITEMS) {
                flag_wait<true>(&g_half[pair][rank], 1);
                TR2(1);
                wg_wait<0>();
                TR2(2);
                release_b();
                uint8_t* o = reinterpret_cast<uint8_t*>(out) + (size_t)((2 * p2_tile(cl, -1) + rank) * 64 + (g & 1) * 32 + w * 8 + (g >> 1)) * P2_XROW + q * 16;
                p2_epilogue_add(acc0, o, up, zero);
                p2_epilogue_add(acc1, o + 384, up, zero);
                TR2(3);
                break;
            }
            mbar_wait(bar_xfull, (n + head) & 1);
            TR2(1);
            wg_wait<0>();
            TR2(2);
            release_b();
            __syncwarp();
            p2_epilogue(acc0, acc1, sx, sbase + P2_OFF_BIAS + q * 32, up, zero);
            TR2(3);
            publish();
            if (!more) break;
            seek(p2_start(n + 3));
            mbar_wait(bar_bfull + st * 8, ph);
        }
        TSTAMP(1, 30);
    }
}

}

extern "C" void kernel_launch(void* const* d_in, const int* in_sizes, int n_in, void* d_out, int out_size) {
    const __nv_bfloat16* x = (const __nv_bfloat16*)d_in[0];
    const __nv_bfloat16* dw = (const __nv_bfloat16*)d_in[1];
    const __nv_bfloat16* w1 = (const __nv_bfloat16*)d_in[2];
    const __nv_bfloat16* w2 = (const __nv_bfloat16*)d_in[3];
    const __nv_bfloat16* grn_g = (const __nv_bfloat16*)d_in[4];
    const __nv_bfloat16* grn_b = (const __nv_bfloat16*)d_in[5];
    __nv_bfloat16* out = (__nv_bfloat16*)d_out;

    cudaFuncSetAttribute(pass1_kernel, cudaFuncAttributeMaxDynamicSharedMemorySize, P1_SMEM);
    cudaFuncSetAttribute(pass2_kernel, cudaFuncAttributeMaxDynamicSharedMemorySize, P2_SMEM);

    typedef CUresult (*EncodeFn)(CUtensorMap*, CUtensorMapDataType, cuuint32_t, void*, const cuuint64_t*, const cuuint64_t*,
                                 const cuuint32_t*, const cuuint32_t*, CUtensorMapInterleave, CUtensorMapSwizzle,
                                 CUtensorMapL2promotion, CUtensorMapFloatOOBfill);
    static EncodeFn encode = nullptr;
    if (!encode) {
        cudaDriverEntryPointQueryResult qres;
        cudaGetDriverEntryPoint("cuTensorMapEncodeTiled", (void**)&encode, cudaEnableDefault, &qres);
    }
    CUtensorMap wmap;
    const cuuint64_t gdim[2] = {HID, C_DIM};
    const cuuint64_t gstr[1] = {HID * 2};
    const cuuint32_t box[2] = {64, 192}, estr[2] = {1, 1};
    CUresult er = encode(&wmap, CU_TENSOR_MAP_DATA_TYPE_BFLOAT16, 2, (void*)w1, gdim, gstr, box, estr, CU_TENSOR_MAP_INTERLEAVE_NONE,
           CU_TENSOR_MAP_SWIZZLE_128B, CU_TENSOR_MAP_L2_PROMOTION_L2_128B, CU_TENSOR_MAP_FLOAT_OOB_FILL_NONE);
    if (er != CUDA_SUCCESS) printf("tensor map encode failed %d\n", (int)er);

    pass1_kernel<<<NUM_CTAS, 512, P1_SMEM>>>(wmap, x, dw, w2, grn_b, 0);

    cudaLaunchAttribute attr[1];
    attr[0].id = cudaLaunchAttributeProgrammaticStreamSerialization;
    attr[0].val.programmaticStreamSerializationAllowed = 1;
    cudaLaunchConfig_t cfg = {};
    cfg.gridDim = dim3(NUM_CTAS);
    cfg.stream = 0;
    cfg.attrs = attr;
    cfg.numAttrs = 1;
    cfg.blockDim = dim3(512);
    cfg.dynamicSmemBytes = P2_SMEM;
    cudaLaunchKernelEx(&cfg, pass2_kernel, x, grn_g, out, 0);
}
```

```cpp
#include <cuda.h>
#include <cuda_runtime.h>
#include <cuda_bf16.h>
#include <stdint.h>
#include <stdio.h>

namespace {

constexpr int M_TOTAL = 384 * 384;
constexpr int C_DIM   = 384;
constexpr int HID     = 1536;
constexpr int NT128   = M_TOTAL / 128;
constexpr int NUM_CTAS = 132;

constexpr int NGRP = 15, NFIRST = NGRP + 1;
#define LN_DEPTH 2
constexpr int LN_STEP = NUM_CTAS / 4, LN_RING = LN_DEPTH * LN_STEP;
constexpr int NT_RING = NT128 - NFIRST;
#define P1_M 51
#define P1_D 5
__device__ __forceinline__ int p1_tile(int t, bool small) {
    return t + (small ? ((t + 1) * P1_M + P1_D - 1) / P1_D : t * P1_D / P1_M);
}
constexpr int LN_TILE = 128 * C_DIM * 2;
constexpr int H_TILE = 64 * HID * 3 / 2;
constexpr int H_HALF = 3072, H_STEP = 6144;

__device__ __align__(1024) uint4 g_h[(size_t)M_TOTAL * HID * 3 / 32];
__device__ __align__(1024) uint4 g_ln[LN_RING * LN_TILE / 16];
__device__ __align__(1024) uint4 g_w2img[2][HID * C_DIM * 2 / 16];
__device__ __align__(16) float g_sums[2][HID + 2 * C_DIM];
__device__ __align__(16) unsigned g_ex[HID];
__device__ unsigned g_epoch, g_par;
__device__ __align__(128) unsigned g_img[2];
__device__ __align__(128) unsigned g_prog;
__device__ __align__(128) unsigned g_half[32][2];
__device__ unsigned g_flag[LN_RING + 3][2][8];
#define TSTAMP(k, i)
#define TRACE(wg, pos, i)
#define TRACEW(pos, i)

#define TR2(i)
#define TR2P(pos, i)
__host__ __device__ __forceinline__ int perm32(int n) {
    return (n & ~31) | (((n >> 1) & 3) << 3) | (((n >> 3) & 3) << 1) | (n & 1);
}

__device__ __forceinline__ uint32_t smem_u32(const void* p) { return (uint32_t)__cvta_generic_to_shared(p); }

__device__ __forceinline__ void mbar_init(uint32_t bar, uint32_t count) {
    asm volatile("mbarrier.init.shared::cta.b64 [%0], %1;\n" ::"r"(bar), "r"(count) : "memory");
}
__device__ __forceinline__ void mbar_expect_tx(uint32_t bar, uint32_t bytes) {
    asm volatile("mbarrier.arrive.expect_tx.shared::cta.b64 _, [%0], %1;\n" ::"r"(bar), "r"(bytes) : "memory");
}
__device__ __forceinline__ void mbar_arrive(uint32_t bar) {
    asm volatile("mbarrier.arrive.shared::cta.b64 _, [%0];\n" ::"r"(bar) : "memory");
}
__device__ __forceinline__ void mbar_arrive_cluster(uint32_t bar_cluster_addr) {
    asm volatile("mbarrier.arrive.shared::cluster.b64 _, [%0];\n" ::"r"(bar_cluster_addr) : "memory");
}
#define SAFE_BREAK
__device__ __forceinline__ void mbar_wait(uint32_t bar, uint32_t parity) {
    asm volatile(
        "{\n"
        ".reg .pred p;\n"
        "LAB_WAIT:\n"
        "mbarrier.try_wait.parity.shared::cta.b64 p, [%0], %1;\n"
        "@!p bra LAB_WAIT;\n"
        "}\n" ::"r"(bar), "r"(parity) : "memory");
}
__device__ __forceinline__ bool mbar_test(uint32_t bar, uint32_t parity) {
    uint32_t ok;
    asm volatile("{\n.reg .pred p;\n"
                 "mbarrier.test_wait.parity.shared::cta.b64 p, [%1], %2;\n"
                 "selp.u32 %0, 1, 0, p;\n}\n" : "=r"(ok) : "r"(bar), "r"(parity) : "memory");
    return ok != 0;
}
__device__ __forceinline__ uint32_t mapa(uint32_t addr, uint32_t rank) {
    uint32_t r;
    asm volatile("mapa.shared::cluster.u32 %0, %1, %2;\n" : "=r"(r) : "r"(addr), "r"(rank));
    return r;
}
__device__ __forceinline__ void bulk_g2s(uint32_t dst, const void* src, uint32_t bytes, uint32_t bar) {
    asm volatile("cp.async.bulk.shared::cluster.global.mbarrier::complete_tx::bytes [%0], [%1], %2, [%3];\n"
                 ::"r"(dst), "l"(src), "r"(bytes), "r"(bar) : "memory");
}
__device__ __forceinline__ void bulk_g2s_mc(uint32_t dst, const void* src, uint32_t bytes, uint32_t bar, uint16_t mask) {
    asm volatile("cp.async.bulk.shared::cluster.global.mbarrier::complete_tx::bytes.multicast::cluster [%0], [%1], %2, [%3], %4;\n"
                 ::"r"(dst), "l"(src), "r"(bytes), "r"(bar), "h"(mask) : "memory");
}
__device__ __forceinline__ void tma2(uint32_t dst, const CUtensorMap* map, int c0, int c1, uint32_t bar) {
    asm volatile("cp.async.bulk.tensor.2d.shared::cluster.global.tile.mbarrier::complete_tx::bytes [%0], [%1, {%2, %3}], [%4];\n"
                 ::"r"(dst), "l"(map), "r"(c0), "r"(c1), "r"(bar) : "memory");
}
template <bool ACQ>
__device__ __forceinline__ uint32_t flag_wait(const unsigned* p, unsigned target) {
    unsigned v, n = 0;
    do {
        if (ACQ) asm volatile("ld.acquire.gpu.global.u32 %0, [%1];\n" : "=r"(v) : "l"(p) : "memory");
        else asm volatile("ld.relaxed.gpu.global.u32 %0, [%1];\n" : "=r"(v) : "l"(p) : "memory");
        n++;
    } while (v < target);
    return n == 1;
}
__device__ __forceinline__ void ldsm4t(uint32_t (&r)[4], uint32_t addr) {
    asm volatile("ldmatrix.sync.aligned.m8n8.x4.trans.shared.b16 {%0,%1,%2,%3}, [%4];\n"
                 : "=r"(r[0]), "=r"(r[1]), "=r"(r[2]), "=r"(r[3]) : "r"(addr) : "memory");
}
__device__ __forceinline__ void bulk_s2g(void* dst, uint32_t src, uint32_t bytes) {
    asm volatile("cp.async.bulk.global.shared::cta.bulk_group [%0], [%1], %2;\n" ::"l"(dst), "r"(src), "r"(bytes) : "memory");
}
__device__ __forceinline__ void cluster_sync_relaxed() {
    asm volatile("barrier.cluster.arrive.relaxed.aligned;\nbarrier.cluster.wait.aligned;\n" ::: "memory");
}
__device__ __forceinline__ void gdc_wait() { asm volatile("griddepcontrol.wait;\n" ::: "memory"); }
__device__ __forceinline__ void gdc_launch() { asm volatile("griddepcontrol.launch_dependents;\n" ::: "memory"); }
__device__ __forceinline__ uint32_t cluster_rank() {
    uint32_t r;
    asm volatile("mov.u32 %0, %%cluster_ctarank;\n" : "=r"(r));
    return r;
}
__device__ __forceinline__ bool elect_one() {
    uint32_t pred;
    asm volatile("{\n.reg .pred p;\nelect.sync _|p, 0xffffffff;\nselp.u32 %0, 1, 0, p;\n}\n" : "=r"(pred));
    return pred != 0;
}
__device__ __forceinline__ void wg_fence() { asm volatile("wgmma.fence.sync.aligned;\n" ::: "memory"); }
__device__ __forceinline__ void wg_commit() { asm volatile("wgmma.commit_group.sync.aligned;\n" ::: "memory"); }
template <int N> __device__ __forceinline__ void wg_wait() {
    asm volatile("wgmma.wait_group.sync.aligned %0;\n" ::"n"(N) : "memory");
}
template <int R> __device__ __forceinline__ void reg_inc() { asm volatile("setmaxnreg.inc.sync.aligned.u32 %0;\n" ::"n"(R)); }
template <int R> __device__ __forceinline__ void reg_dec() { asm volatile("setmaxnreg.dec.sync.aligned.u32 %0;\n" ::"n"(R)); }
__device__ __forceinline__ void bar_sync(int id, int n) { asm volatile("bar.sync %0, %1;\n" ::"r"(id), "r"(n) : "memory"); }
__device__ __forceinline__ void bar_arrive(int id, int n) { asm volatile("bar.arrive %0, %1;\n" ::"r"(id), "r"(n) : "memory"); }

__device__ __forceinline__ uint64_t make_desc(uint32_t saddr, uint32_t lbo, uint32_t sbo) {
    return (uint64_t)((saddr & 0x3FFFF) >> 4) | ((uint64_t)(lbo >> 4) << 16) | ((uint64_t)(sbo >> 4) << 32);
}

__device__ __forceinline__ void stg128_cs(void* p, uint32_t a, uint32_t b, uint32_t c, uint32_t d) {
    asm volatile("st.global.cs.v4.u32 [%0], {%1,%2,%3,%4};\n" ::"l"(p), "r"(a), "r"(b), "r"(c), "r"(d) : "memory");
}
__device__ __forceinline__ uint32_t pack_bf16(float lo, float hi) {
    uint32_t r;
    asm("cvt.rn.bf16x2.f32 %0, %1, %2;\n" : "=r"(r) : "f"(hi), "f"(lo));
    return r;
}
__device__ __forceinline__ float bf_lo(uint32_t v) { return __uint_as_float(v << 16); }
__device__ __forceinline__ float bf_hi(uint32_t v) { return __uint_as_float(v & 0xffff0000u); }
__device__ __forceinline__ uint32_t bf2_mul(uint32_t a, uint32_t b) {
    uint32_t r;
    asm("mul.rn.bf16x2 %0, %1, %2;\n" : "=r"(r) : "r"(a), "r"(b));
    return r;
}
__device__ __forceinline__ uint32_t bf2_fma(uint32_t a, uint32_t b, uint32_t c) {
    uint32_t r;
    asm("fma.rn.bf16x2 %0, %1, %2, %3;\n" : "=r"(r) : "r"(a), "r"(b), "r"(c));
    return r;
}
__device__ __forceinline__ uint32_t bf2_add(uint32_t a, uint32_t b) {
    uint32_t r;
    asm("add.rn.bf16x2 %0, %1, %2;\n" : "=r"(r) : "r"(a), "r"(b));
    return r;
}
constexpr float KAPPA = 0.3292034911525734f;
constexpr float GELU_C = 2.423681954311584f;
constexpr float HSCALE = 1.0f / (2.0f * KAPPA);
__device__ __forceinline__ uint32_t acc_exp(float z) { return max(__float_as_uint(z) >> 23, 10u); }
__device__ __forceinline__ void sched_break(int zero) {
    asm volatile("{\n.reg .pred p;\nsetp.ne.s32 p, %0, 0;\nSB_LOOP:\n@p nanosleep.u32 1;\n@p bra SB_LOOP;\n}\n" ::"r"(zero));
}

#define ACC8(d, o) "+f"(d[o + 0]), "+f"(d[o + 1]), "+f"(d[o + 2]), "+f"(d[o + 3]), "+f"(d[o + 4]), "+f"(d[o + 5]), "+f"(d[o + 6]), "+f"(d[o + 7])

#define ACCR8(d, o) "+r"(d[o + 0]), "+r"(d[o + 1]), "+r"(d[o + 2]), "+r"(d[o + 3]), "+r"(d[o + 4]), "+r"(d[o + 5]), "+r"(d[o + 6]), "+r"(d[o + 7])
__device__ __forceinline__ void mma_rs_n128(uint32_t (&d)[32], const uint32_t (&a)[4], uint64_t desc, int scale_d) {
    asm volatile(
        "{\n.reg .pred p;\nsetp.ne.b32 p, %37, 0;\n"
        "wgmma.mma_async.sync.aligned.m64n128k16.f16.f16.f16 "
        "{%0,%1,%2,%3,%4,%5,%6,%7,%8,%9,%10,%11,%12,%13,%14,%15,"
        "%16,%17,%18,%19,%20,%21,%22,%23,%24,%25,%26,%27,%28,%29,%30,%31},"
        "{%32,%33,%34,%35}, %36, p, 1, 1, 0;\n}\n"
        : ACCR8(d, 0), ACCR8(d, 8), ACCR8(d, 16), ACCR8(d, 24)
        : "r"(a[0]), "r"(a[1]), "r"(a[2]), "r"(a[3]), "l"(desc), "r"(scale_d));
}
__device__ __forceinline__ void mma_ss_n128(uint32_t (&d)[32], uint64_t da, uint64_t db) {
    asm volatile(
        "{\n.reg .pred p;\nsetp.ne.b32 p, %34, 0;\n"
        "wgmma.mma_async.sync.aligned.m64n128k16.f16.f16.f16 "
        "{%0,%1,%2,%3,%4,%5,%6,%7,%8,%9,%10,%11,%12,%13,%14,%15,"
        "%16,%17,%18,%19,%20,%21,%22,%23,%24,%25,%26,%27,%28,%29,%30,%31},"
        "%32, %33, p, 1, 1, 0, 0;\n}\n"
        : ACCR8(d, 0), ACCR8(d, 8), ACCR8(d, 16), ACCR8(d, 24)
        : "l"(da), "l"(db), "r"(1));
}
__device__ __forceinline__ uint32_t bf2_as_h2(uint32_t v) { return (v & 0x0fff0fffu) * 7u + v; }
__device__ __forceinline__ float h_lo(uint32_t v) {
    float r;
    asm("{\n.reg .b16 l, h;\nmov.b32 {l, h}, %1;\ncvt.f32.f16 %0, l;\n}\n" : "=f"(r) : "r"(v));
    return r;
}
__device__ __forceinline__ float h_hi(uint32_t v) {
    float r;
    asm("{\n.reg .b16 l, h;\nmov.b32 {l, h}, %1;\ncvt.f32.f16 %0, h;\n}\n" : "=f"(r) : "r"(v));
    return r;
}

__device__ __forceinline__ void mma_rs_n192(uint32_t (&d)[48], const uint4& a, uint64_t db, int scale_d) {
    asm volatile(
        "{\n.reg .pred p;\nsetp.ne.b32 p, %53, 0;\n"
        "wgmma.mma_async.sync.aligned.m64n192k16.f16.f16.f16 "
        "{%0,%1,%2,%3,%4,%5,%6,%7,%8,%9,%10,%11,%12,%13,%14,%15,"
        "%16,%17,%18,%19,%20,%21,%22,%23,%24,%25,%26,%27,%28,%29,%30,%31,"
        "%32,%33,%34,%35,%36,%37,%38,%39,%40,%41,%42,%43,%44,%45,%46,%47},"
        "{%48,%49,%50,%51}, %52, p, 1, 1, 0;\n}\n"
        : ACCR8(d, 0), ACCR8(d, 8), ACCR8(d, 16), ACCR8(d, 24), ACCR8(d, 32), ACCR8(d, 40)
        : "r"(a.x), "r"(a.y), "r"(a.z), "r"(a.w), "l"(db), "r"(scale_d));
}

__device__ __forceinline__ uint32_t pack_f16(float lo, float hi) {
    uint32_t r;
    asm("cvt.rn.f16x2.f32 %0, %1, %2;\n" : "=r"(r) : "f"(hi), "f"(lo));
    return r;
}

#define P1_IMG 900
constexpr int P1_SLOT = LN_TILE / 2, P1_NST = 4;
constexpr int P1_X = 16 * C_DIM * 2;
constexpr int P1_OFF_X = P1_SLOT * P1_NST;
constexpr int P1_OFF_A = P1_OFF_X + 2 * P1_X;
constexpr int P1_OFF_BAR = P1_OFF_A + 3 * 2048;
constexpr int P1_OFF_TILE = P1_OFF_BAR + (2 * P1_NST + 3 + 2 + 3 + 2) * 8;
constexpr int P1_OFF_DW = P1_OFF_TILE + 64;
constexpr int P1_SMEM = P1_OFF_DW + C_DIM * 2;

__device__ __forceinline__ float rsqrt_fast(float x) {
    float r;
    asm("rsqrt.approx.ftz.f32 %0, %1;\n" : "=f"(r) : "f"(x));
    return r;
}
__device__ __forceinline__ float sum8(const uint32_t (&c)[4]) {
    const uint32_t u = bf2_add(bf2_add(c[0], c[1]), bf2_add(c[2], c[3]));
    return bf_lo(u) + bf_hi(u);
}
__device__ __forceinline__ void lds128(uint32_t (&v)[4], uint32_t a) {
    asm volatile("ld.shared.v4.u32 {%0,%1,%2,%3}, [%4];\n" : "=r"(v[0]), "=r"(v[1]), "=r"(v[2]), "=r"(v[3]) : "r"(a) : "memory");
}
template <class F>
__device__ __forceinline__ void ln_row(uint32_t (&v)[6][4], uint32_t sdw, F after_loads) {
    uint32_t c[4], s[4], d[4], nm;
#pragma unroll
    for (int i = 0; i < 6; i++) {
        lds128(d, sdw + i * 128);
        if (i == 0) {
#pragma unroll
            for (int k = 0; k < 4; k++) c[k] = bf2_mul(v[0][k], d[k]);
            const float p = sum8(c) * -0.125f;
            nm = pack_bf16(p, p);
        }
#pragma unroll
        for (int k = 0; k < 4; k++) {
            v[i][k] = bf2_fma(v[i][k], d[k], nm);
            s[k] = i ? bf2_add(v[i][k], s[k]) : v[i][k];
            c[k] = i ? bf2_fma(v[i][k], v[i][k], c[k]) : bf2_mul(v[i][k], v[i][k]);
        }
    }
    after_loads(c[0]);
    float m = fmaf(sum8(s), 1.0f / 48, -bf_lo(nm));
    float q = fmaf(-bf_lo(nm), fmaf(2.f, m, bf_lo(nm)), sum8(c) * (1.0f / 48));
#pragma unroll
    for (int o = 1; o < 8; o <<= 1) {
        m += __shfl_xor_sync(0xffffffffu, m, o);
        q += __shfl_xor_sync(0xffffffffu, q, o);
    }
    m *= 0.125f;
    const float r = KAPPA * rsqrt_fast(fmaxf(fmaf(-m, m, q * 0.125f), 0.f) + 1e-5f);
    const float e = (-bf_lo(nm) - m) * r * 0x1p-112f;
    const bool two = __any_sync(0xffffffffu, r < 0x1p-14f);
    const float r1 = r * (two ? 0x1p-56f : 0x1p-112f);
    uint32_t mul = pack_bf16(r1, r1), add = two ? 0u : pack_bf16(e, e);
#pragma unroll 1
    for (int it = !two; it < 2; it++) {
#pragma unroll
        for (int i = 0; i < 6; i++)
#pragma unroll
            for (int k = 0; k < 4; k++) v[i][k] = bf2_fma(v[i][k], mul, add);
        mul = 0x23802380u;
        add = pack_bf16(e, e);
    }
#pragma unroll
    for (int i = 0; i < 6; i++)
#pragma unroll
        for (int k = 0; k < 4; k++) v[i][k] = bf2_as_h2(v[i][k]);
}

__device__ __forceinline__ float gelu_s(float y) {
    float u = y * fmaf(y, y, GELU_C);
    float t;
    asm volatile("tanh.approx.f32 %0, %1;\n" : "=f"(t) : "f"(u));
    return fmaf(y, t, y);
}
__device__ __forceinline__ void p1_pack(int c, uint32_t (&p)[4], uint32_t (&dd)[4]) {
#pragma unroll
    for (int u = 0; u < 4; u++) {
        if ((c & 3) == 0) dd[u] = p[u];
        else {
            uint32_t n = dd[u];
            if ((c & 3) == 1) n = __byte_perm(n, 0, 0x2301);
            if ((c & 3) == 2) {
                dd[u] = __byte_perm(n >> 3, n >> 1, 0x6341);
                n = __byte_perm(n >> 3, n >> 1, 0x7250);
            }
            asm("lop3.b32 %0, %0, %1, 0x40074007, 0xd8;\n" : "+r"(p[u]) : "r"(n));
        }
    }
}
__device__ __forceinline__ void p1_store(int c, const uint32_t (&p)[4], uint8_t* hptr) {
    if (c & 3) stg128_cs(hptr + (c >> 2) * H_HALF + ((c & 3) - 1) * 512, p[0], p[1], p[2], p[3]);
}

template <bool GEN>
__device__ __forceinline__ void p1_epilogue(const uint32_t (&acc)[32], float (&ssq)[2], uint32_t sc2, uint8_t* hp, int zero) {
    uint32_t sq[2], dd[4];
#pragma unroll
    for (int c = 0; c < 8; c++) {
        if (GEN) sched_break(zero);
        uint32_t p[4];
#pragma unroll
        for (int u = 0; u < 4; u++) {
            const uint32_t y = acc[8 * (c >> 1) + 2 * u + (c & 1)];
            if (GEN) {
                const float sc = c & 1 ? bf_hi(sc2) : bf_lo(sc2), fs = __uint_as_float(0x78000000u - __float_as_uint(sc));
                const float g0 = gelu_s(h_lo(y) * fs), g1 = gelu_s(h_hi(y) * fs);
                ssq[c & 1] = fmaf(g1, g1, fmaf(g0, g0, ssq[c & 1]));
                p[u] = pack_f16(g0 * sc, g1 * sc);
            } else {
                uint32_t g;
                asm("{\n.reg .b32 w;\n"
                    "fma.rn.f16x2 w, %1, %1, %2;\n"
                    "mul.rn.f16x2 w, w, %1;\n"
                    "tanh.approx.f16x2 w, w;\n"
                    "fma.rn.f16x2 %0, %1, w, %1;\n}\n" : "=r"(g) : "r"(y), "r"(0x40d940d9u));
                if (c < 2 && u == 0) asm("mul.rn.f16x2 %0, %1, %1;\n" : "=r"(sq[c & 1]) : "r"(g));
                else asm("fma.rn.f16x2 %0, %1, %1, %0;\n" : "+r"(sq[c & 1]) : "r"(g));
                if (c & 1) asm("{\n.reg .b16 l, h;\n.reg .b32 f;\nmov.b32 {l, h}, %2;\nmov.b32 f, {h, h};\nmul.rn.f16x2 %0, %1, f;\n}\n" : "=r"(p[u]) : "r"(g), "r"(sc2));
                else asm("{\n.reg .b16 l, h;\n.reg .b32 f;\nmov.b32 {l, h}, %2;\nmov.b32 f, {l, l};\nmul.rn.f16x2 %0, %1, f;\n}\n" : "=r"(p[u]) : "r"(g), "r"(sc2));
            }
        }
        p1_pack(c, p, dd);
        p1_store(c, p, hp);
    }
    if (!GEN) {
#pragma unroll
        for (int r = 0; r < 2; r++) ssq[r] += h_lo(sq[r]) + h_hi(sq[r]);
    }
}
__device__ __forceinline__ void p1_consumer(const uint32_t (&a)[24][4], uint32_t sc2, bool gen, uint32_t sbase, int wg, int nwg, int cb, int first,
                                            int w, int lane, int zero) {
    const uint32_t bar_full = sbase + P1_OFF_BAR, bar_empty = bar_full + P1_NST * 8;
    const uint32_t empty_remote = mapa(bar_empty, lane & 1);
    const int g = lane >> 2, q = lane & 3, turn = wg + 1 == nwg ? 1 : wg + 2;
    float ssq[2] = {0.f, 0.f};
    uint32_t acc[32];
    TSTAMP(0, 1);

    uint8_t* hp = reinterpret_cast<uint8_t*>(g_h) + (size_t)first * (2 * H_TILE) + ((cb * 2 + (w >> 1)) * H_STEP + (w & 1) * 1536) + g * 64 + (q ^ (g >> 1)) * 16;
    const uint64_t desc_base = make_desc(sbase, 16, 1024) | (1ull << 62);
    const uint64_t da = make_desc(sbase + P1_OFF_A + wg * 2048, 128, 256);
#pragma unroll 1
    for (int i = 0;; i++) {
        const int s0 = (i & 1) * 16, par = (i >> 1) & 1;
        const uint64_t d0 = desc_base + (uint64_t)((i & 1) * (LN_TILE / 16));
        TRACE(wg, i, 0);
        mbar_wait(bar_full + s0, par);
        bar_sync(1 + wg, 256);
        TRACE(wg, i, 1);
        uint32_t step, more;
        wg_fence();
#pragma unroll
        for (int k = 0; k < 24; k++) {
            if (k == 12) mbar_wait(bar_full + s0 + 8, par);
            const uint64_t db = d0 + (uint64_t)((k >> 2) * 1024 + (k & 3) * 2);
            if (k < 23) mma_rs_n128(acc, a[k], db, k != 0);
            else mma_ss_n128(acc, da, db);
            if (k == 23) bar_arrive(turn, 256);
            if (k % 12 == 11) wg_commit();
        }
        asm volatile("ld.shared.v2.u32 {%0, %1}, [%2];\n" : "=r"(step), "=r"(more) : "r"(sbase + P1_OFF_TILE + (i & 3) * 16) : "memory");
        TRACE(wg, i, 2);
        wg_wait<1>();
        if (lane < 2) mbar_arrive_cluster(empty_remote + s0);
        hp += step;
        TRACE(wg, i, 3);
        wg_wait<0>();
        TRACE(wg, i, 4);
        if (lane < 2) mbar_arrive_cluster(empty_remote + s0 + 8);
        if (gen) p1_epilogue<true>(acc, ssq, sc2, hp, zero);
        else p1_epilogue<false>(acc, ssq, sc2, hp, zero);
        if (!more) break;
    }
    TSTAMP(0, 21);
    if (wg == 0) bar_sync(1, 256);
    uint32_t par;
    asm volatile("ld.shared.u32 %0, [%1];\n" : "=r"(par) : "r"(sbase + P1_OFF_TILE - 4) : "memory");
    float* sums = g_sums[par];
#pragma unroll
    for (int r = 0; r < 2; r++) {
        ssq[r] += __shfl_xor_sync(0xffffffffu, ssq[r], 1);
        ssq[r] += __shfl_xor_sync(0xffffffffu, ssq[r], 2);
        if (q == 0) atomicAdd(sums + cb * 64 + w * 16 + r * 8 + g, ssq[r]);
    }
}

__device__ __forceinline__ void p1_w2(const __nv_bfloat16* __restrict__ w2, const __nv_bfloat16* __restrict__ grn_b, int w, int lane) {
    const int gw = (blockIdx.x - 8 * NGRP) * 4 + w;
    float* sums = g_sums[__ldcg(&g_epoch) & 1] + HID;
    flag_wait<true>(&g_flag[40][1][0], 12);
    {
        const int col = gw % 6 * 64 + lane * 2;
        float bsum[2] = {0.f, 0.f}, asum[2] = {0.f, 0.f};
#pragma unroll 4
        for (int kk = 0; kk < 192; kk++) {
            const int k = gw / 6 * 192 + kk;
            const uint32_t v = *reinterpret_cast<const uint32_t*>(w2 + k * C_DIM + col);
            const float b = __bfloat162float(grn_b[k]), f = __uint_as_float(__ldcg(&g_ex[k]) << 23);
            bsum[0] = fmaf(b, bf_lo(v), bsum[0]);
            bsum[1] = fmaf(b, bf_hi(v), bsum[1]);
            asum[0] = fmaf(f, fabsf(bf_lo(v)), asum[0]);
            asum[1] = fmaf(f, fabsf(bf_hi(v)), asum[1]);
        }
#pragma unroll
        for (int j = 0; j < 2; j++) {
            atomicAdd(sums + col + j, bsum[j]);
            atomicAdd(sums + C_DIM + col + j, asum[j]);
        }
        __threadfence();
        __syncwarp();
        if (lane == 0) asm volatile("red.relaxed.gpu.global.add.u32 [%0], 1;\n" ::"l"(&g_flag[LN_RING + 2][0][0]) : "memory");
    }
    while (*(volatile unsigned*)&g_flag[P1_IMG % LN_RING][1][0] < 12 * (P1_IMG / LN_RING + 1)) {
        __nanosleep(2000);
        SAFE_BREAK
    }
    flag_wait<true>(&g_flag[LN_RING + 2][0][0], 48);
    float z = 0.f;
#pragma unroll
    for (int j = 0; j < C_DIM / 32; j++) z = fmaxf(z, __ldcg(sums + C_DIM + j * 32 + lane));
    const float sc = __uint_as_float((263u - acc_exp(__uint_as_float(__reduce_max_sync(0xffffffffu, __float_as_uint(z))))) << 23);
    const int np = gw % 6 * 64 + lane * 2;
#pragma unroll 2
    for (int cc = 0; cc < 24; cc++) {
        const int c = gw / 6 * 24 + cc;
        uint32_t v[8], o[2][4];
#pragma unroll
        for (int e = 0; e < 8; e++) v[e] = *reinterpret_cast<const uint32_t*>(w2 + (c * 8 + e) * C_DIM + perm32(np));
#pragma unroll
        for (int e = 0; e < 4; e++) {
            const uint2 t = __ldcg(reinterpret_cast<const uint2*>(g_ex) + c * 4 + e);
            const float f0 = __uint_as_float(t.x << 23), f1 = __uint_as_float(t.y << 23);
            o[0][e] = pack_f16(bf_lo(v[2 * e]) * f0 * sc, bf_lo(v[2 * e + 1]) * f1 * sc);
            o[1][e] = pack_f16(bf_hi(v[2 * e]) * f0 * sc, bf_hi(v[2 * e + 1]) * f1 * sc);
        }
#pragma unroll
        for (int j = 0; j < 2; j++)
            g_w2img[0][(((c >> 1) * 48 + (np >> 3)) * 2 + (c & 1)) * 8 + (np & 7) + j] = make_uint4(o[j][0], o[j][1], o[j][2], o[j][3]);
    }
    asm volatile("fence.proxy.async.global;\n" ::: "memory");
    __threadfence();
    __syncwarp();
    if (lane == 0) asm volatile("red.relaxed.gpu.global.add.u32 [%0], 1;\n" ::"l"(&g_img[0]) : "memory");
}

__global__ void __cluster_dims__(2, 1, 1) __launch_bounds__(512, 1)
pass1_kernel(const __grid_constant__ CUtensorMap wmap, const __nv_bfloat16* __restrict__ x, const __nv_bfloat16* __restrict__ dw,
             const __nv_bfloat16* __restrict__ w1, const __nv_bfloat16* __restrict__ w2, const __nv_bfloat16* __restrict__ grn_b, int zero) {
    extern __shared__ __align__(1024) uint8_t smem[];
    if (threadIdx.x == 128 && blockIdx.x < 128)
        asm volatile("cp.async.bulk.prefetch.L2.global [%0], 9216;\n" ::"l"(w1 + blockIdx.x * 4608) : "memory");
    const uint32_t sbase = smem_u32(smem);
    const uint32_t bar_full = sbase + P1_OFF_BAR, bar_empty = bar_full + P1_NST * 8, bar_w = bar_empty + P1_NST * 8;
    const uint32_t bar_xfull = bar_w + 24, bar_raw = bar_xfull + 16, bar_dw = bar_raw + 16, bar_done = bar_dw + 8;
    const int tid = threadIdx.x;
    const int warp = __shfl_sync(0xffffffffu, tid >> 5, 0), lane = tid & 31;
    const uint32_t rank = cluster_rank();
    const int cl = blockIdx.x >> 1, first = min(cl >> 2, NGRP);
    const bool small = cl >= 4 * NGRP;
    const int nwg = small ? 2 : 3, cb0 = small ? (blockIdx.x - 8 * NGRP) * 2 : (blockIdx.x & 7) * 3;
    const int tile1 = p1_tile(small ? 0 : first, small), tile2 = p1_tile(small ? 1 : first + NGRP, small);
    uint8_t* const ring = reinterpret_cast<uint8_t*>(g_ln);
    const uint32_t sdw = sbase + P1_OFF_DW + (lane & 7) * 16;
    const uint8_t* xsrc = reinterpret_cast<const uint8_t*>(x) + (size_t)(NFIRST * 4 + blockIdx.x) * (2 * P1_X);
    auto ring_row = [&](int p) {
        const int n = (blockIdx.x & 2) * 32 + (lane >> 3) * 8 + p * 2 + (blockIdx.x & 1);
        return n * 128 + (((lane ^ n) & 7) << 4);
    };

    TSTAMP(0, 0);
    TRACEW(110 + warp, 0);

    if (warp >= 12) {
        reg_dec<56>();
        asm volatile("barrier.cluster.arrive.relaxed.aligned;\n" ::: "memory");
        asm volatile("barrier.cluster.wait.aligned;\n" ::: "memory");
        if (warp == 12) {
            int prev = first - NFIRST, t = tile1, next = tile2;
            const uint32_t rbase = mapa(sbase, lane & 1);
            int i = 1;
#pragma unroll 1
            for (; t < NT_RING; i++) {
                const int s0 = (i & 1) * 2, par = ((i + 1) >> 1 & 1) ^ 1;
                const int round = t / LN_RING, slot = t - round * LN_RING;
                const uint8_t* src = ring + slot * LN_TILE + rank * (P1_SLOT / 2);
                int draw = i + 1;
                if (rank == 0 && lane == 0 && !small) draw = 2 * NGRP + atomicAdd(&g_flag[LN_RING + ((cl >> 1) & 1)][cl & 1][0], 1u);
                flag_wait<true>(&g_flag[slot][0][0], 4 * round + 4);
                TRACEW(i, 2);
                asm volatile("fence.proxy.async.global;\n" ::: "memory");
                draw = p1_tile(__shfl_sync(0xffffffffu, draw, 0), small);
#pragma unroll
                for (int h = 0; h < 2; h++) {
                    mbar_wait(bar_empty + (s0 + h) * 8, par);
                    TRACEW(i, 4 + h);
                    if (elect_one()) {
                        mbar_expect_tx(bar_full + (s0 + h) * 8, P1_SLOT + 16 - 16 * h);
                        bulk_g2s_mc(sbase + (s0 + h) * P1_SLOT + rank * (P1_SLOT / 2), src + h * P1_SLOT, P1_SLOT / 2, bar_full + (s0 + h) * 8, (uint16_t)3);
                    }
                    __syncwarp();
                    if (h == 0 && rank == 0 && lane < 2)
                        asm volatile("st.async.shared::cluster.mbarrier::complete_tx::bytes.v4.u32 [%0], {%1, %2, %3, %3}, [%4];\n"
                                     ::"r"(rbase + P1_OFF_TILE + (i & 3) * 16), "r"((t - prev) * (2 * H_TILE)), "r"((int)(next < NT_RING)), "r"(draw),
                                       "r"(rbase + P1_OFF_BAR + s0 * 8) : "memory");
                }
                prev = t;
                t = next;
                next = draw;
                if (rank != 0) {
                    mbar_wait(bar_full + s0 * 8, (i >> 1) & 1);
                    mbar_wait(bar_full + s0 * 8 + 8, (i >> 1) & 1);
                    if (lane == 0) asm volatile("red.relaxed.gpu.global.add.u32 [%0], %1;\n" ::"l"(&g_flag[slot][1][0]), "r"(nwg) : "memory");
                    asm volatile("ld.shared.u32 %0, [%1];\n" : "=r"(next) : "r"(sbase + P1_OFF_TILE + (i & 3) * 16 + 8) : "memory");
                    TRACEW(i, 3);
                }
            }
#pragma unroll 1
            for (int j = 2 * i; j < 2 * i + 4; j++) mbar_wait(bar_empty + (j & 3) * 8, ((j + 2) >> 2 & 1) ^ 1);
        } else if (warp == 13) {
            const uint32_t par = g_epoch & 1;
            asm volatile("st.shared.u32 [%0], %1;\n" ::"r"(sbase + P1_OFF_TILE - 4), "r"(par) : "memory");
            if (blockIdx.x == 18) g_par = par;
            if (blockIdx.x < 18) reinterpret_cast<float4*>(g_sums[par ^ 1])[blockIdx.x * 32 + lane] = make_float4(0.f, 0.f, 0.f, 0.f);
            {
                bar_sync(4, 288);
                mbar_wait(bar_raw + 8, 0);
                const uint32_t o = lane * 16384 + rank * 8192, peer = mapa(sbase, rank ^ 1);
                if (lane < 6)
                    asm volatile("cp.async.bulk.shared::cluster.shared::cta.mbarrier::complete_tx::bytes [%0], [%1], 8192, [%2];\n"
                                 ::"r"(peer + o), "r"(sbase + o), "r"(peer + P1_OFF_BAR + (lane >= 3 ? 8 : 0)) : "memory");
                __syncwarp();
            }
#pragma unroll 1
            for (int i = 0; i * LN_STEP + (blockIdx.x >> 2) < NT_RING; i++) {
                mbar_wait(bar_done, i & 1);
                asm volatile("fence.proxy.async.global;\n" ::: "memory");
                if (lane == 0) {
                    mbar_arrive(bar_done);
                    asm volatile("red.release.gpu.global.add.u32 [%0], 1;\n" ::"l"(&g_flag[(blockIdx.x >> 2) + i % LN_DEPTH * LN_STEP][0][0]) : "memory");
                }
                __syncwarp();
                TRACEW(128 + i, 3);
            }
            flag_wait<true>(&g_flag[LN_RING + 2][0][0], 48);
        } else {
            const uint32_t xbar = bar_xfull + (warp & 1) * 8, xdst = sbase + P1_OFF_X + (warp & 1) * P1_X;
            const uint32_t src = xdst + (lane >> 3) * (C_DIM * 2) + (lane & 7) * 16;
            const int row0 = ring_row((warp & 1) * 2);
            int slot = blockIdx.x >> 2, used = 0;
            xsrc += (warp & 1) * P1_X;
            auto next = [&]() {
                xsrc += (size_t)NUM_CTAS * 2 * P1_X;
                if (elect_one()) {
                    mbar_expect_tx(xbar, P1_X);
                    bulk_g2s(xdst, xsrc, P1_X, xbar);
                }
                __syncwarp();
            };
            if (lane == 0) asm volatile("cp.async.bulk.prefetch.L2.global [%0], %1;\n" ::"l"(xsrc + (size_t)NUM_CTAS * 2 * P1_X), "r"(P1_X) : "memory");
#pragma unroll 1
            for (int i = 0; i * LN_STEP + (blockIdx.x >> 2) < NT_RING; i++) {
                if (warp == 14) TRACEW(128 + i, 0);
#pragma unroll 1
                for (int ps = i ? 0 : -1; ps < (i ? 4 : 2); ps++) {
                    if (ps == 0) {
                        if (i == 0) mbar_wait(bar_dw, 0);
                        if (i == 1) {
                            bar_sync(9, 192);
                            next();
                        }
                        if (i) flag_wait<false>(&g_flag[slot][1][0], used);
                        mbar_wait(xbar, i & 1);
                        if (warp == 14) TRACEW(128 + i, 1);
                    }
                    uint32_t v[6][4];
#pragma unroll
                    for (int j = 0; j < 6; j++) lds128(v[j], src + (ps & 3) * (4 * C_DIM * 2) + j * 128);
                    ln_row(v, sdw, [&](uint32_t dep) {
                        if (ps == 3 && (i + 1) * LN_STEP + (blockIdx.x >> 2) < NT_RING && !__any_sync(0xffffffffu, dep & zero)) next();
                    });
                    uint8_t* dst = ring + (slot * LN_TILE + (ps & 1) * 4096 + (row0 ^ (ps & 2) * 144));
#pragma unroll
                    for (int j = 0; j < 6; j++)
                        asm volatile("{\n.reg .pred p;\nsetp.ge.s32 p, %5, 0;\n@p st.global.v4.u32 [%0], {%1,%2,%3,%4};\n}\n"
                                     ::"l"(dst + j * 16384), "r"(v[j][0]), "r"(v[j][1]), "r"(v[j][2]), "r"(v[j][3]), "r"(ps) : "memory");
                }
                if (warp == 14) TRACEW(128 + i, 2);
                asm volatile("fence.proxy.async.global;\nfence.acq_rel.cta;\n" ::: "memory");
                if (i) mbar_wait(bar_done, ~i & 1);
                __syncwarp();
                if (lane == 0) mbar_arrive(bar_done);
                if ((slot += LN_STEP) >= LN_RING) { slot -= LN_RING; used += 12; }
            }
        }
    } else {
        if (tid == 0) {
            mbar_init(bar_raw, 1);
            mbar_init(bar_raw + 8, 1);
            asm volatile("fence.mbarrier_init.release.cluster;\n" ::: "memory");
            mbar_expect_tx(bar_raw, P1_SLOT);
            for (int i = 0; i < 6; i++)
                bulk_g2s(sbase + i * 16384 + rank * 8192, x + (size_t)(first * 128 + rank * 64) * C_DIM + i * 4096, 8192, bar_raw);
        }
        if (tid == 32) {
            mbar_init(bar_dw, 1);
            mbar_init(bar_xfull, 1);
            mbar_init(bar_xfull + 8, 1);
            mbar_init(bar_done, 3);
            asm volatile("fence.mbarrier_init.release.cluster;\n" ::: "memory");
            mbar_expect_tx(bar_dw, C_DIM * 2);
            bulk_g2s(sbase + P1_OFF_DW, dw, C_DIM * 2, bar_dw);
            for (int i = 0; i < 2; i++) {
                mbar_expect_tx(bar_xfull + i * 8, P1_X);
                bulk_g2s(sbase + P1_OFF_X + i * P1_X, xsrc + i * P1_X, P1_X, bar_xfull + i * 8);
            }
        }
        if (tid == 64) {
            asm volatile("st.shared.v2.u32 [%0], {0, 1};\n" ::"r"(sbase + P1_OFF_TILE) : "memory");
            for (int i = 0; i < P1_NST; i++) {
                mbar_init(bar_full + i * 8, 1);
                mbar_init(bar_empty + i * 8, 8 * nwg);
                if (i < 2) mbar_expect_tx(bar_full + i * 8, P1_SLOT / 2);
            }
            asm volatile("fence.mbarrier_init.release.cluster;\n" ::: "memory");
            if (blockIdx.x < 64) (&g_half[0][0])[blockIdx.x] = 0;
            else if (blockIdx.x == 64) g_prog = 0;
            else if (blockIdx.x < 67) g_img[blockIdx.x - 65] = 0;
        }
        if (tid == 96) {
            for (int i = 0; i < 3; i++) mbar_init(bar_w + i * 8, 1);
            asm volatile("fence.mbarrier_init.release.cluster;\n" ::: "memory");
        }
        __syncwarp();
        asm volatile("barrier.cluster.arrive.relaxed.aligned;\n" ::: "memory");
        if (tid == 96)
            for (int i = 0; i < nwg; i++) {
                mbar_expect_tx(bar_w + i * 8, P1_SLOT);
                for (int j = 0; j < 6; j++)
                    tma2(sbase + (i ? (1 + i) * P1_SLOT + j * 8192 : j * 16384 + (rank ^ 1) * 8192), &wmap, (cb0 + i) * 64, 64 * j, bar_w + i * 8);
            }
        __syncwarp();
        reg_inc<152>();
        TRACEW(110 + warp, 1);
        const int wg = warp >> 2, w = warp & 3;
        gdc_launch();
        asm volatile("barrier.cluster.wait.aligned;\n" ::: "memory");
        if (wg) {
            const int n = (warp - 4) * 8 + (lane >> 3), px = (n & 1) * 32 + (n >> 5) * 4 + ((n >> 1) & 1) * 8 + ((n >> 3) & 3);
            uint32_t v[6][4], nx[6][4];
#pragma unroll 1
            for (int ps = -2; ps <= wg; ps++) {
                if (ps == -1) {
                    mbar_wait(bar_dw, 0);
                    mbar_wait(bar_raw, 0);
                }
                if (ps == 1 && wg == 2) mbar_wait(bar_xfull + (w >> 1) * 8, 0);
                TRACEW(110 + warp, 2 + (ps == -1));
#pragma unroll
                for (int j = 0; j < 6; j++) {
                    const uint32_t o = (ps < 1 ? px + (~ps & 1) * 16 : (w >> 1) * 16 + (w & 1) * 4 + 8 + (lane >> 3)) * (C_DIM * 2) + j * 128;
#pragma unroll
                    for (int k = 0; k < 4; k++) v[j][k] = nx[j][k];
                    lds128(nx[j], sbase + (lane & 7) * 16 + o + (ps < 1 ? rank * 8192 + (o & ~8191u) : P1_OFF_X));
                }
                if (ps == -1) continue;
                ln_row(v, sdw, [&](uint32_t) {});
                if (ps == 0) bar_sync(11, 256);
                if (ps == 1 && wg == 2) bar_arrive(9, 192);
                uint8_t* dst = ps < 2 ? smem + (rank * 64 + n + (ps & 1) * 4) * 128 + (((lane ^ n ^ (ps & 1) * 4) & 7) << 4)
                                      : ring + (blockIdx.x >> 2) * LN_TILE + (w & 1) * 4096 + ring_row((w & 2) + 1);
#pragma unroll
                for (int j = 0; j < 6; j++)
                    asm volatile("{\n.reg .pred p;\nsetp.ge.s32 p, %5, 0;\n@p st.v4.u32 [%4], {%0,%1,%2,%3};\n}\n"
                                 ::"r"(v[j][0]), "r"(v[j][1]), "r"(v[j][2]), "r"(v[j][3]), "l"(dst + j * 16384), "r"(ps) : "memory");
                if (ps == 1) {
                    asm volatile("fence.proxy.async.shared::cta;\n" ::: "memory");
                    bar_arrive(4, 288);
                    bar_arrive(wg == 1 ? 1 : 8, 256);
                    TRACEW(110 + warp, 4);
                }
            }
            if (wg == 2) {
                asm volatile("fence.proxy.async.global;\n" ::: "memory");
                bar_sync(7, 128);
                if (tid == 256) mbar_arrive(bar_done);
            }
            if (wg == nwg) {
                p1_w2(w2, grn_b, w, lane);
                return;
            }
        }
        uint32_t a[24][4], ex[2], gen;
        const uint32_t wsrc = sbase + (wg ? (1 + wg) * P1_SLOT : (rank ^ 1) * 8192) + ((lane >> 4) * 8 + (lane & 7)) * 128 + (((2 * w + ((lane >> 3) & 1)) ^ (lane & 7)) << 4);
#pragma unroll 1
        for (int it = wg != 0; it < 2; it++) {
            if (it) mbar_wait(bar_w + wg * 8, 0);
            TRACEW(110 + warp, 5);
#pragma unroll
            for (int k = 0; k < 24; k++) ldsm4t(a[k], wsrc + (k & 3) * 2048 + (k >> 2) * (wg ? 8192 : 16384));
            if (it && wg == 0) {
                bar_sync(5, 128);
                if (tid == 0) mbar_arrive_cluster(mapa(bar_raw + 8, rank ^ 1));
            }
#pragma unroll
            for (int r = 0; r < 2; r++) {
                float t = 0.f;
#pragma unroll
                for (int j = 0; j < 6; j++) {
                    uint32_t c = bf2_mul(a[4 * j][r], a[4 * j][r]);
#pragma unroll
                    for (int k = 1; k < 8; k++) c = bf2_fma(a[4 * j + k / 2][r + (k & 1) * 2], a[4 * j + k / 2][r + (k & 1) * 2], c);
                    t += bf_lo(c) + bf_hi(c);
                }
                t += __shfl_xor_sync(0xffffffffu, t, 1);
                t += __shfl_xor_sync(0xffffffffu, t, 2);
                ex[r] = min(max(__float_as_uint(13.9f * __fsqrt_rn(t)) >> 23, 72u), 198u);
            }
            asm volatile("{\n.reg .pred p;\nsetp.gt.u32 p, %1, 7;\nbar.red.or.pred p, %2, 128, p;\nselp.u32 %0, 1, 0, p;\n}\n"
                         : "=r"(gen) : "r"(max(ex[0] - 125u, ex[1] - 125u)), "r"(5 + wg) : "memory");
            gen = __shfl_sync(0xffffffffu, gen, 0) & it;
            if (it) {
                if ((lane & 3) < 2) g_ex[(cb0 + wg) * 64 + w * 16 + (lane & 1) * 8 + (lane >> 2)] = lane & 1 ? ex[1] : ex[0];
                if (lane < 4) mbar_arrive_cluster(mapa(bar_empty, lane & 1) + (2 + (lane >> 1)) * 8);
                __syncwarp();
            }
            if (gen) {
#pragma unroll
                for (int k = 0; k < 24; k++)
#pragma unroll
                    for (int j = 0; j < 4; j++) a[k][j] = bf2_mul(a[k][j], (268u - ex[j & 1]) * 0x00800080u);
            }
#pragma unroll
            for (int k = 0; k < 24; k++)
#pragma unroll
                for (int j = 0; j < 4; j++) {
                    a[k][j] = bf2_as_h2(bf2_mul(a[k][j], 0x07800780u));
                    asm volatile("" : "+r"(a[k][j]));
                }
            TRACEW(110 + warp, 6);
        }
#pragma unroll
        for (int j = 0; j < 4; j++)
            asm volatile("st.shared.u32 [%0], %1;\n" ::"r"(sbase + P1_OFF_A + warp * 512 + (j & 1) * 256 + (j >> 1) * 128 + lane * 4), "r"(a[23][j]) : "memory");
        asm volatile("fence.proxy.async.shared::cta;\n" ::: "memory");
        if (wg == 0) bar_sync(8, 256);
        TRACEW(110 + warp, 7);
        const uint32_t ex2 = ex[0] | ex[1] << 16;
        p1_consumer(a, gen ? 0x7f007f00u - (ex2 << 7) : (0x008e008eu - ex2) << 10, gen, sbase, wg, nwg, cb0 + wg, first, w, lane, zero);
        TSTAMP(0, 30);
    }
}

#define P2_NB_ 5
#define P2_NA_ 5
#define P2_DELTA_ 7
#define P2_EXTRA 0
#define P2_HSLEEP 64
#define P2_PSLEEP 100
#define P2_T0 5
#define P2_TS 11
constexpr int P2_B = 24576, P2_NB = P2_NB_;
constexpr int P2_A = 3072, P2_NA = P2_NA_;
constexpr int P2_XROW = C_DIM * 2;
constexpr int P2_OFF_A = P2_B * P2_NB;
constexpr int P2_OFF_X = P2_OFF_A + 3 * P2_NA * P2_A;
constexpr int P2_XHALF = 32 * P2_XROW + 64;
constexpr int P2_OFF_BIAS = P2_OFF_X + 64 * P2_XROW + 64;
constexpr int P2_OFF_GRN = P2_OFF_BIAS + C_DIM * 4;
constexpr int P2_OFF_BAR = P2_OFF_GRN + HID * 2;
constexpr int P2_SMEM = P2_OFF_BAR + (2 * P2_NB + 6 * P2_NA + 3) * 8;
#define P2_LAG_ 17
constexpr int P2_LAG = P2_LAG_;
constexpr int P2_NCL = NUM_CTAS / 2, P2_ITEMS = NT128 / P2_NCL, P2_SHARED = NT128 - P2_ITEMS * P2_NCL;
constexpr int P2_POS = P2_LAG * (P2_ITEMS - 1) + 48;
__device__ __forceinline__ int p2_start(int n) { return n < 0 ? 0 : n == P2_ITEMS ? P2_POS - 24 : P2_LAG * n; }
constexpr int P2_FOLD = 17;
constexpr int P2_XC = 8 * P2_XROW;
constexpr int P2_DELTA = P2_DELTA_;
__device__ __forceinline__ int p2_tile(int cl, int n) {
    return n == 0 ? NT128 - 1 - cl : n < 0 || n == P2_ITEMS ? NT128 - 1 - P2_NCL - (cl >> 1) : cl + P2_NCL * (n - 1);
}

constexpr int P2_EG = 2;
__device__ __forceinline__ void p2_epilogue(const uint32_t (&acc0)[48], const uint32_t (&acc1)[48], uint32_t sx, uint32_t sb, float up, int zero) {
    uint32_t v[2][P2_EG][4];
    float b[2][8];
    auto load = [&](int c, uint32_t a) {
#pragma unroll
        for (int j = 0; j < 2; j++)
            asm volatile("ld.shared.v4.f32 {%0,%1,%2,%3}, [%4];\n" : "=f"(b[c & 1][4 * j]), "=f"(b[c & 1][4 * j + 1]), "=f"(b[c & 1][4 * j + 2]), "=f"(b[c & 1][4 * j + 3])
                         : "r"(sb + c * 128 + j * 16) : "memory");
#pragma unroll
        for (int j = 0; j < P2_EG; j++) {
            const int u = c * P2_EG + j;
            asm volatile("ld.shared.v4.u32 {%0,%1,%2,%3}, [%4];\n" : "=r"(v[c & 1][j][0]), "=r"(v[c & 1][j][1]), "=r"(v[c & 1][j][2]), "=r"(v[c & 1][j][3])
                         : "r"(a + (u >> 1) * 64 + (u & 1) * 4 * P2_XROW) : "memory");
        }
    };
    load(0, sx);
#pragma unroll
    for (int c = 0; c < 24 / P2_EG; c++) {
        if (c + 1 < 24 / P2_EG) load(c + 1, sx + (v[c & 1][P2_EG - 1][0] & zero));
#pragma unroll
        for (int j = 0; j < P2_EG; j++) {
            const int u = c * P2_EG + j, i = 8 * ((u >> 1) % 6) + (u & 1);
            const uint32_t (&acc)[48] = u < 12 ? acc0 : acc1;
            uint32_t (&w)[4] = v[c & 1][j];
#pragma unroll
            for (int e = 0; e < 4; e++)
                w[e] = bf2_add(pack_bf16(fmaf(h_lo(acc[i + 2 * e]), up, b[c & 1][2 * e]), fmaf(h_hi(acc[i + 2 * e]), up, b[c & 1][2 * e + 1])), w[e]);
            asm volatile("st.shared.v4.u32 [%4], {%0,%1,%2,%3};\n" ::"r"(w[0]), "r"(w[1]), "r"(w[2]), "r"(w[3]),
                         "r"(sx + (u >> 1) * 64 + (u & 1) * 4 * P2_XROW) : "memory");
        }
    }
}

__device__ __forceinline__ void p2_unpack(uint4& u, uint32_t o1, uint32_t o2, uint32_t o3) {
    u.z = o1 & 0xbff8bff8u;
    u.y = o2 & 0xbff8bff8u;
    u.w = o3 & 0xbff8bff8u;
    u.x = (__byte_perm(o1, 0, 0x2301) & 0x07400740u) | ((__byte_perm(o2, o3, 0x6240) << 3) & 0x38383838u) | ((__byte_perm(o2, o3, 0x3715) << 1) & 0x80808080u);
}
__device__ __forceinline__ uint32_t h2_mul(uint32_t a, uint32_t b) {
    uint32_t r;
    asm("mul.rn.f16x2 %0, %1, %2;\n" : "=r"(r) : "r"(a), "r"(b));
    return r;
}
__device__ __forceinline__ void p2_epilogue_add(const uint32_t (&acc)[48], uint8_t* o, float f, int zero) {
#pragma unroll
    for (int t = 0; t < 12; t++) {
        uint32_t v[4];
#pragma unroll
        for (int e = 0; e < 4; e++) {
            v[e] = acc[8 * (t >> 1) + (t & 1) + 2 * e];
            asm volatile("" : "+r"(v[e]));
            v[e] = pack_bf16(h_lo(v[e]) * f, h_hi(v[e]) * f);
        }
        asm volatile("red.global.add.noftz.v4.bf16x2 [%0], {%1,%2,%3,%4};\n" ::"l"(o + (t >> 1) * 64 + (t & 1) * 4 * P2_XROW),
                     "r"(v[0]), "r"(v[1]), "r"(v[2]), "r"(v[3]) : "memory");
        if (t % 3 == 2) sched_break(zero);
    }
}

__global__ void __cluster_dims__(2, 1, 1) __launch_bounds__(512, 1)
pass2_kernel(const __nv_bfloat16* __restrict__ x, const __nv_bfloat16* __restrict__ grn_g, __nv_bfloat16* __restrict__ out, int zero) {
    extern __shared__ __align__(1024) uint8_t smem[];
    const uint32_t sbase = smem_u32(smem);
    const uint32_t bar_bfull = sbase + P2_OFF_BAR, bar_bempty = bar_bfull + P2_NB * 8;
    const uint32_t bar_afull = bar_bempty + P2_NB * 8, bar_aempty = bar_afull + 3 * P2_NA * 8;
    const uint32_t bar_xfull = bar_aempty + 3 * P2_NA * 8, bar_oready = bar_xfull + 8, s_pos = bar_xfull + 16;
    int tid;
    asm volatile("mov.u32 %0, %%tid.x;\n" : "=r"(tid));
    const int warp = __shfl_sync(0xffffffffu, tid >> 5, 0), lane = tid & 31;
    const uint32_t rank = cluster_rank();
    const int cl = blockIdx.x >> 1, pair = cl >> 1;
    const int k0 = (4 * pair + (cl & 1) * (48 - P2_POS % 48)) % 48;
    const int head = pair < P2_SHARED && !(cl & 1), tail = pair < P2_SHARED && (cl & 1);

    uint32_t par, gg[4];
    float pre[4];
    if (warp < 12) {
        asm volatile("ld.global.cg.u32 %0, [%1];\n" : "=r"(par) : "l"(&g_par) : "memory");
#pragma unroll
        for (int i = 0; i < 4; i++) {
            asm volatile("ld.global.cg.f32 %0, [%1];\n" : "=f"(pre[i]) : "l"(&g_sums[i & 1][HID + (i >> 1) * C_DIM + tid]) : "memory");
            asm volatile("ld.global.nc.u16 %0, [%1];\n" : "=r"(gg[i]) : "l"(grn_g + tid + 384 * i) : "memory");
        }
    }
    TSTAMP(1, 0);
    if (tid == 384) {
        for (int i = 0; i < P2_NB; i++) {
            mbar_init(bar_bfull + i * 8, 1);
            mbar_init(bar_bempty + i * 8, 24);
        }
        for (int i = 0; i < 3 * P2_NA; i++) {
            mbar_init(bar_afull + i * 8, 1);
            mbar_init(bar_aempty + i * 8, 4);
        }
        mbar_init(bar_xfull, 2);
        mbar_init(bar_oready, 4);
        asm volatile("st.shared.u32 [%0], 0;\n" ::"r"(s_pos) : "memory");
        asm volatile("fence.mbarrier_init.release.cluster;\n" ::: "memory");
    }
    __syncthreads();
    cluster_sync_relaxed();

    if (warp >= 12) {
        reg_dec<32>();
        if (warp == 12) {
            const uint8_t* wsrc = reinterpret_cast<const uint8_t*>(g_w2img) + rank * (P2_B / 2);
            int st = 0, ph = 1, kb = k0, m = 0, r = 0;
            const int busy = head ? 0 : tail ? P2_POS - 24 : P2_POS;
#pragma unroll 1
            for (int p = 0; p < P2_POS; p++) {
                if (p == 0 || p == P2_FOLD) {
                    flag_wait<true>(&g_img[p != 0], p ? 96 * 4 : 48);
                    asm volatile("fence.proxy.async.global;\n" ::: "memory");
                    if (p) wsrc += sizeof(g_w2img[0]);
                }
                mbar_wait(bar_bempty + st * 8, ph);
                TR2P(p, 0);
                if (elect_one()) {
                    mbar_expect_tx(bar_bfull + st * 8, P2_B);
                    bulk_g2s_mc(sbase + st * P2_B + rank * (P2_B / 2), wsrc + kb * P2_B, P2_B / 2, bar_bfull + st * 8, (uint16_t)3);
                    asm volatile("st.volatile.shared.u32 [%0], %1;\n" ::"r"(s_pos), "r"(p) : "memory");
                    const int idle = 2 - min(m, P2_ITEMS - 1) + max(m - 2 + (r >= 48 - 2 * P2_LAG), 0) - ((unsigned)(p - busy) < 24);
                    if (idle) asm volatile("mbarrier.arrive.shared::cta.b64 _, [%0], %1;\n" ::"r"(bar_bempty + st * 8), "r"(idle * 8) : "memory");
                    if (rank == 0) asm volatile("red.relaxed.gpu.global.add.u32 [%0], 1;\n" ::"l"(&g_prog) : "memory");
                }
                __syncwarp();
                if (++st == P2_NB) { st = 0; ph ^= 1; }
                if (++kb == 48) kb = 0;
                if (++r == P2_LAG) { r = 0; m++; }
            }
            mbar_wait(bar_bempty + st * 8, ph);
            if (lane == 0) mbar_arrive(bar_bfull + st * 8);
#pragma unroll 1
            for (int p = 1; p < P2_NB; p++) {
                if (++st == P2_NB) { st = 0; ph ^= 1; }
                mbar_wait(bar_bempty + st * 8, ph);
            }
        } else if (warp == 13) {
            const uint8_t* src[3];
            int n[3], left[3], wrap[3];
            uint32_t st[3];
            auto item = [&](int w) {
                const int u = (k0 + p2_start(n[w])) % 48;
                left[w] = n[w] < 0 || n[w] == P2_ITEMS ? 24 : 48;
                wrap[w] = left[w] - (48 - u);
                src[w] = reinterpret_cast<const uint8_t*>(g_h) + (size_t)p2_tile(cl, n[w]) * (2 * H_TILE) + rank * H_HALF + u * H_STEP;
            };
#pragma unroll
            for (int w = 0; w < 3; w++) {
                n[w] = w == 2 && head ? -1 : w;
                st[w] = 0x80000000u;
                item(w);
            }
            gdc_wait();
#pragma unroll 1
            for (int done = 0; done < 3;) {
                bool idle = true;
#pragma unroll
                for (int w = 0; w < 3; w++) {
                    const uint32_t o = (st[w] & 0xff) + w * P2_NA * 8;
                    if (left[w] >= 0 && mbar_test(bar_aempty + o, st[w] >> 31)) {
                        idle = false;
                        if (left[w] == 0) {
                            if (lane == 0) mbar_arrive(bar_afull + o);
                            left[w] = -1;
                            done++;
                        } else {
                            if (elect_one()) {
                                mbar_expect_tx(bar_afull + o, P2_A);
                                bulk_g2s(sbase + P2_OFF_A + o * (P2_A / 8), src[w], P2_A, bar_afull + o);
                            }
                            __syncwarp();
                            src[w] += H_STEP;
                            st[w] += 8;
                            if ((st[w] & 0xff) == P2_NA * 8) st[w] ^= 0x80000000u | (P2_NA * 8);
                            if (--left[w] == wrap[w]) src[w] -= 48 * H_STEP;
                            if (left[w] == 0 && (n[w] += 3) < P2_ITEMS + tail) item(w);
                        }
                    }
                }
                if (idle) __nanosleep(P2_HSLEEP);
                SAFE_BREAK
            }
        } else if (warp == 14) {
            const uint32_t sx = sbase + P2_OFF_X;
            size_t o = 0;
            auto pace = [&](int target) {
                int v;
                while (true) {
                    asm volatile("ld.volatile.shared.u32 %0, [%1];\n" : "=r"(v) : "r"(s_pos) : "memory");
                    if (v * 16 >= target) break;
                    __nanosleep(P2_PSLEEP);
                    SAFE_BREAK
                }
            };
#pragma unroll 1
            for (int n = -head; n <= P2_ITEMS; n++) {
                const size_t on = (size_t)(2 * p2_tile(cl, n) + rank) * (64 * C_DIM * 2);
                const bool st = n + head > 0, ld = n < P2_ITEMS;
                if (st) mbar_wait(bar_oready, (n - 1 + head) & 1);
                TR2P(n + 1, 1);
                if (lane == 0) {
                    if (n == 1 && head) {
                        asm volatile("cp.async.bulk.wait_group 0;\nfence.proxy.async.global;\n" ::: "memory");
                        asm volatile("st.release.gpu.global.u32 [%0], 1;\n" ::"l"(&g_half[pair][rank]) : "memory");
                    }
                    if (ld) mbar_expect_tx(bar_xfull, 64 * C_DIM * 2);
                    int t = st && n < P2_ITEMS - 1 ? (P2_LAG * (n - 1) + 48 + P2_T0 - 1) * 16 : -1024;
#pragma unroll 1
                    for (int c = 0; st && c < 64 * P2_XROW; c += P2_XC) {
                        pace(t += P2_TS);
                        bulk_s2g(reinterpret_cast<uint8_t*>(out) + o + c, sx + c + (c >= 32 * P2_XROW ? 64 : 0), P2_XC);
                    }
                    asm volatile("cp.async.bulk.commit_group;\ncp.async.bulk.wait_group.read 0;\n" ::: "memory");
#pragma unroll 1
                    for (int c = 0; ld && c < 64 * P2_XROW; c += P2_XC) {
                        pace(t += P2_TS);
                        bulk_g2s(sx + c + (c >= 32 * P2_XROW ? 64 : 0), reinterpret_cast<const uint8_t*>(x) + on + c, P2_XC, bar_xfull);
                    }
                    TR2P(n + 1, 2);
                    if (rank == 0 && n > 0 && n < P2_ITEMS - 2)
                        flag_wait<false>(&g_prog, P2_NCL * (P2_LAG * n + 48 + P2_EXTRA) + (tail ? P2_SHARED - P2_NCL : P2_SHARED) * P2_DELTA);
                    if (ld) mbar_arrive(bar_xfull);
                    TR2P(n + 1, 3);
                }
                __syncwarp();
                o = on;
            }
            asm volatile("cp.async.bulk.wait_group 0;\n" ::: "memory");
            TR2P(30, 1);
        }
    } else {
        reg_inc<160>();
        const int wg = warp >> 2, w = warp & 3, g = lane >> 2, q = lane & 3;
        const uint32_t sx = sbase + P2_OFF_X + (g & 1) * P2_XHALF + (w * 8 + (g >> 1)) * P2_XROW + q * 16;
        const uint32_t af = bar_afull + wg * P2_NA * 8, ae = bar_aempty + wg * P2_NA * 8;
        const uint32_t s_a = sbase + P2_OFF_A - bar_afull * (P2_A / 8) + (lane >> 3) * 512 + (lane & 7) * 64 +
                             ((w ^ ((lane & 7) >> 1)) << 4);
        uint32_t acc0[48], acc1[48];
        float up;
        uint4 a0[2], a1[2];
        int st = 0, ph = 0;

        {
            float4* s_red = reinterpret_cast<float4*>(smem + P2_OFF_BIAS);
            const float* sums = g_sums[par];
            float gx[4], part = 0.f, mx = 0.f;
            TSTAMP(1, 27);
            gdc_wait();
            TSTAMP(1, 1);
#pragma unroll
            for (int i = 0; i < 4; i++) gx[i] = __ldcg(sums + tid + 384 * i);
            if (blockIdx.x == 120 && tid < (LN_RING + 3) * 2) (&g_flag[0][0][0])[tid * 8] = 0;
            if (blockIdx.x == 121 && tid == 0) atomicAdd(&g_epoch, 1u);
            float z = __uint_as_float(__reduce_max_sync(0xffffffffu, __float_as_uint(pre[2] + pre[3])));
#pragma unroll
            for (int i = 0; i < 4; i++) {
                asm("sqrt.approx.f32 %0, %1;\n" : "=f"(gx[i]) : "f"(fmaf(gx[i], HSCALE * HSCALE, 1e-6f)));
                part += gx[i];
                gx[i] *= bf_lo(gg[i]);
                mx = fmaxf(mx, fabsf(gx[i]));
            }
#pragma unroll
            for (int o = 16; o > 0; o >>= 1) part += __shfl_xor_sync(0xffffffffu, part, o);
            mx = __uint_as_float(__reduce_max_sync(0xffffffffu, __float_as_uint(mx)));
            TSTAMP(1, 26);
            if (lane == 0) s_red[warp] = make_float4(part, mx, z, 0.f);
            bar_sync(1, 384);
            float tot = 0.f;
            {
                const float4 t = s_red[min(lane & 15, 11)];
                tot = (lane & 15) < 12 ? t.x : 0.f;
#pragma unroll
                for (int o = 8; o > 0; o >>= 1) tot += __shfl_xor_sync(0xffffffffu, tot, o);
                mx = __uint_as_float(__reduce_max_sync(0xffffffffu, __float_as_uint(t.y)));
                z = __uint_as_float(__reduce_max_sync(0xffffffffu, __float_as_uint(t.z)));
            }
            const float inv = __fdividef(1.0f, fmaf(tot, 1.0f / HID, 1e-6f));
            const uint32_t j = max(__float_as_uint(fmaf(mx, inv, 1.0f) * 1.01f) >> 23, 130u) - 130u;
            const float dn = __uint_as_float((127u - j) << 23);
#pragma unroll
            for (int i = 0; i < 4; i++)
                *reinterpret_cast<uint16_t*>(smem + P2_OFF_GRN + (tid + 384 * i) * 2) = pack_f16(fmaf(gx[i], inv, 1.0f) * dn, 0.f);
            up = (HSCALE * 1.00235f) * __uint_as_float(min(acc_exp(z) - 9u + j, 253u) << 23);
            TSTAMP(1, 25);
            bar_sync(1, 384);
            reinterpret_cast<float*>(smem + P2_OFF_BIAS)[tid] = pre[0] + pre[1];
            if (wg == 1 && blockIdx.x < 96) {
                const uint4* src = g_w2img[0] + blockIdx.x * 768 + tid - 128;
                const uint4 fk = *reinterpret_cast<const uint4*>(smem + P2_OFF_GRN + blockIdx.x * 32 + (tid & 8) * 2);
                uint4 v[6];
#pragma unroll
                for (int i = 0; i < 6; i++) v[i] = __ldcg(src + i * 128);
                auto fold = [&](uint32_t b, uint32_t f) { return (h2_mul(b, f) + 0x00040004u) & 0xfff8fff8u; };
#pragma unroll
                for (int i = 0; i < 6; i++)
                    g_w2img[1][blockIdx.x * 768 + tid - 128 + i * 128] = make_uint4(fold(v[i].x, fk.x), fold(v[i].y, fk.y), fold(v[i].z, fk.z), fold(v[i].w, fk.w));
                asm volatile("fence.proxy.async.global;\n" ::: "memory");
                __threadfence();
                __syncwarp();
                if (lane == 0) asm volatile("red.release.gpu.global.add.u32 [%0], 1;\n" ::"l"(&g_img[1]) : "memory");
            }
        }
        TSTAMP(1, 28);
        int kt = k0, pos;
        const int who = __shfl_sync(0xffffffffu, lane == 2 ? 0 : lane < 2 ? 1 : 2, lane);
        const uint32_t rel0 = who ? mapa(bar_bempty, lane & 1) : mapa(ae, rank), rel1 = rel0 + (who ? P2_NB : P2_NA) * 8;
        uint32_t rel = rel1 - 8;
        auto next_rel = [&](bool go) {
            if (go) rel += 8;
            if (rel == rel1) rel = rel0;
        };
        auto release_b = [&]() {
            next_rel(who == 1);
            if (who == 1) mbar_arrive_cluster(rel);
        };
        auto seek = [&](int p) {
            pos = p;
            st = p % P2_NB;
            ph = p / P2_NB & 1;
            if (who == 1) rel = (st ? rel0 + st * 8 : rel1) - 8;
            int v;
            while (true) {
                asm volatile("ld.volatile.shared.u32 %0, [%1];\n" : "=r"(v) : "r"(s_pos) : "memory");
                if (v >= p) break;
                __nanosleep(200);
                SAFE_BREAK
            }
        };
        auto publish = [&]() {
            asm volatile("fence.proxy.async.shared::cta;\n" ::: "memory");
            __syncwarp();
            if (who == 0) mbar_arrive(bar_oready);
        };
        bool ok_a;
        uint32_t abar = af, pa = 0;
        auto fetch = [&](uint4 (&a)[2], bool early) {
            const uint32_t src = s_a + abar * (P2_A / 8);
            abar += 8;
            if (abar == af + P2_NA * 8) { abar = af; pa ^= 0x80000000u; }
            const bool ok_b = mbar_test(bar_bfull + st * 8, ph);
            ok_a = mbar_test(abar, pa >> 31);
            uint32_t o[6];
            asm volatile("ldmatrix.sync.aligned.m8n8.x4.trans.shared.b16 {%0,%1,%2,%3}, [%4];\n"
                         : "=r"(o[0]), "=r"(o[1]), "=r"(o[2]), "=r"(o[3]) : "r"(src) : "memory");
            asm volatile("ldmatrix.sync.aligned.m8n8.x2.trans.shared.b16 {%0,%1}, [%2];\n"
                         : "=r"(o[4]), "=r"(o[5]) : "r"(src + 2048) : "memory");
            p2_unpack(a[0], o[0], o[1], o[2]);
            p2_unpack(a[1], o[3], o[4], o[5]);
            if (early) {
                const uint32_t* t = reinterpret_cast<const uint32_t*>(smem + P2_OFF_GRN) + kt * 16 + q;
#pragma unroll
                for (int i = 0; i < 2; i++)
                    a[i] = make_uint4(h2_mul(a[i].x, t[8 * i]), h2_mul(a[i].y, t[8 * i]), h2_mul(a[i].z, t[8 * i + 4]), h2_mul(a[i].w, t[8 * i + 4]));
                if (++kt == 48) kt = 0;
            }
            if (!ok_b) mbar_wait(bar_bfull + st * 8, ph);
        };
        auto step = [&](const uint4 (&a)[2], uint4 (&an)[2], int thr, bool early) {
            TR2(0);
            const uint64_t db = make_desc(sbase + st * P2_B, 128, 256);
            wg_fence();
            mma_rs_n192(acc0, a[0], db, thr - 1);
            mma_rs_n192(acc1, a[0], db + 384, thr - 1);
            mma_rs_n192(acc0, a[1], db + 768, 1);
            mma_rs_n192(acc1, a[1], db + 768 + 384, 1);
            wg_commit();
            next_rel(who < thr);
            if (++st == P2_NB) { st = 0; ph ^= 1; }
            wg_wait<1>();
            if (!ok_a) {
                if (who < thr) mbar_arrive_cluster(rel);
                thr = 0;
                mbar_wait(abar, pa >> 31);
            }
            if (who < thr) mbar_arrive_cluster(rel);
            fetch(an, early);
            pos++;
        };
        int n = wg == 2 && head ? -1 : wg;
        mbar_wait(af, 0);
        seek(p2_start(n));
        fetch(a0, n <= 0);
#pragma unroll 1
        for (;; n += 3) {
            TSTAMP(1, 2 + n);
            const int p0 = n < 0 || n == P2_ITEMS ? 12 : 0, pe = n <= 0 ? p0 + P2_FOLD / 2 : 0;
            const bool more = n + 3 < P2_ITEMS + tail;
#pragma unroll 1
            for (int p = p0; p < 24; p++) {
                step(a0, a1, p == p0 ? 1 : 2, p < pe);
                step(a1, a0, 2, p < pe);
            }
            if (n == P2_ITEMS) {
                flag_wait<true>(&g_half[pair][rank], 1);
                TR2(1);
                wg_wait<0>();
                TR2(2);
                release_b();
                uint8_t* o = reinterpret_cast<uint8_t*>(out) + (size_t)((2 * p2_tile(cl, -1) + rank) * 64 + (g & 1) * 32 + w * 8 + (g >> 1)) * P2_XROW + q * 16;
                p2_epilogue_add(acc0, o, up, zero);
                p2_epilogue_add(acc1, o + 384, up, zero);
                TR2(3);
                break;
            }
            mbar_wait(bar_xfull, (n + head) & 1);
            TR2(1);
            wg_wait<0>();
            TR2(2);
            release_b();
            __syncwarp();
            p2_epilogue(acc0, acc1, sx, sbase + P2_OFF_BIAS + q * 32, up, zero);
            TR2(3);
            publish();
            if (!more) break;
            seek(p2_start(n + 3));
            mbar_wait(bar_bfull + st * 8, ph);
        }
        TSTAMP(1, 30);
    }
}

}

extern "C" void kernel_launch(void* const* d_in, const int* in_sizes, int n_in, void* d_out, int out_size) {
    const __nv_bfloat16* x = (const __nv_bfloat16*)d_in[0];
    const __nv_bfloat16* dw = (const __nv_bfloat16*)d_in[1];
    const __nv_bfloat16* w1 = (const __nv_bfloat16*)d_in[2];
    const __nv_bfloat16* w2 = (const __nv_bfloat16*)d_in[3];
    const __nv_bfloat16* grn_g = (const __nv_bfloat16*)d_in[4];
    const __nv_bfloat16* grn_b = (const __nv_bfloat16*)d_in[5];
    __nv_bfloat16* out = (__nv_bfloat16*)d_out;

    cudaFuncSetAttribute(pass1_kernel, cudaFuncAttributeMaxDynamicSharedMemorySize, P1_SMEM);
    cudaFuncSetAttribute(pass2_kernel, cudaFuncAttributeMaxDynamicSharedMemorySize, P2_SMEM);

    typedef CUresult (*EncodeFn)(CUtensorMap*, CUtensorMapDataType, cuuint32_t, void*, const cuuint64_t*, const cuuint64_t*,
                                 const cuuint32_t*, const cuuint32_t*, CUtensorMapInterleave, CUtensorMapSwizzle,
                                 CUtensorMapL2promotion, CUtensorMapFloatOOBfill);
    static EncodeFn encode = nullptr;
    if (!encode) {
        cudaDriverEntryPointQueryResult qres;
        cudaGetDriverEntryPoint("cuTensorMapEncodeTiled", (void**)&encode, cudaEnableDefault, &qres);
    }
    CUtensorMap wmap;
    const cuuint64_t gdim[2] = {HID, C_DIM};
    const cuuint64_t gstr[1] = {HID * 2};
    const cuuint32_t box[2] = {64, 64}, estr[2] = {1, 1};
    CUresult er = encode(&wmap, CU_TENSOR_MAP_DATA_TYPE_BFLOAT16, 2, (void*)w1, gdim, gstr, box, estr, CU_TENSOR_MAP_INTERLEAVE_NONE,
           CU_TENSOR_MAP_SWIZZLE_128B, CU_TENSOR_MAP_L2_PROMOTION_L2_128B, CU_TENSOR_MAP_FLOAT_OOB_FILL_NONE);
    if (er != CUDA_SUCCESS) printf("tensor map encode failed %d\n", (int)er);

    pass1_kernel<<<NUM_CTAS, 512, P1_SMEM>>>(wmap, x, dw, w1, w2, grn_b, 0);

    cudaLaunchAttribute attr[1];
    attr[0].id = cudaLaunchAttributeProgrammaticStreamSerialization;
    attr[0].val.programmaticStreamSerializationAllowed = 1;
    cudaLaunchConfig_t cfg = {};
    cfg.gridDim = dim3(NUM_CTAS);
    cfg.stream = 0;
    cfg.attrs = attr;
    cfg.numAttrs = 1;
    cfg.blockDim = dim3(512);
    cfg.dynamicSmemBytes = P2_SMEM;
    cudaLaunchKernelEx(&cfg, pass2_kernel, x, grn_g, out, 0);
}
```

```cpp
#include <cuda.h>
#include <cuda_runtime.h>
#include <cuda_bf16.h>
#include <stdint.h>
#include <stdio.h>

namespace {

constexpr int M_TOTAL = 384 * 384;
constexpr int C_DIM   = 384;
constexpr int HID     = 1536;
constexpr int NT128   = M_TOTAL / 128;
constexpr int NUM_CTAS = 132;

constexpr int NGRP = 15, NFIRST = NGRP + 1;
#define LN_DEPTH 2
constexpr int LN_STEP = NUM_CTAS / 4, LN_RING = LN_DEPTH * LN_STEP;
constexpr int NT_RING = NT128 - NFIRST;
#define P1_M 51
#define P1_D 5
__device__ __forceinline__ int p1_tile(int t, bool small) {
    return t + (small ? ((t + 1) * P1_M + P1_D - 1) / P1_D : t * P1_D / P1_M);
}
constexpr int LN_TILE = 128 * C_DIM * 2;
constexpr int H_TILE = 64 * HID * 3 / 2;
constexpr int H_HALF = 3072, H_STEP = 6144;

__device__ __align__(1024) uint4 g_h[(size_t)M_TOTAL * HID * 3 / 32];
__device__ __align__(1024) uint4 g_ln[LN_RING * LN_TILE / 16];
__device__ __align__(1024) uint4 g_w2img[2][HID * C_DIM * 2 / 16];
__device__ __align__(16) float g_sums[2][HID + 2 * C_DIM];
__device__ __align__(16) unsigned g_ex[HID];
__device__ unsigned g_epoch, g_par;
__device__ __align__(128) unsigned g_img[2];
__device__ __align__(128) unsigned g_prog;
__device__ __align__(128) unsigned g_half[32][2];
__device__ unsigned g_flag[LN_RING + 3][2][8];
#define TSTAMP(k, i)
#define TRACE(wg, pos, i)
#define TRACEW(pos, i)

#define TR2(i)
#define TR2P(pos, i)
__host__ __device__ __forceinline__ int perm32(int n) {
    return (n & ~31) | (((n >> 1) & 3) << 3) | (((n >> 3) & 3) << 1) | (n & 1);
}

__device__ __forceinline__ uint32_t smem_u32(const void* p) { return (uint32_t)__cvta_generic_to_shared(p); }

__device__ __forceinline__ void mbar_init(uint32_t bar, uint32_t count) {
    asm volatile("mbarrier.init.shared::cta.b64 [%0], %1;\n" ::"r"(bar), "r"(count) : "memory");
}
__device__ __forceinline__ void mbar_expect_tx(uint32_t bar, uint32_t bytes) {
    asm volatile("mbarrier.arrive.expect_tx.shared::cta.b64 _, [%0], %1;\n" ::"r"(bar), "r"(bytes) : "memory");
}
__device__ __forceinline__ void mbar_arrive(uint32_t bar) {
    asm volatile("mbarrier.arrive.shared::cta.b64 _, [%0];\n" ::"r"(bar) : "memory");
}
__device__ __forceinline__ void mbar_arrive_cluster(uint32_t bar_cluster_addr) {
    asm volatile("mbarrier.arrive.shared::cluster.b64 _, [%0];\n" ::"r"(bar_cluster_addr) : "memory");
}
#define SAFE_BREAK
__device__ __forceinline__ void mbar_wait(uint32_t bar, uint32_t parity) {
    asm volatile(
        "{\n"
        ".reg .pred p;\n"
        "LAB_WAIT:\n"
        "mbarrier.try_wait.parity.shared::cta.b64 p, [%0], %1;\n"
        "@!p bra LAB_WAIT;\n"
        "}\n" ::"r"(bar), "r"(parity) : "memory");
}
__device__ __forceinline__ bool mbar_test(uint32_t bar, uint32_t parity) {
    uint32_t ok;
    asm volatile("{\n.reg .pred p;\n"
                 "mbarrier.test_wait.parity.shared::cta.b64 p, [%1], %2;\n"
                 "selp.u32 %0, 1, 0, p;\n}\n" : "=r"(ok) : "r"(bar), "r"(parity) : "memory");
    return ok != 0;
}
__device__ __forceinline__ uint32_t mapa(uint32_t addr, uint32_t rank) {
    uint32_t r;
    asm volatile("mapa.shared::cluster.u32 %0, %1, %2;\n" : "=r"(r) : "r"(addr), "r"(rank));
    return r;
}
__device__ __forceinline__ void bulk_g2s(uint32_t dst, const void* src, uint32_t bytes, uint32_t bar) {
    asm volatile("cp.async.bulk.shared::cluster.global.mbarrier::complete_tx::bytes [%0], [%1], %2, [%3];\n"
                 ::"r"(dst), "l"(src), "r"(bytes), "r"(bar) : "memory");
}
__device__ __forceinline__ void bulk_g2s_mc(uint32_t dst, const void* src, uint32_t bytes, uint32_t bar, uint16_t mask) {
    asm volatile("cp.async.bulk.shared::cluster.global.mbarrier::complete_tx::bytes.multicast::cluster [%0], [%1], %2, [%3], %4;\n"
                 ::"r"(dst), "l"(src), "r"(bytes), "r"(bar), "h"(mask) : "memory");
}
__device__ __forceinline__ void tma2(uint32_t dst, const CUtensorMap* map, int c0, int c1, uint32_t bar) {
    asm volatile("cp.async.bulk.tensor.2d.shared::cluster.global.tile.mbarrier::complete_tx::bytes [%0], [%1, {%2, %3}], [%4];\n"
                 ::"r"(dst), "l"(map), "r"(c0), "r"(c1), "r"(bar) : "memory");
}
template <bool ACQ>
__device__ __forceinline__ uint32_t flag_wait(const unsigned* p, unsigned target) {
    unsigned v, n = 0;
    do {
        if (ACQ) asm volatile("ld.acquire.gpu.global.u32 %0, [%1];\n" : "=r"(v) : "l"(p) : "memory");
        else asm volatile("ld.relaxed.gpu.global.u32 %0, [%1];\n" : "=r"(v) : "l"(p) : "memory");
        n++;
    } while (v < target);
    return n == 1;
}
__device__ __forceinline__ void ldsm4t(uint32_t (&r)[4], uint32_t addr) {
    asm volatile("ldmatrix.sync.aligned.m8n8.x4.trans.shared.b16 {%0,%1,%2,%3}, [%4];\n"
                 : "=r"(r[0]), "=r"(r[1]), "=r"(r[2]), "=r"(r[3]) : "r"(addr) : "memory");
}
__device__ __forceinline__ void bulk_s2g(void* dst, uint32_t src, uint32_t bytes) {
    asm volatile("cp.async.bulk.global.shared::cta.bulk_group [%0], [%1], %2;\n" ::"l"(dst), "r"(src), "r"(bytes) : "memory");
}
__device__ __forceinline__ void cluster_sync_relaxed() {
    asm volatile("barrier.cluster.arrive.relaxed.aligned;\nbarrier.cluster.wait.aligned;\n" ::: "memory");
}
__device__ __forceinline__ void gdc_wait() { asm volatile("griddepcontrol.wait;\n" ::: "memory"); }
__device__ __forceinline__ void gdc_launch() { asm volatile("griddepcontrol.launch_dependents;\n" ::: "memory"); }
__device__ __forceinline__ uint32_t cluster_rank() {
    uint32_t r;
    asm volatile("mov.u32 %0, %%cluster_ctarank;\n" : "=r"(r));
    return r;
}
__device__ __forceinline__ bool elect_one() {
    uint32_t pred;
    asm volatile("{\n.reg .pred p;\nelect.sync _|p, 0xffffffff;\nselp.u32 %0, 1, 0, p;\n}\n" : "=r"(pred));
    return pred != 0;
}
__device__ __forceinline__ void wg_fence() { asm volatile("wgmma.fence.sync.aligned;\n" ::: "memory"); }
__device__ __forceinline__ void wg_commit() { asm volatile("wgmma.commit_group.sync.aligned;\n" ::: "memory"); }
template <int N> __device__ __forceinline__ void wg_wait() {
    asm volatile("wgmma.wait_group.sync.aligned %0;\n" ::"n"(N) : "memory");
}
template <int R> __device__ __forceinline__ void reg_inc() { asm volatile("setmaxnreg.inc.sync.aligned.u32 %0;\n" ::"n"(R)); }
template <int R> __device__ __forceinline__ void reg_dec() { asm volatile("setmaxnreg.dec.sync.aligned.u32 %0;\n" ::"n"(R)); }
__device__ __forceinline__ void bar_sync(int id, int n) { asm volatile("bar.sync %0, %1;\n" ::"r"(id), "r"(n) : "memory"); }
__device__ __forceinline__ void bar_arrive(int id, int n) { asm volatile("bar.arrive %0, %1;\n" ::"r"(id), "r"(n) : "memory"); }

__device__ __forceinline__ uint64_t make_desc(uint32_t saddr, uint32_t lbo, uint32_t sbo) {
    return (uint64_t)((saddr & 0x3FFFF) >> 4) | ((uint64_t)(lbo >> 4) << 16) | ((uint64_t)(sbo >> 4) << 32);
}

__device__ __forceinline__ void stg128_cs(void* p, uint32_t a, uint32_t b, uint32_t c, uint32_t d) {
    asm volatile("st.global.cs.v4.u32 [%0], {%1,%2,%3,%4};\n" ::"l"(p), "r"(a), "r"(b), "r"(c), "r"(d) : "memory");
}
__device__ __forceinline__ uint32_t pack_bf16(float lo, float hi) {
    uint32_t r;
    asm("cvt.rn.bf16x2.f32 %0, %1, %2;\n" : "=r"(r) : "f"(hi), "f"(lo));
    return r;
}
__device__ __forceinline__ float bf_lo(uint32_t v) { return __uint_as_float(v << 16); }
__device__ __forceinline__ float bf_hi(uint32_t v) { return __uint_as_float(v & 0xffff0000u); }
__device__ __forceinline__ uint32_t bf2_mul(uint32_t a, uint32_t b) {
    uint32_t r;
    asm("mul.rn.bf16x2 %0, %1, %2;\n" : "=r"(r) : "r"(a), "r"(b));
    return r;
}
__device__ __forceinline__ uint32_t bf2_fma(uint32_t a, uint32_t b, uint32_t c) {
    uint32_t r;
    asm("fma.rn.bf16x2 %0, %1, %2, %3;\n" : "=r"(r) : "r"(a), "r"(b), "r"(c));
    return r;
}
__device__ __forceinline__ uint32_t bf2_add(uint32_t a, uint32_t b) {
    uint32_t r;
    asm("add.rn.bf16x2 %0, %1, %2;\n" : "=r"(r) : "r"(a), "r"(b));
    return r;
}
constexpr float KAPPA = 0.3292034911525734f;
constexpr float GELU_C = 2.423681954311584f;
constexpr float HSCALE = 1.0f / (2.0f * KAPPA);
__device__ __forceinline__ uint32_t acc_exp(float z) { return max(__float_as_uint(z) >> 23, 10u); }
__device__ __forceinline__ void sched_break(int zero) {
    asm volatile("{\n.reg .pred p;\nsetp.ne.s32 p, %0, 0;\nSB_LOOP:\n@p nanosleep.u32 1;\n@p bra SB_LOOP;\n}\n" ::"r"(zero));
}

#define ACC8(d, o) "+f"(d[o + 0]), "+f"(d[o + 1]), "+f"(d[o + 2]), "+f"(d[o + 3]), "+f"(d[o + 4]), "+f"(d[o + 5]), "+f"(d[o + 6]), "+f"(d[o + 7])

#define ACCR8(d, o) "+r"(d[o + 0]), "+r"(d[o + 1]), "+r"(d[o + 2]), "+r"(d[o + 3]), "+r"(d[o + 4]), "+r"(d[o + 5]), "+r"(d[o + 6]), "+r"(d[o + 7])
__device__ __forceinline__ void mma_rs_n128(uint32_t (&d)[32], const uint32_t (&a)[4], uint64_t desc, int scale_d) {
    asm volatile(
        "{\n.reg .pred p;\nsetp.ne.b32 p, %37, 0;\n"
        "wgmma.mma_async.sync.aligned.m64n128k16.f16.f16.f16 "
        "{%0,%1,%2,%3,%4,%5,%6,%7,%8,%9,%10,%11,%12,%13,%14,%15,"
        "%16,%17,%18,%19,%20,%21,%22,%23,%24,%25,%26,%27,%28,%29,%30,%31},"
        "{%32,%33,%34,%35}, %36, p, 1, 1, 0;\n}\n"
        : ACCR8(d, 0), ACCR8(d, 8), ACCR8(d, 16), ACCR8(d, 24)
        : "r"(a[0]), "r"(a[1]), "r"(a[2]), "r"(a[3]), "l"(desc), "r"(scale_d));
}
__device__ __forceinline__ void mma_ss_n128(uint32_t (&d)[32], uint64_t da, uint64_t db) {
    asm volatile(
        "{\n.reg .pred p;\nsetp.ne.b32 p, %34, 0;\n"
        "wgmma.mma_async.sync.aligned.m64n128k16.f16.f16.f16 "
        "{%0,%1,%2,%3,%4,%5,%6,%7,%8,%9,%10,%11,%12,%13,%14,%15,"
        "%16,%17,%18,%19,%20,%21,%22,%23,%24,%25,%26,%27,%28,%29,%30,%31},"
        "%32, %33, p, 1, 1, 0, 0;\n}\n"
        : ACCR8(d, 0), ACCR8(d, 8), ACCR8(d, 16), ACCR8(d, 24)
        : "l"(da), "l"(db), "r"(1));
}
__device__ __forceinline__ uint32_t bf2_as_h2(uint32_t v) { return (v & 0x0fff0fffu) * 7u + v; }
__device__ __forceinline__ float h_lo(uint32_t v) {
    float r;
    asm("{\n.reg .b16 l, h;\nmov.b32 {l, h}, %1;\ncvt.f32.f16 %0, l;\n}\n" : "=f"(r) : "r"(v));
    return r;
}
__device__ __forceinline__ float h_hi(uint32_t v) {
    float r;
    asm("{\n.reg .b16 l, h;\nmov.b32 {l, h}, %1;\ncvt.f32.f16 %0, h;\n}\n" : "=f"(r) : "r"(v));
    return r;
}

__device__ __forceinline__ void mma_rs_n192(uint32_t (&d)[48], const uint4& a, uint64_t db, int scale_d) {
    asm volatile(
        "{\n.reg .pred p;\nsetp.ne.b32 p, %53, 0;\n"
        "wgmma.mma_async.sync.aligned.m64n192k16.f16.f16.f16 "
        "{%0,%1,%2,%3,%4,%5,%6,%7,%8,%9,%10,%11,%12,%13,%14,%15,"
        "%16,%17,%18,%19,%20,%21,%22,%23,%24,%25,%26,%27,%28,%29,%30,%31,"
        "%32,%33,%34,%35,%36,%37,%38,%39,%40,%41,%42,%43,%44,%45,%46,%47},"
        "{%48,%49,%50,%51}, %52, p, 1, 1, 0;\n}\n"
        : ACCR8(d, 0), ACCR8(d, 8), ACCR8(d, 16), ACCR8(d, 24), ACCR8(d, 32), ACCR8(d, 40)
        : "r"(a.x), "r"(a.y), "r"(a.z), "r"(a.w), "l"(db), "r"(scale_d));
}

__device__ __forceinline__ uint32_t pack_f16(float lo, float hi) {
    uint32_t r;
    asm("cvt.rn.f16x2.f32 %0, %1, %2;\n" : "=r"(r) : "f"(hi), "f"(lo));
    return r;
}

#define P1_IMG 900
constexpr int P1_SLOT = LN_TILE / 2, P1_NST = 4;
constexpr int P1_X = 16 * C_DIM * 2;
constexpr int P1_OFF_X = P1_SLOT * P1_NST;
constexpr int P1_OFF_A = P1_OFF_X + 2 * P1_X;
constexpr int P1_OFF_BAR = P1_OFF_A + 3 * 2048;
constexpr int P1_OFF_TILE = P1_OFF_BAR + (2 * P1_NST + 3 + 2 + 3 + 2) * 8;
constexpr int P1_OFF_DW = P1_OFF_TILE + 64;
constexpr int P1_OFF_RAW = P1_OFF_DW + C_DIM * 2;
constexpr int P1_SMEM = P1_OFF_RAW + 4 * C_DIM * 2;

__device__ __forceinline__ float rsqrt_fast(float x) {
    float r;
    asm("rsqrt.approx.ftz.f32 %0, %1;\n" : "=f"(r) : "f"(x));
    return r;
}
__device__ __forceinline__ float sum8(const uint32_t (&c)[4]) {
    const uint32_t u = bf2_add(bf2_add(c[0], c[1]), bf2_add(c[2], c[3]));
    return bf_lo(u) + bf_hi(u);
}
__device__ __forceinline__ void lds128(uint32_t (&v)[4], uint32_t a) {
    asm volatile("ld.shared.v4.u32 {%0,%1,%2,%3}, [%4];\n" : "=r"(v[0]), "=r"(v[1]), "=r"(v[2]), "=r"(v[3]) : "r"(a) : "memory");
}
template <class F>
__device__ __forceinline__ void ln_row(uint32_t (&v)[6][4], uint32_t sdw, F after_loads) {
    uint32_t c[4], s[4], d[4], nm;
#pragma unroll
    for (int i = 0; i < 6; i++) {
        lds128(d, sdw + i * 128);
        if (i == 0) {
#pragma unroll
            for (int k = 0; k < 4; k++) c[k] = bf2_mul(v[0][k], d[k]);
            const float p = sum8(c) * -0.125f;
            nm = pack_bf16(p, p);
        }
#pragma unroll
        for (int k = 0; k < 4; k++) {
            v[i][k] = bf2_fma(v[i][k], d[k], nm);
            s[k] = i ? bf2_add(v[i][k], s[k]) : v[i][k];
            c[k] = i ? bf2_fma(v[i][k], v[i][k], c[k]) : bf2_mul(v[i][k], v[i][k]);
        }
    }
    after_loads(c[0]);
    float m = fmaf(sum8(s), 1.0f / 48, -bf_lo(nm));
    float q = fmaf(-bf_lo(nm), fmaf(2.f, m, bf_lo(nm)), sum8(c) * (1.0f / 48));
#pragma unroll
    for (int o = 1; o < 8; o <<= 1) {
        m += __shfl_xor_sync(0xffffffffu, m, o);
        q += __shfl_xor_sync(0xffffffffu, q, o);
    }
    m *= 0.125f;
    const float r = KAPPA * rsqrt_fast(fmaxf(fmaf(-m, m, q * 0.125f), 0.f) + 1e-5f);
    const float e = (-bf_lo(nm) - m) * r * 0x1p-112f;
    const bool two = __any_sync(0xffffffffu, r < 0x1p-14f);
    const float r1 = r * (two ? 0x1p-56f : 0x1p-112f);
    uint32_t mul = pack_bf16(r1, r1), add = two ? 0u : pack_bf16(e, e);
#pragma unroll 1
    for (int it = !two; it < 2; it++) {
#pragma unroll
        for (int i = 0; i < 6; i++)
#pragma unroll
            for (int k = 0; k < 4; k++) v[i][k] = bf2_fma(v[i][k], mul, add);
        mul = 0x23802380u;
        add = pack_bf16(e, e);
    }
#pragma unroll
    for (int i = 0; i < 6; i++)
#pragma unroll
        for (int k = 0; k < 4; k++) v[i][k] = bf2_as_h2(v[i][k]);
}

__device__ __forceinline__ float gelu_s(float y) {
    float u = y * fmaf(y, y, GELU_C);
    float t;
    asm volatile("tanh.approx.f32 %0, %1;\n" : "=f"(t) : "f"(u));
    return fmaf(y, t, y);
}
__device__ __forceinline__ void p1_pack(int c, uint32_t (&p)[4], uint32_t (&dd)[4]) {
#pragma unroll
    for (int u = 0; u < 4; u++) {
        if ((c & 3) == 0) dd[u] = p[u];
        else {
            uint32_t n = dd[u];
            if ((c & 3) == 1) n = __byte_perm(n, 0, 0x2301);
            if ((c & 3) == 2) {
                dd[u] = __byte_perm(n >> 3, n >> 1, 0x6341);
                n = __byte_perm(n >> 3, n >> 1, 0x7250);
            }
            asm("lop3.b32 %0, %0, %1, 0x40074007, 0xd8;\n" : "+r"(p[u]) : "r"(n));
        }
    }
}
__device__ __forceinline__ void p1_store(int c, const uint32_t (&p)[4], uint8_t* hptr) {
    if (c & 3) stg128_cs(hptr + (c >> 2) * H_HALF + ((c & 3) - 1) * 512, p[0], p[1], p[2], p[3]);
}

template <bool GEN>
__device__ __forceinline__ void p1_epilogue(uint32_t (&acc)[32], float (&ssq)[2], uint32_t sc2, uint8_t* hp, int zero) {
    uint32_t sq[2], dd[4];
#pragma unroll
    for (int c = 0; c < 8; c++) {
        if (GEN) sched_break(zero);
        uint32_t p[4];
#pragma unroll
        for (int u = 0; u < 4; u++) {
            const uint32_t y = acc[8 * (c >> 1) + 2 * u + (c & 1)];
            if (GEN) {
                const float sc = c & 1 ? bf_hi(sc2) : bf_lo(sc2), fs = __uint_as_float(0x78000000u - __float_as_uint(sc));
                const float g0 = gelu_s(h_lo(y) * fs), g1 = gelu_s(h_hi(y) * fs);
                ssq[c & 1] = fmaf(g1, g1, fmaf(g0, g0, ssq[c & 1]));
                p[u] = pack_f16(g0 * sc, g1 * sc);
            } else {
                uint32_t g;
                asm("{\n.reg .b32 w;\n"
                    "fma.rn.f16x2 w, %1, %1, %2;\n"
                    "mul.rn.f16x2 w, w, %1;\n"
                    "tanh.approx.f16x2 w, w;\n"
                    "fma.rn.f16x2 %0, %1, w, %1;\n}\n" : "=r"(g) : "r"(y), "r"(0x40d940d9u));
                acc[8 * (c >> 1) + 2 * u + (c & 1)] = g;
                if (c < 2 && u == 0) asm("mul.rn.f16x2 %0, %1, %1;\n" : "=r"(sq[c & 1]) : "r"(g));
                else asm("fma.rn.f16x2 %0, %1, %1, %0;\n" : "+r"(sq[c & 1]) : "r"(g));
                if (c & 1) asm("{\n.reg .b16 l, h;\n.reg .b32 f;\nmov.b32 {l, h}, %2;\nmov.b32 f, {h, h};\nmul.rn.f16x2 %0, %1, f;\n}\n" : "=r"(p[u]) : "r"(g), "r"(sc2));
                else asm("{\n.reg .b16 l, h;\n.reg .b32 f;\nmov.b32 {l, h}, %2;\nmov.b32 f, {l, l};\nmul.rn.f16x2 %0, %1, f;\n}\n" : "=r"(p[u]) : "r"(g), "r"(sc2));
            }
        }
        p1_pack(c, p, dd);
        if (c & 3) {
#pragma unroll
            for (int u = 0; u < 4; u++) acc[4 * (c - 1 - (c >> 2)) + u] = p[u];
        }
        p1_store(c, p, hp);
    }
    if (!GEN) {
#pragma unroll
        for (int r = 0; r < 2; r++) ssq[r] += h_lo(sq[r]) + h_hi(sq[r]);
    }
}
__device__ __forceinline__ void p1_consumer(const uint32_t (&a)[24][4], uint32_t sc2, bool gen, uint32_t sbase, int wg, int nwg, int cb, int first,
                                            int w, int lane, int zero) {
    const uint32_t bar_full = sbase + P1_OFF_BAR, bar_empty = bar_full + P1_NST * 8;
    const uint32_t empty_remote = mapa(bar_empty, lane & 1);
    const int g = lane >> 2, q = lane & 3, turn = wg + 1 == nwg ? 1 : wg + 2;
    float ssq[2] = {0.f, 0.f};
    uint32_t acc[32] = {};
    TSTAMP(0, 1);

    uint8_t* hp = reinterpret_cast<uint8_t*>(g_h) + (size_t)first * (2 * H_TILE) + ((cb * 2 + (w >> 1)) * H_STEP + (w & 1) * 1536) + g * 64 + (q ^ (g >> 1)) * 16;
    const uint64_t desc_base = make_desc(sbase, 16, 1024) | (1ull << 62);
    const uint64_t da = make_desc(sbase + P1_OFF_A + wg * 2048, 128, 256);
#pragma unroll 1
    for (int i = 0;; i++) {
        const int s0 = (i & 1) * 16, par = (i >> 1) & 1;
        const uint64_t d0 = desc_base + (uint64_t)((i & 1) * (LN_TILE / 16));
        TRACE(wg, i, 0);
        mbar_wait(bar_full + s0, par);
        bar_sync(1 + wg, 256);
        TRACE(wg, i, 1);
        uint32_t step, more;
        wg_fence();
#pragma unroll
        for (int k = 0; k < 24; k++) {
            if (k == 12) mbar_wait(bar_full + s0 + 8, par);
            const uint64_t db = d0 + (uint64_t)((k >> 2) * 1024 + (k & 3) * 2);
            if (k < 23) mma_rs_n128(acc, a[k], db, k ? 1 : zero);
            else mma_ss_n128(acc, da, db);
            if (k == 23) bar_arrive(turn, 256);
            if (k % 12 == 11) wg_commit();
        }
        asm volatile("ld.shared.v2.u32 {%0, %1}, [%2];\n" : "=r"(step), "=r"(more) : "r"(sbase + P1_OFF_TILE + (i & 3) * 16) : "memory");
        TRACE(wg, i, 2);
        wg_wait<1>();
        if (lane < 2) mbar_arrive_cluster(empty_remote + s0);
        hp += step;
        TRACE(wg, i, 3);
        wg_wait<0>();
        TRACE(wg, i, 4);
        if (lane < 2) mbar_arrive_cluster(empty_remote + s0 + 8);
        if (gen) p1_epilogue<true>(acc, ssq, sc2, hp, zero);
        else p1_epilogue<false>(acc, ssq, sc2, hp, zero);
        if (!more) break;
    }
    TSTAMP(0, 21);
    if (wg == 0) bar_sync(1, 256);
    uint32_t par;
    asm volatile("ld.shared.u32 %0, [%1];\n" : "=r"(par) : "r"(sbase + P1_OFF_TILE - 4) : "memory");
    float* sums = g_sums[par];
#pragma unroll
    for (int r = 0; r < 2; r++) {
        ssq[r] += __shfl_xor_sync(0xffffffffu, ssq[r], 1);
        ssq[r] += __shfl_xor_sync(0xffffffffu, ssq[r], 2);
        if (q == 0) atomicAdd(sums + cb * 64 + w * 16 + r * 8 + g, ssq[r]);
    }
}

__device__ __forceinline__ void p1_w2(const __nv_bfloat16* __restrict__ w2, const __nv_bfloat16* __restrict__ grn_b, int w, int lane) {
    const int gw = (blockIdx.x - 8 * NGRP) * 4 + w;
    float* sums = g_sums[__ldcg(&g_epoch) & 1] + HID;
    flag_wait<true>(&g_flag[40][1][0], 12);
    {
        const int col = gw % 6 * 64 + lane * 2;
        float bsum[2] = {0.f, 0.f}, asum[2] = {0.f, 0.f};
#pragma unroll 4
        for (int kk = 0; kk < 192; kk++) {
            const int k = gw / 6 * 192 + kk;
            const uint32_t v = *reinterpret_cast<const uint32_t*>(w2 + k * C_DIM + col);
            const float b = __bfloat162float(grn_b[k]), f = __uint_as_float(__ldcg(&g_ex[k]) << 23);
            bsum[0] = fmaf(b, bf_lo(v), bsum[0]);
            bsum[1] = fmaf(b, bf_hi(v), bsum[1]);
            asum[0] = fmaf(f, fabsf(bf_lo(v)), asum[0]);
            asum[1] = fmaf(f, fabsf(bf_hi(v)), asum[1]);
        }
#pragma unroll
        for (int j = 0; j < 2; j++) {
            atomicAdd(sums + col + j, bsum[j]);
            atomicAdd(sums + C_DIM + col + j, asum[j]);
        }
        __threadfence();
        __syncwarp();
        if (lane == 0) asm volatile("red.relaxed.gpu.global.add.u32 [%0], 1;\n" ::"l"(&g_flag[LN_RING + 2][0][0]) : "memory");
    }
    while (*(volatile unsigned*)&g_flag[P1_IMG % LN_RING][1][0] < 12 * (P1_IMG / LN_RING + 1)) {
        __nanosleep(2000);
        SAFE_BREAK
    }
    flag_wait<true>(&g_flag[LN_RING + 2][0][0], 48);
    float z = 0.f;
#pragma unroll
    for (int j = 0; j < C_DIM / 32; j++) z = fmaxf(z, __ldcg(sums + C_DIM + j * 32 + lane));
    const float sc = __uint_as_float((263u - acc_exp(__uint_as_float(__reduce_max_sync(0xffffffffu, __float_as_uint(z))))) << 23);
    const int np = gw % 6 * 64 + lane * 2;
#pragma unroll 2
    for (int cc = 0; cc < 24; cc++) {
        const int c = gw / 6 * 24 + cc;
        uint32_t v[8], o[2][4];
#pragma unroll
        for (int e = 0; e < 8; e++) v[e] = *reinterpret_cast<const uint32_t*>(w2 + (c * 8 + e) * C_DIM + perm32(np));
#pragma unroll
        for (int e = 0; e < 4; e++) {
            const uint2 t = __ldcg(reinterpret_cast<const uint2*>(g_ex) + c * 4 + e);
            const float f0 = __uint_as_float(t.x << 23), f1 = __uint_as_float(t.y << 23);
            o[0][e] = pack_f16(bf_lo(v[2 * e]) * f0 * sc, bf_lo(v[2 * e + 1]) * f1 * sc);
            o[1][e] = pack_f16(bf_hi(v[2 * e]) * f0 * sc, bf_hi(v[2 * e + 1]) * f1 * sc);
        }
#pragma unroll
        for (int j = 0; j < 2; j++)
            g_w2img[0][(((c >> 1) * 48 + (np >> 3)) * 2 + (c & 1)) * 8 + (np & 7) + j] = make_uint4(o[j][0], o[j][1], o[j][2], o[j][3]);
    }
    asm volatile("fence.proxy.async.global;\n" ::: "memory");
    __threadfence();
    __syncwarp();
    if (lane == 0) asm volatile("red.relaxed.gpu.global.add.u32 [%0], 1;\n" ::"l"(&g_img[0]) : "memory");
}

__global__ void __cluster_dims__(2, 1, 1) __launch_bounds__(512, 1)
pass1_kernel(const __grid_constant__ CUtensorMap wmap, const __nv_bfloat16* __restrict__ x, const __nv_bfloat16* __restrict__ dw,
             const __nv_bfloat16* __restrict__ w1, const __nv_bfloat16* __restrict__ w2, const __nv_bfloat16* __restrict__ grn_b, int zero) {
    extern __shared__ __align__(1024) uint8_t smem[];
    const uint32_t sbase = smem_u32(smem);
    const uint32_t bar_full = sbase + P1_OFF_BAR, bar_empty = bar_full + P1_NST * 8, bar_w = bar_empty + P1_NST * 8;
    const uint32_t bar_xfull = bar_w + 24, bar_raw = bar_xfull + 16, bar_done = bar_raw + 8, bar_peer = bar_raw + 16;
    const int tid = threadIdx.x;
    const int warp = __shfl_sync(0xffffffffu, tid >> 5, 0), lane = tid & 31;
    const uint32_t rank = cluster_rank();
    const int cl = blockIdx.x >> 1, first = min(cl >> 2, NGRP);
    const bool small = cl >= 4 * NGRP;
    const int nwg = small ? 2 : 3, cb0 = small ? (blockIdx.x - 8 * NGRP) * 2 : (blockIdx.x & 7) * 3;
    const int tile1 = p1_tile(small ? 0 : first, small), tile2 = p1_tile(small ? 1 : first + NGRP, small);
    uint8_t* const ring = reinterpret_cast<uint8_t*>(g_ln);
    const uint32_t sdw = sbase + P1_OFF_DW + (lane & 7) * 16;
    const uint8_t* xsrc = reinterpret_cast<const uint8_t*>(x) + (size_t)(NFIRST * 4 + blockIdx.x) * (2 * P1_X);
    auto ring_row = [&](int p) {
        const int n = (blockIdx.x & 2) * 32 + (lane >> 3) * 8 + p * 2 + (blockIdx.x & 1);
        return n * 128 + (((lane ^ n) & 7) << 4);
    };
    const int n1 = (warp & 1) * 32 + (lane & 24) + (warp & 6) + (warp >> 3);
    const int px = tid >> 3;
    const uint32_t src1 = sbase + (px < 60 ? (rank ^ 1) * 8192 + px / 10 * (16384 - 7680) : P1_OFF_RAW - 60 * 768) + px * 768 + (lane & 7) * 16;
    const uint32_t dst1 = sbase + (rank * 64 + n1) * 128 + (((lane ^ n1) & 7) << 4);
    auto store_row = [&](const uint32_t (&v)[6][4], uint8_t* dst, bool local) {
        if (local) {
#pragma unroll
            for (int j = 0; j < 6; j++)
                asm volatile("st.shared.v4.u32 [%4], {%0,%1,%2,%3};\n" ::"r"(v[j][0]), "r"(v[j][1]), "r"(v[j][2]), "r"(v[j][3]), "r"(dst1 + j * 16384) : "memory");
        } else {
#pragma unroll
            for (int j = 0; j < 6; j++)
                asm volatile("st.global.v4.u32 [%4], {%0,%1,%2,%3};\n" ::"r"(v[j][0]), "r"(v[j][1]), "r"(v[j][2]), "r"(v[j][3]), "l"(dst + j * 16384) : "memory");
        }
    };
    auto load_w1 = [&](int i) {
        mbar_expect_tx(bar_w + i * 8, P1_SLOT);
        tma2(sbase + (2 + (i & 1)) * P1_SLOT, &wmap, (cb0 + i) * 64, 0, bar_w + i * 8);
        tma2(sbase + (2 + (i & 1)) * P1_SLOT + P1_SLOT / 2, &wmap, (cb0 + i) * 64, 192, bar_w + i * 8);
    };

    TSTAMP(0, 0);
    TRACEW(110 + warp, 0);

    if (warp >= 12) {
        reg_dec<56>();
        asm volatile("barrier.cluster.arrive.relaxed.aligned;\n" ::: "memory");
        asm volatile("barrier.cluster.wait.aligned;\n" ::: "memory");
        {
            const uint32_t xbar = bar_xfull + (warp & 1) * 8, xdst = sbase + P1_OFF_X + (warp & 1) * P1_X;
            uint32_t src = src1;
            const int row0 = ring_row((warp & 1) * 2);
            int slot = blockIdx.x >> 2, used = 0;
            xsrc += (warp & 1) * P1_X;
            auto next = [&]() {
                xsrc += (size_t)NUM_CTAS * 2 * P1_X;
                if (elect_one()) {
                    mbar_expect_tx(xbar, P1_X);
                    bulk_g2s(xdst, xsrc, P1_X, xbar);
                }
                __syncwarp();
            };
#pragma unroll 1
            for (int i = -1; i * LN_STEP + (int)(blockIdx.x >> 2) < NT_RING; i++) {
                if (warp == 14) TRACEW(128 + i, 0);
#pragma unroll 1
                for (int ps = i < 0 ? -4 : 0; ps < (i > 0 ? 4 : i + 2); ps += i < 0 ? 4 : 1) {
                    if (ps == 0) {
                        if (i < 0) mbar_wait(bar_raw, 0);
                        else {
                            if (i == 1) {
                                bar_sync(9, 192);
                                next();
                            }
                            if (used) flag_wait<false>(&g_flag[slot][1][0], used);
                            mbar_wait(xbar, i & 1);
                        }
                        if (warp == 14) TRACEW(128 + i, 1);
                    }
                    uint32_t v[6][4];
#pragma unroll
                    for (int j = 0; j < 6; j++) lds128(v[j], src + (ps & 3) * (4 * C_DIM * 2) + j * 128);
                    ln_row(v, sdw, [&](uint32_t dep) {
                        if (i < 0 && ps == 0 && lane == 0) mbar_arrive_cluster(mapa(bar_peer, rank ^ 1) + (dep & zero));
                        if (ps == 3 && (i + 1) * LN_STEP + (blockIdx.x >> 2) < NT_RING && !__any_sync(0xffffffffu, dep & zero)) next();
                    });
                    store_row(v, ring + (slot * LN_TILE + (ps & 1) * 4096 + (row0 ^ (ps & 2) * 144)), i < 0);
                }
                if (warp == 14) TRACEW(128 + i, 2);
                if (i < 0) {
                    asm volatile("fence.proxy.async.shared::cta;\n" ::: "memory");
                    bar_arrive(8, 512);
                    if (warp != 13) bar_arrive(4, 512);
                    if (warp < 14) break;
                    src = xdst + (lane >> 3) * (C_DIM * 2) + (lane & 7) * 16;
                } else {
                    asm volatile("fence.proxy.async.global;\nfence.acq_rel.cta;\n" ::: "memory");
                    if (i) mbar_wait(bar_done, ~i & 1);
                    __syncwarp();
                    if (lane == 0) mbar_arrive(bar_done);
                    if ((slot += LN_STEP) >= LN_RING) { slot -= LN_RING; used += 12; }
                }
            }
        }
        if (warp == 12) {
            int prev = first - NFIRST, t = tile1, next = tile2;
            const uint32_t rbase = mapa(sbase, lane & 1);
            int i = 1;
#pragma unroll 1
            for (; t < NT_RING; i++) {
                const int s0 = (i & 1) * 2, par = ((i + 1) >> 1 & 1) ^ 1;
                const int round = t / LN_RING, slot = t - round * LN_RING;
                const uint8_t* src = ring + slot * LN_TILE + rank * (P1_SLOT / 2);
                int draw = i + 1;
                if (rank == 0 && lane == 0 && !small) draw = 2 * NGRP + atomicAdd(&g_flag[LN_RING + ((cl >> 1) & 1)][cl & 1][0], 1u);
                flag_wait<true>(&g_flag[slot][0][0], 4 * round + 4);
                TRACEW(i, 2);
                asm volatile("fence.proxy.async.global;\n" ::: "memory");
                draw = p1_tile(__shfl_sync(0xffffffffu, draw, 0), small);
#pragma unroll
                for (int h = 0; h < 2; h++) {
                    mbar_wait(bar_empty + (s0 + h) * 8, par);
                    TRACEW(i, 4 + h);
                    if (elect_one()) {
                        mbar_expect_tx(bar_full + (s0 + h) * 8, P1_SLOT + 16 - 16 * h);
                        bulk_g2s_mc(sbase + (s0 + h) * P1_SLOT + rank * (P1_SLOT / 2), src + h * P1_SLOT, P1_SLOT / 2, bar_full + (s0 + h) * 8, (uint16_t)3);
                    }
                    __syncwarp();
                    if (h == 0 && rank == 0 && lane < 2)
                        asm volatile("st.async.shared::cluster.mbarrier::complete_tx::bytes.v4.u32 [%0], {%1, %2, %3, %3}, [%4];\n"
                                     ::"r"(rbase + P1_OFF_TILE + (i & 3) * 16), "r"((t - prev) * (2 * H_TILE)), "r"((int)(next < NT_RING)), "r"(draw),
                                       "r"(rbase + P1_OFF_BAR + s0 * 8) : "memory");
                }
                prev = t;
                t = next;
                next = draw;
                if (rank != 0) {
                    mbar_wait(bar_full + s0 * 8, (i >> 1) & 1);
                    mbar_wait(bar_full + s0 * 8 + 8, (i >> 1) & 1);
                    if (lane == 0) asm volatile("red.relaxed.gpu.global.add.u32 [%0], %1;\n" ::"l"(&g_flag[slot][1][0]), "r"(nwg) : "memory");
                    asm volatile("ld.shared.u32 %0, [%1];\n" : "=r"(next) : "r"(sbase + P1_OFF_TILE + (i & 3) * 16 + 8) : "memory");
                    TRACEW(i, 3);
                }
            }
#pragma unroll 1
            for (int j = 2 * i; j < 2 * i + 4; j++) mbar_wait(bar_empty + (j & 3) * 8, ((j + 2) >> 2 & 1) ^ 1);
        } else if (warp == 13) {
            {
                bar_sync(4, 512);
                mbar_wait(bar_peer, 0);
                const uint32_t o = lane * 16384 + rank * 8192, peer = mapa(sbase, rank ^ 1);
                if (lane < 6)
                    asm volatile("cp.async.bulk.shared::cluster.shared::cta.mbarrier::complete_tx::bytes [%0], [%1], 8192, [%2];\n"
                                 ::"r"(peer + o), "r"(sbase + o), "r"(peer + P1_OFF_BAR + (lane >= 3 ? 8 : 0)) : "memory");
                __syncwarp();
            }
            const uint32_t par = g_epoch & 1;
            asm volatile("st.shared.u32 [%0], %1;\n" ::"r"(sbase + P1_OFF_TILE - 4), "r"(par) : "memory");
            if (blockIdx.x == 18) g_par = par;
            if (blockIdx.x < 18) reinterpret_cast<float4*>(g_sums[par ^ 1])[blockIdx.x * 32 + lane] = make_float4(0.f, 0.f, 0.f, 0.f);
#pragma unroll 1
            for (int i = 0; i * LN_STEP + (blockIdx.x >> 2) < NT_RING; i++) {
                mbar_wait(bar_done, i & 1);
                asm volatile("fence.proxy.async.global;\n" ::: "memory");
                if (lane == 0) {
                    mbar_arrive(bar_done);
                    asm volatile("red.release.gpu.global.add.u32 [%0], 1;\n" ::"l"(&g_flag[(blockIdx.x >> 2) + i % LN_DEPTH * LN_STEP][0][0]) : "memory");
                }
                __syncwarp();
                TRACEW(128 + i, 3);
            }
            flag_wait<true>(&g_flag[LN_RING + 2][0][0], 48);
        }
    } else {
        if (tid == 0) {
            mbar_init(bar_raw, 1);
            mbar_init(bar_xfull, 1);
            mbar_init(bar_xfull + 8, 1);
            mbar_init(bar_w, 1);
            mbar_init(bar_w + 8, 1);
            asm volatile("fence.mbarrier_init.release.cluster;\n" ::: "memory");
            mbar_expect_tx(bar_raw, P1_SLOT + C_DIM * 2);
            bulk_g2s(sbase + P1_OFF_DW, dw, C_DIM * 2, bar_raw);
            for (int i = 0; i < 7; i++)
                bulk_g2s(sbase + (i < 6 ? i * 16384 + (rank ^ 1) * 8192 : P1_OFF_RAW), x + (size_t)(first * 128 + rank * 64 + i * 10) * C_DIM, i < 6 ? 7680 : 3072, bar_raw);
            if (blockIdx.x < 128)
                asm volatile("cp.async.bulk.prefetch.L2.global [%0], 9216;\n" ::"l"(w1 + blockIdx.x * 4608) : "memory");
            load_w1(0);
            for (int i = 0; i < 2; i++) {
                mbar_expect_tx(bar_xfull + i * 8, P1_X);
                bulk_g2s(sbase + P1_OFF_X + i * P1_X, xsrc + i * P1_X, P1_X, bar_xfull + i * 8);
            }
            load_w1(1);
        }
        if (tid == 32) {
            mbar_init(bar_done, 3);
            mbar_init(bar_peer, 16);
            mbar_init(bar_w + 16, 1);
            asm volatile("fence.mbarrier_init.release.cluster;\n" ::: "memory");
        }
        if (tid == 64) {
            asm volatile("st.shared.v2.u32 [%0], {0, 1};\n" ::"r"(sbase + P1_OFF_TILE) : "memory");
            for (int i = 0; i < P1_NST; i++) {
                mbar_init(bar_full + i * 8, 1);
                mbar_init(bar_empty + i * 8, 8 * nwg);
                if (i < 2) mbar_expect_tx(bar_full + i * 8, P1_SLOT / 2);
            }
            asm volatile("fence.mbarrier_init.release.cluster;\n" ::: "memory");
            if (blockIdx.x < 64) (&g_half[0][0])[blockIdx.x] = 0;
            else if (blockIdx.x == 64) g_prog = 0;
            else if (blockIdx.x < 67) g_img[blockIdx.x - 65] = 0;
        }
        __syncwarp();
        asm volatile("barrier.cluster.arrive.relaxed.aligned;\n" ::: "memory");
        reg_inc<152>();
        TRACEW(110 + warp, 1);
        const int wg = warp >> 2, w = warp & 3;
        gdc_launch();
        asm volatile("barrier.cluster.wait.aligned;\n" ::: "memory");
        uint32_t a[24][4], ex[2], gen = 0;
        const uint32_t wsrc = sbase + (2 + (wg & 1)) * P1_SLOT + ((lane >> 4) * 8 + (lane & 7)) * 128 + (((2 * w + ((lane >> 3) & 1)) ^ (lane & 7)) << 4);
#pragma unroll 1
        for (int it = 0; it < 2; it++) {
#pragma unroll 1
            for (int ps = it - 1; ps < (it ? (wg == 2 ? 2 : 1) : wg - 2); ps++) {
                if (ps == 0) mbar_wait(bar_raw, 0);
                if (ps == 1) mbar_wait(bar_xfull + (w >> 1) * 8, 0);
                TRACEW(110 + warp, 2 + (ps == 0));
                uint32_t v[6][4];
                const uint32_t src = ps < 1 ? src1 : sbase + P1_OFF_X + ((w >> 1) * 16 + (w & 1) * 4 + 8 + (lane >> 3)) * 768 + (lane & 7) * 16;
#pragma unroll
                for (int j = 0; j < 6; j++) lds128(v[j], src + j * 128);
                ln_row(v, sdw, [&](uint32_t dep) {
                    if (ps == 0 && lane == 0) mbar_arrive_cluster(mapa(bar_peer, rank ^ 1) + (dep & zero));
                    if (ps == 1) bar_arrive(9, 192);
                });
                store_row(v, ring + ((blockIdx.x >> 2) * LN_TILE + (w & 1) * 4096 + ring_row((w & 2) + 1)), ps < 1);
                if (ps == 0) {
                    asm volatile("fence.proxy.async.shared::cta;\n" ::: "memory");
                    bar_arrive(4, 512);
                    if (wg) bar_arrive(8, 512);
                    if (wg == 1) bar_arrive(1, 256);
                    TRACEW(110 + warp, 4);
                }
                if (ps == 1) {
                    asm volatile("fence.proxy.async.global;\n" ::: "memory");
                    bar_sync(7, 128);
                    if (tid == 256) mbar_arrive(bar_done);
                }
            }
            if (it) {
                if (wg == nwg) {
                    p1_w2(w2, grn_b, w, lane);
                    return;
                }
                mbar_wait(bar_w + wg * 8, 0);
            }
            TRACEW(110 + warp, 5);
            if (it || wg == 0) {
#pragma unroll
            for (int k = 0; k < 24; k++) ldsm4t(a[k], wsrc + k * 2048);
            if (it && wg == 0 && !small) {
                bar_sync(5, 128);
                if (tid == 0) load_w1(2);
                __syncwarp();
            }
#pragma unroll
            for (int r = 0; r < 2; r++) {
                float t = 0.f;
#pragma unroll
                for (int j = 0; j < 6; j++) {
                    uint32_t c = bf2_mul(a[4 * j][r], a[4 * j][r]);
#pragma unroll
                    for (int k = 1; k < 8; k++) c = bf2_fma(a[4 * j + k / 2][r + (k & 1) * 2], a[4 * j + k / 2][r + (k & 1) * 2], c);
                    t += bf_lo(c) + bf_hi(c);
                }
                t += __shfl_xor_sync(0xffffffffu, t, 1);
                t += __shfl_xor_sync(0xffffffffu, t, 2);
                asm("sqrt.approx.f32 %0, %0;\n" : "+f"(t));
                ex[r] = min(max(__float_as_uint(13.9f * t) >> 23, 72u), 198u);
            }
            asm volatile("{\n.reg .pred p;\nsetp.gt.u32 p, %1, 7;\nbar.red.or.pred p, %2, 128, p;\nselp.u32 %0, 1, 0, p;\n}\n"
                         : "=r"(gen) : "r"(max(ex[0] - 125u, ex[1] - 125u)), "r"(5 + wg) : "memory");
            gen = __shfl_sync(0xffffffffu, gen, 0) & it;
            if (it) {
                if ((lane & 3) < 2) g_ex[(cb0 + wg) * 64 + w * 16 + (lane & 1) * 8 + (lane >> 2)] = lane & 1 ? ex[1] : ex[0];
                if (lane < 4) mbar_arrive_cluster(mapa(bar_empty, lane & 1) + (2 + (lane >> 1)) * 8);
                __syncwarp();
            }
            }
            if (gen) {
#pragma unroll
                for (int k = 0; k < 24; k++)
#pragma unroll
                    for (int j = 0; j < 4; j++) a[k][j] = bf2_mul(a[k][j], (268u - ex[j & 1]) * 0x00800080u);
            }
            if (it || wg == 1) {
#pragma unroll
                for (int k = 0; k < 24; k++)
#pragma unroll
                    for (int j = 0; j < 4; j++) {
                        a[k][j] = bf2_as_h2(bf2_mul(a[k][j], 0x07800780u));
                        asm volatile("" : "+r"(a[k][j]));
                    }
            }
            TRACEW(110 + warp, 6);
        }
#pragma unroll
        for (int j = 0; j < 4; j++)
            asm volatile("st.shared.u32 [%0], %1;\n" ::"r"(sbase + P1_OFF_A + warp * 512 + (j & 1) * 256 + (j >> 1) * 128 + lane * 4), "r"(a[23][j]) : "memory");
        asm volatile("fence.proxy.async.shared::cta;\n" ::: "memory");
        if (wg == 0) bar_sync(8, 512);
        TRACEW(110 + warp, 7);
        const uint32_t ex2 = ex[0] | ex[1] << 16;
        p1_consumer(a, gen ? 0x7f007f00u - (ex2 << 7) : (0x008e008eu - ex2) << 10, gen, sbase, wg, nwg, cb0 + wg, first, w, lane, zero);
        TSTAMP(0, 30);
    }
}

#define P2_NB_ 5
#define P2_NA_ 5
#define P2_DELTA_ 7
#define P2_EXTRA 0
#define P2_HSLEEP 64
#define P2_PSLEEP 100
#define P2_T0 5
#define P2_TS 11
constexpr int P2_B = 24576, P2_NB = P2_NB_;
constexpr int P2_A = 3072, P2_NA = P2_NA_;
constexpr int P2_XROW = C_DIM * 2;
constexpr int P2_OFF_A = P2_B * P2_NB;
constexpr int P2_OFF_X = P2_OFF_A + 3 * P2_NA * P2_A;
constexpr int P2_XHALF = 32 * P2_XROW + 64;
constexpr int P2_OFF_BIAS = P2_OFF_X + 64 * P2_XROW + 64;
constexpr int P2_OFF_GRN = P2_OFF_BIAS + C_DIM * 4;
constexpr int P2_OFF_BAR = P2_OFF_GRN + HID * 2;
constexpr int P2_SMEM = P2_OFF_BAR + (2 * P2_NB + 6 * P2_NA + 3) * 8;
#define P2_LAG_ 17
constexpr int P2_LAG = P2_LAG_;
constexpr int P2_NCL = NUM_CTAS / 2, P2_ITEMS = NT128 / P2_NCL, P2_SHARED = NT128 - P2_ITEMS * P2_NCL;
constexpr int P2_POS = P2_LAG * (P2_ITEMS - 1) + 48;
__device__ __forceinline__ int p2_start(int n) { return n < 0 ? 0 : n == P2_ITEMS ? P2_POS - 24 : P2_LAG * n; }
constexpr int P2_FOLD = 17;
constexpr int P2_XC = 8 * P2_XROW;
constexpr int P2_DELTA = P2_DELTA_;
__device__ __forceinline__ int p2_tile(int cl, int n) {
    return n == 0 ? NT128 - 1 - cl : n < 0 || n == P2_ITEMS ? NT128 - 1 - P2_NCL - (cl >> 1) : cl + P2_NCL * (n - 1);
}

constexpr int P2_EG = 2;
__device__ __forceinline__ void p2_epilogue(const uint32_t (&acc0)[48], const uint32_t (&acc1)[48], uint32_t sx, uint32_t sb, float up, int zero) {
    uint32_t v[2][P2_EG][4];
    float b[2][8];
    auto load = [&](int c, uint32_t a) {
#pragma unroll
        for (int j = 0; j < 2; j++)
            asm volatile("ld.shared.v4.f32 {%0,%1,%2,%3}, [%4];\n" : "=f"(b[c & 1][4 * j]), "=f"(b[c & 1][4 * j + 1]), "=f"(b[c & 1][4 * j + 2]), "=f"(b[c & 1][4 * j + 3])
                         : "r"(sb + c * 128 + j * 16) : "memory");
#pragma unroll
        for (int j = 0; j < P2_EG; j++) {
            const int u = c * P2_EG + j;
            asm volatile("ld.shared.v4.u32 {%0,%1,%2,%3}, [%4];\n" : "=r"(v[c & 1][j][0]), "=r"(v[c & 1][j][1]), "=r"(v[c & 1][j][2]), "=r"(v[c & 1][j][3])
                         : "r"(a + (u >> 1) * 64 + (u & 1) * 4 * P2_XROW) : "memory");
        }
    };
    load(0, sx);
#pragma unroll
    for (int c = 0; c < 24 / P2_EG; c++) {
        if (c + 1 < 24 / P2_EG) load(c + 1, sx + (v[c & 1][P2_EG - 1][0] & zero));
#pragma unroll
        for (int j = 0; j < P2_EG; j++) {
            const int u = c * P2_EG + j, i = 8 * ((u >> 1) % 6) + (u & 1);
            const uint32_t (&acc)[48] = u < 12 ? acc0 : acc1;
            uint32_t (&w)[4] = v[c & 1][j];
#pragma unroll
            for (int e = 0; e < 4; e++)
                w[e] = bf2_add(pack_bf16(fmaf(h_lo(acc[i + 2 * e]), up, b[c & 1][2 * e]), fmaf(h_hi(acc[i + 2 * e]), up, b[c & 1][2 * e + 1])), w[e]);
            asm volatile("st.shared.v4.u32 [%4], {%0,%1,%2,%3};\n" ::"r"(w[0]), "r"(w[1]), "r"(w[2]), "r"(w[3]),
                         "r"(sx + (u >> 1) * 64 + (u & 1) * 4 * P2_XROW) : "memory");
        }
    }
}

__device__ __forceinline__ void p2_unpack(uint4& u, uint32_t o1, uint32_t o2, uint32_t o3) {
    u.z = o1 & 0xbff8bff8u;
    u.y = o2 & 0xbff8bff8u;
    u.w = o3 & 0xbff8bff8u;
    u.x = (__byte_perm(o1, 0, 0x2301) & 0x07400740u) | ((__byte_perm(o2, o3, 0x6240) << 3) & 0x38383838u) | ((__byte_perm(o2, o3, 0x3715) << 1) & 0x80808080u);
}
__device__ __forceinline__ uint32_t h2_mul(uint32_t a, uint32_t b) {
    uint32_t r;
    asm("mul.rn.f16x2 %0, %1, %2;\n" : "=r"(r) : "r"(a), "r"(b));
    return r;
}
__device__ __forceinline__ void p2_epilogue_add(const uint32_t (&acc)[48], uint8_t* o, float f, int zero) {
#pragma unroll
    for (int t = 0; t < 12; t++) {
        uint32_t v[4];
#pragma unroll
        for (int e = 0; e < 4; e++) {
            v[e] = acc[8 * (t >> 1) + (t & 1) + 2 * e];
            asm volatile("" : "+r"(v[e]));
            v[e] = pack_bf16(h_lo(v[e]) * f, h_hi(v[e]) * f);
        }
        asm volatile("red.global.add.noftz.v4.bf16x2 [%0], {%1,%2,%3,%4};\n" ::"l"(o + (t >> 1) * 64 + (t & 1) * 4 * P2_XROW),
                     "r"(v[0]), "r"(v[1]), "r"(v[2]), "r"(v[3]) : "memory");
        if (t % 3 == 2) sched_break(zero);
    }
}

__global__ void __cluster_dims__(2, 1, 1) __launch_bounds__(512, 1)
pass2_kernel(const __nv_bfloat16* __restrict__ x, const __nv_bfloat16* __restrict__ grn_g, __nv_bfloat16* __restrict__ out, int zero) {
    extern __shared__ __align__(1024) uint8_t smem[];
    const uint32_t sbase = smem_u32(smem);
    const uint32_t bar_bfull = sbase + P2_OFF_BAR, bar_bempty = bar_bfull + P2_NB * 8;
    const uint32_t bar_afull = bar_bempty + P2_NB * 8, bar_aempty = bar_afull + 3 * P2_NA * 8;
    const uint32_t bar_xfull = bar_aempty + 3 * P2_NA * 8, bar_oready = bar_xfull + 8, s_pos = bar_xfull + 16;
    int tid;
    asm volatile("mov.u32 %0, %%tid.x;\n" : "=r"(tid));
    const int warp = __shfl_sync(0xffffffffu, tid >> 5, 0), lane = tid & 31;
    const uint32_t rank = cluster_rank();
    const int cl = blockIdx.x >> 1, pair = cl >> 1;
    const int k0 = (4 * pair + (cl & 1) * (48 - P2_POS % 48)) % 48;
    const int head = pair < P2_SHARED && !(cl & 1), tail = pair < P2_SHARED && (cl & 1);

    uint32_t par, gg[4];
    float pre[4];
    if (warp < 12) {
        asm volatile("ld.global.cg.u32 %0, [%1];\n" : "=r"(par) : "l"(&g_par) : "memory");
#pragma unroll
        for (int i = 0; i < 4; i++) {
            asm volatile("ld.global.cg.f32 %0, [%1];\n" : "=f"(pre[i]) : "l"(&g_sums[i & 1][HID + (i >> 1) * C_DIM + tid]) : "memory");
            asm volatile("ld.global.nc.u16 %0, [%1];\n" : "=r"(gg[i]) : "l"(grn_g + tid + 384 * i) : "memory");
        }
    }
    TSTAMP(1, 0);
    if (tid == 384) {
        for (int i = 0; i < P2_NB; i++) {
            mbar_init(bar_bfull + i * 8, 1);
            mbar_init(bar_bempty + i * 8, 24);
        }
        for (int i = 0; i < 3 * P2_NA; i++) {
            mbar_init(bar_afull + i * 8, 1);
            mbar_init(bar_aempty + i * 8, 4);
        }
        mbar_init(bar_xfull, 2);
        mbar_init(bar_oready, 4);
        asm volatile("st.shared.u32 [%0], 0;\n" ::"r"(s_pos) : "memory");
        asm volatile("fence.mbarrier_init.release.cluster;\n" ::: "memory");
    }
    __syncthreads();
    cluster_sync_relaxed();

    if (warp >= 12) {
        reg_dec<32>();
        if (warp == 12) {
            const uint8_t* wsrc = reinterpret_cast<const uint8_t*>(g_w2img) + rank * (P2_B / 2);
            int st = 0, ph = 1, kb = k0, m = 0, r = 0;
            const int busy = head ? 0 : tail ? P2_POS - 24 : P2_POS;
#pragma unroll 1
            for (int p = 0; p < P2_POS; p++) {
                if (p == 0 || p == P2_FOLD) {
                    flag_wait<true>(&g_img[p != 0], p ? 96 * 4 : 48);
                    asm volatile("fence.proxy.async.global;\n" ::: "memory");
                    if (p) wsrc += sizeof(g_w2img[0]);
                }
                mbar_wait(bar_bempty + st * 8, ph);
                TR2P(p, 0);
                if (elect_one()) {
                    mbar_expect_tx(bar_bfull + st * 8, P2_B);
                    bulk_g2s_mc(sbase + st * P2_B + rank * (P2_B / 2), wsrc + kb * P2_B, P2_B / 2, bar_bfull + st * 8, (uint16_t)3);
                    asm volatile("st.volatile.shared.u32 [%0], %1;\n" ::"r"(s_pos), "r"(p) : "memory");
                    const int idle = 2 - min(m, P2_ITEMS - 1) + max(m - 2 + (r >= 48 - 2 * P2_LAG), 0) - ((unsigned)(p - busy) < 24);
                    if (idle) asm volatile("mbarrier.arrive.shared::cta.b64 _, [%0], %1;\n" ::"r"(bar_bempty + st * 8), "r"(idle * 8) : "memory");
                    if (rank == 0) asm volatile("red.relaxed.gpu.global.add.u32 [%0], 1;\n" ::"l"(&g_prog) : "memory");
                }
                __syncwarp();
                if (++st == P2_NB) { st = 0; ph ^= 1; }
                if (++kb == 48) kb = 0;
                if (++r == P2_LAG) { r = 0; m++; }
            }
            mbar_wait(bar_bempty + st * 8, ph);
            if (lane == 0) mbar_arrive(bar_bfull + st * 8);
#pragma unroll 1
            for (int p = 1; p < P2_NB; p++) {
                if (++st == P2_NB) { st = 0; ph ^= 1; }
                mbar_wait(bar_bempty + st * 8, ph);
            }
        } else if (warp == 13) {
            const uint8_t* src[3];
            int n[3], left[3], wrap[3];
            uint32_t st[3];
            auto item = [&](int w) {
                const int u = (k0 + p2_start(n[w])) % 48;
                left[w] = n[w] < 0 || n[w] == P2_ITEMS ? 24 : 48;
                wrap[w] = left[w] - (48 - u);
                src[w] = reinterpret_cast<const uint8_t*>(g_h) + (size_t)p2_tile(cl, n[w]) * (2 * H_TILE) + rank * H_HALF + u * H_STEP;
            };
#pragma unroll
            for (int w = 0; w < 3; w++) {
                n[w] = w == 2 && head ? -1 : w;
                st[w] = 0x80000000u;
                item(w);
            }
            gdc_wait();
#pragma unroll 1
            for (int done = 0; done < 3;) {
                bool idle = true;
#pragma unroll
                for (int w = 0; w < 3; w++) {
                    const uint32_t o = (st[w] & 0xff) + w * P2_NA * 8;
                    if (left[w] >= 0 && mbar_test(bar_aempty + o, st[w] >> 31)) {
                        idle = false;
                        if (left[w] == 0) {
                            if (lane == 0) mbar_arrive(bar_afull + o);
                            left[w] = -1;
                            done++;
                        } else {
                            if (elect_one()) {
                                mbar_expect_tx(bar_afull + o, P2_A);
                                bulk_g2s(sbase + P2_OFF_A + o * (P2_A / 8), src[w], P2_A, bar_afull + o);
                            }
                            __syncwarp();
                            src[w] += H_STEP;
                            st[w] += 8;
                            if ((st[w] & 0xff) == P2_NA * 8) st[w] ^= 0x80000000u | (P2_NA * 8);
                            if (--left[w] == wrap[w]) src[w] -= 48 * H_STEP;
                            if (left[w] == 0 && (n[w] += 3) < P2_ITEMS + tail) item(w);
                        }
                    }
                }
                if (idle) __nanosleep(P2_HSLEEP);
                SAFE_BREAK
            }
        } else if (warp == 14) {
            const uint32_t sx = sbase + P2_OFF_X;
            size_t o = 0;
            auto pace = [&](int target) {
                int v;
                while (true) {
                    asm volatile("ld.volatile.shared.u32 %0, [%1];\n" : "=r"(v) : "r"(s_pos) : "memory");
                    if (v * 16 >= target) break;
                    __nanosleep(P2_PSLEEP);
                    SAFE_BREAK
                }
            };
#pragma unroll 1
            for (int n = -head; n <= P2_ITEMS; n++) {
                const size_t on = (size_t)(2 * p2_tile(cl, n) + rank) * (64 * C_DIM * 2);
                const bool st = n + head > 0, ld = n < P2_ITEMS;
                if (st) mbar_wait(bar_oready, (n - 1 + head) & 1);
                TR2P(n + 1, 1);
                if (lane == 0) {
                    if (n == 1 && head) {
                        asm volatile("cp.async.bulk.wait_group 0;\nfence.proxy.async.global;\n" ::: "memory");
                        asm volatile("st.release.gpu.global.u32 [%0], 1;\n" ::"l"(&g_half[pair][rank]) : "memory");
                    }
                    if (ld) mbar_expect_tx(bar_xfull, 64 * C_DIM * 2);
                    int t = st && n < P2_ITEMS - 1 ? (P2_LAG * (n - 1) + 48 + P2_T0 - 1) * 16 : -1024;
#pragma unroll 1
                    for (int c = 0; st && c < 64 * P2_XROW; c += P2_XC) {
                        pace(t += P2_TS);
                        bulk_s2g(reinterpret_cast<uint8_t*>(out) + o + c, sx + c + (c >= 32 * P2_XROW ? 64 : 0), P2_XC);
                    }
                    asm volatile("cp.async.bulk.commit_group;\ncp.async.bulk.wait_group.read 0;\n" ::: "memory");
#pragma unroll 1
                    for (int c = 0; ld && c < 64 * P2_XROW; c += P2_XC) {
                        pace(t += P2_TS);
                        bulk_g2s(sx + c + (c >= 32 * P2_XROW ? 64 : 0), reinterpret_cast<const uint8_t*>(x) + on + c, P2_XC, bar_xfull);
                    }
                    TR2P(n + 1, 2);
                    if (rank == 0 && n > 0 && n < P2_ITEMS - 2)
                        flag_wait<false>(&g_prog, P2_NCL * (P2_LAG * n + 48 + P2_EXTRA) + (tail ? P2_SHARED - P2_NCL : P2_SHARED) * P2_DELTA);
                    if (ld) mbar_arrive(bar_xfull);
                    TR2P(n + 1, 3);
                }
                __syncwarp();
                o = on;
            }
            asm volatile("cp.async.bulk.wait_group 0;\n" ::: "memory");
            TR2P(30, 1);
        }
    } else {
        reg_inc<160>();
        const int wg = warp >> 2, w = warp & 3, g = lane >> 2, q = lane & 3;
        const uint32_t sx = sbase + P2_OFF_X + (g & 1) * P2_XHALF + (w * 8 + (g >> 1)) * P2_XROW + q * 16;
        const uint32_t af = bar_afull + wg * P2_NA * 8, ae = bar_aempty + wg * P2_NA * 8;
        const uint32_t s_a = sbase + P2_OFF_A - bar_afull * (P2_A / 8) + (lane >> 3) * 512 + (lane & 7) * 64 +
                             ((w ^ ((lane & 7) >> 1)) << 4);
        uint32_t acc0[48], acc1[48];
        float up;
        uint4 a0[2], a1[2];
        int st = 0, ph = 0;

        {
            float4* s_red = reinterpret_cast<float4*>(smem + P2_OFF_BIAS);
            const float* sums = g_sums[par];
            float gx[4], part = 0.f, mx = 0.f;
            TSTAMP(1, 27);
            gdc_wait();
            TSTAMP(1, 1);
#pragma unroll
            for (int i = 0; i < 4; i++) gx[i] = __ldcg(sums + tid + 384 * i);
            if (blockIdx.x == 120 && tid < (LN_RING + 3) * 2) (&g_flag[0][0][0])[tid * 8] = 0;
            if (blockIdx.x == 121 && tid == 0) atomicAdd(&g_epoch, 1u);
            float z = __uint_as_float(__reduce_max_sync(0xffffffffu, __float_as_uint(pre[2] + pre[3])));
#pragma unroll
            for (int i = 0; i < 4; i++) {
                asm("sqrt.approx.f32 %0, %1;\n" : "=f"(gx[i]) : "f"(fmaf(gx[i], HSCALE * HSCALE, 1e-6f)));
                part += gx[i];
                gx[i] *= bf_lo(gg[i]);
                mx = fmaxf(mx, fabsf(gx[i]));
            }
#pragma unroll
            for (int o = 16; o > 0; o >>= 1) part += __shfl_xor_sync(0xffffffffu, part, o);
            mx = __uint_as_float(__reduce_max_sync(0xffffffffu, __float_as_uint(mx)));
            TSTAMP(1, 26);
            if (lane == 0) s_red[warp] = make_float4(part, mx, z, 0.f);
            bar_sync(1, 384);
            float tot = 0.f;
            {
                const float4 t = s_red[min(lane & 15, 11)];
                tot = (lane & 15) < 12 ? t.x : 0.f;
#pragma unroll
                for (int o = 8; o > 0; o >>= 1) tot += __shfl_xor_sync(0xffffffffu, tot, o);
                mx = __uint_as_float(__reduce_max_sync(0xffffffffu, __float_as_uint(t.y)));
                z = __uint_as_float(__reduce_max_sync(0xffffffffu, __float_as_uint(t.z)));
            }
            const float inv = __fdividef(1.0f, fmaf(tot, 1.0f / HID, 1e-6f));
            const uint32_t j = max(__float_as_uint(fmaf(mx, inv, 1.0f) * 1.01f) >> 23, 130u) - 130u;
            const float dn = __uint_as_float((127u - j) << 23);
#pragma unroll
            for (int i = 0; i < 4; i++)
                *reinterpret_cast<uint16_t*>(smem + P2_OFF_GRN + (tid + 384 * i) * 2) = pack_f16(fmaf(gx[i], inv, 1.0f) * dn, 0.f);
            up = (HSCALE * 1.00235f) * __uint_as_float(min(acc_exp(z) - 9u + j, 253u) << 23);
            TSTAMP(1, 25);
            bar_sync(1, 384);
            reinterpret_cast<float*>(smem + P2_OFF_BIAS)[tid] = pre[0] + pre[1];
            if (wg == 1 && blockIdx.x < 96) {
                const uint4* src = g_w2img[0] + blockIdx.x * 768 + tid - 128;
                const uint4 fk = *reinterpret_cast<const uint4*>(smem + P2_OFF_GRN + blockIdx.x * 32 + (tid & 8) * 2);
                uint4 v[6];
#pragma unroll
                for (int i = 0; i < 6; i++) v[i] = __ldcg(src + i * 128);
                auto fold = [&](uint32_t b, uint32_t f) { return (h2_mul(b, f) + 0x00040004u) & 0xfff8fff8u; };
#pragma unroll
                for (int i = 0; i < 6; i++)
                    g_w2img[1][blockIdx.x * 768 + tid - 128 + i * 128] = make_uint4(fold(v[i].x, fk.x), fold(v[i].y, fk.y), fold(v[i].z, fk.z), fold(v[i].w, fk.w));
                asm volatile("fence.proxy.async.global;\n" ::: "memory");
                __threadfence();
                __syncwarp();
                if (lane == 0) asm volatile("red.release.gpu.global.add.u32 [%0], 1;\n" ::"l"(&g_img[1]) : "memory");
            }
        }
        TSTAMP(1, 28);
        int kt = k0, pos;
        const int who = __shfl_sync(0xffffffffu, lane == 2 ? 0 : lane < 2 ? 1 : 2, lane);
        const uint32_t rel0 = who ? mapa(bar_bempty, lane & 1) : mapa(ae, rank), rel1 = rel0 + (who ? P2_NB : P2_NA) * 8;
        uint32_t rel = rel1 - 8;
        auto next_rel = [&](bool go) {
            if (go) rel += 8;
            if (rel == rel1) rel = rel0;
        };
        auto release_b = [&]() {
            next_rel(who == 1);
            if (who == 1) mbar_arrive_cluster(rel);
        };
        auto seek = [&](int p) {
            pos = p;
            st = p % P2_NB;
            ph = p / P2_NB & 1;
            if (who == 1) rel = (st ? rel0 + st * 8 : rel1) - 8;
            int v;
            while (true) {
                asm volatile("ld.volatile.shared.u32 %0, [%1];\n" : "=r"(v) : "r"(s_pos) : "memory");
                if (v >= p) break;
                __nanosleep(200);
                SAFE_BREAK
            }
        };
        auto publish = [&]() {
            asm volatile("fence.proxy.async.shared::cta;\n" ::: "memory");
            __syncwarp();
            if (who == 0) mbar_arrive(bar_oready);
        };
        bool ok_a;
        uint32_t abar = af, pa = 0;
        auto fetch = [&](uint4 (&a)[2], bool early) {
            const uint32_t src = s_a + abar * (P2_A / 8);
            abar += 8;
            if (abar == af + P2_NA * 8) { abar = af; pa ^= 0x80000000u; }
            const bool ok_b = mbar_test(bar_bfull + st * 8, ph);
            ok_a = mbar_test(abar, pa >> 31);
            uint32_t o[6];
            asm volatile("ldmatrix.sync.aligned.m8n8.x4.trans.shared.b16 {%0,%1,%2,%3}, [%4];\n"
                         : "=r"(o[0]), "=r"(o[1]), "=r"(o[2]), "=r"(o[3]) : "r"(src) : "memory");
            asm volatile("ldmatrix.sync.aligned.m8n8.x2.trans.shared.b16 {%0,%1}, [%2];\n"
                         : "=r"(o[4]), "=r"(o[5]) : "r"(src + 2048) : "memory");
            p2_unpack(a[0], o[0], o[1], o[2]);
            p2_unpack(a[1], o[3], o[4], o[5]);
            if (early) {
                const uint32_t* t = reinterpret_cast<const uint32_t*>(smem + P2_OFF_GRN) + kt * 16 + q;
#pragma unroll
                for (int i = 0; i < 2; i++)
                    a[i] = make_uint4(h2_mul(a[i].x, t[8 * i]), h2_mul(a[i].y, t[8 * i]), h2_mul(a[i].z, t[8 * i + 4]), h2_mul(a[i].w, t[8 * i + 4]));
                if (++kt == 48) kt = 0;
            }
            if (!ok_b) mbar_wait(bar_bfull + st * 8, ph);
        };
        auto step = [&](const uint4 (&a)[2], uint4 (&an)[2], int thr, bool early) {
            TR2(0);
            const uint64_t db = make_desc(sbase + st * P2_B, 128, 256);
            wg_fence();
            mma_rs_n192(acc0, a[0], db, thr - 1);
            mma_rs_n192(acc1, a[0], db + 384, thr - 1);
            mma_rs_n192(acc0, a[1], db + 768, 1);
            mma_rs_n192(acc1, a[1], db + 768 + 384, 1);
            wg_commit();
            next_rel(who < thr);
            if (++st == P2_NB) { st = 0; ph ^= 1; }
            wg_wait<1>();
            if (!ok_a) {
                if (who < thr) mbar_arrive_cluster(rel);
                thr = 0;
                mbar_wait(abar, pa >> 31);
            }
            if (who < thr) mbar_arrive_cluster(rel);
            fetch(an, early);
            pos++;
        };
        int n = wg == 2 && head ? -1 : wg;
        mbar_wait(af, 0);
        seek(p2_start(n));
        fetch(a0, n <= 0);
#pragma unroll 1
        for (;; n += 3) {
            TSTAMP(1, 2 + n);
            const int p0 = n < 0 || n == P2_ITEMS ? 12 : 0, pe = n <= 0 ? p0 + P2_FOLD / 2 : 0;
            const bool more = n + 3 < P2_ITEMS + tail;
#pragma unroll 1
            for (int p = p0; p < 24; p++) {
                step(a0, a1, p == p0 ? 1 : 2, p < pe);
                step(a1, a0, 2, p < pe);
            }
            if (n == P2_ITEMS) {
                flag_wait<true>(&g_half[pair][rank], 1);
                TR2(1);
                wg_wait<0>();
                TR2(2);
                release_b();
                uint8_t* o = reinterpret_cast<uint8_t*>(out) + (size_t)((2 * p2_tile(cl, -1) + rank) * 64 + (g & 1) * 32 + w * 8 + (g >> 1)) * P2_XROW + q * 16;
                p2_epilogue_add(acc0, o, up, zero);
                p2_epilogue_add(acc1, o + 384, up, zero);
                TR2(3);
                break;
            }
            mbar_wait(bar_xfull, (n + head) & 1);
            TR2(1);
            wg_wait<0>();
            TR2(2);
            release_b();
            __syncwarp();
            p2_epilogue(acc0, acc1, sx, sbase + P2_OFF_BIAS + q * 32, up, zero);
            TR2(3);
            publish();
            if (!more) break;
            seek(p2_start(n + 3));
            mbar_wait(bar_bfull + st * 8, ph);
        }
        TSTAMP(1, 30);
    }
}

}

extern "C" void kernel_launch(void* const* d_in, const int* in_sizes, int n_in, void* d_out, int out_size) {
    const __nv_bfloat16* x = (const __nv_bfloat16*)d_in[0];
    const __nv_bfloat16* dw = (const __nv_bfloat16*)d_in[1];
    const __nv_bfloat16* w1 = (const __nv_bfloat16*)d_in[2];
    const __nv_bfloat16* w2 = (const __nv_bfloat16*)d_in[3];
    const __nv_bfloat16* grn_g = (const __nv_bfloat16*)d_in[4];
    const __nv_bfloat16* grn_b = (const __nv_bfloat16*)d_in[5];
    __nv_bfloat16* out = (__nv_bfloat16*)d_out;

    cudaFuncSetAttribute(pass1_kernel, cudaFuncAttributeMaxDynamicSharedMemorySize, P1_SMEM);
    cudaFuncSetAttribute(pass2_kernel, cudaFuncAttributeMaxDynamicSharedMemorySize, P2_SMEM);

    typedef CUresult (*EncodeFn)(CUtensorMap*, CUtensorMapDataType, cuuint32_t, void*, const cuuint64_t*, const cuuint64_t*,
                                 const cuuint32_t*, const cuuint32_t*, CUtensorMapInterleave, CUtensorMapSwizzle,
                                 CUtensorMapL2promotion, CUtensorMapFloatOOBfill);
    static EncodeFn encode = nullptr;
    if (!encode) {
        cudaDriverEntryPointQueryResult qres;
        cudaGetDriverEntryPoint("cuTensorMapEncodeTiled", (void**)&encode, cudaEnableDefault, &qres);
    }
    CUtensorMap wmap;
    const cuuint64_t gdim[2] = {HID, C_DIM};
    const cuuint64_t gstr[1] = {HID * 2};
    const cuuint32_t box[2] = {64, 192}, estr[2] = {1, 1};
    CUresult er = encode(&wmap, CU_TENSOR_MAP_DATA_TYPE_BFLOAT16, 2, (void*)w1, gdim, gstr, box, estr, CU_TENSOR_MAP_INTERLEAVE_NONE,
           CU_TENSOR_MAP_SWIZZLE_128B, CU_TENSOR_MAP_L2_PROMOTION_L2_128B, CU_TENSOR_MAP_FLOAT_OOB_FILL_NONE);
    if (er != CUDA_SUCCESS) printf("tensor map encode failed %d\n", (int)er);

    pass1_kernel<<<NUM_CTAS, 512, P1_SMEM>>>(wmap, x, dw, w1, w2, grn_b, 0);

    cudaLaunchAttribute attr[1];
    attr[0].id = cudaLaunchAttributeProgrammaticStreamSerialization;
    attr[0].val.programmaticStreamSerializationAllowed = 1;
    cudaLaunchConfig_t cfg = {};
    cfg.gridDim = dim3(NUM_CTAS);
    cfg.stream = 0;
    cfg.attrs = attr;
    cfg.numAttrs = 1;
    cfg.blockDim = dim3(512);
    cfg.dynamicSmemBytes = P2_SMEM;
    cudaLaunchKernelEx(&cfg, pass2_kernel, x, grn_g, out, 0);
}
```

```cpp
#include <cuda.h>
#include <cuda_runtime.h>
#include <cuda_bf16.h>
#include <stdint.h>
#include <stdio.h>

namespace {

constexpr int M_TOTAL = 384 * 384;
constexpr int C_DIM   = 384;
constexpr int HID     = 1536;
constexpr int NT128   = M_TOTAL / 128;
constexpr int NUM_CTAS = 132;

constexpr int NGRP = 15, NFIRST = NGRP + 1;
#define LN_DEPTH 2
constexpr int LN_STEP = 2 * NGRP, LN_RING = LN_DEPTH * LN_STEP;
constexpr int NT_RING = NT128 - NFIRST;
#define P1_M 101
#define P1_D 10
__device__ __forceinline__ int p1_tile(int t, bool small) {
    return t + (small ? ((t + 1) * P1_M + P1_D - 1) / P1_D : t * P1_D / P1_M);
}
constexpr int LN_TILE = 128 * C_DIM * 2;
constexpr int H_TILE = 64 * HID * 3 / 2;
constexpr int H_HALF = 3072, H_STEP = 6144;

__device__ __align__(1024) uint4 g_h[(size_t)M_TOTAL * HID * 3 / 32];
__device__ __align__(1024) uint4 g_ln[LN_RING * LN_TILE / 16];
__device__ __align__(1024) uint4 g_w2img[2][HID * C_DIM * 2 / 16];
__device__ __align__(16) float g_sums[2][HID + 2 * C_DIM];
__device__ __align__(16) unsigned g_ex[HID];
__device__ unsigned g_epoch, g_par;
__device__ __align__(128) unsigned g_img[2];
__device__ __align__(128) unsigned g_prog;
__device__ __align__(128) unsigned g_half[32][2];
__device__ unsigned g_flag[LN_RING + 3][2][8];
#define TSTAMP(k, i)
#define TRACE(wg, pos, i)
#define TRACEW(pos, i)

#define TR2(i)
#define TR2P(pos, i)
__host__ __device__ __forceinline__ int perm32(int n) {
    return (n & ~31) | (((n >> 1) & 3) << 3) | (((n >> 3) & 3) << 1) | (n & 1);
}

__device__ __forceinline__ uint32_t smem_u32(const void* p) { return (uint32_t)__cvta_generic_to_shared(p); }

__device__ __forceinline__ void mbar_init(uint32_t bar, uint32_t count) {
    asm volatile("mbarrier.init.shared::cta.b64 [%0], %1;\n" ::"r"(bar), "r"(count) : "memory");
}
__device__ __forceinline__ void mbar_expect_tx(uint32_t bar, uint32_t bytes) {
    asm volatile("mbarrier.arrive.expect_tx.shared::cta.b64 _, [%0], %1;\n" ::"r"(bar), "r"(bytes) : "memory");
}
__device__ __forceinline__ void mbar_arrive(uint32_t bar) {
    asm volatile("mbarrier.arrive.shared::cta.b64 _, [%0];\n" ::"r"(bar) : "memory");
}
__device__ __forceinline__ void mbar_arrive_cluster(uint32_t bar_cluster_addr) {
    asm volatile("mbarrier.arrive.shared::cluster.b64 _, [%0];\n" ::"r"(bar_cluster_addr) : "memory");
}
#define SAFE_BREAK
__device__ __forceinline__ void mbar_wait(uint32_t bar, uint32_t parity) {
    asm volatile(
        "{\n"
        ".reg .pred p;\n"
        "LAB_WAIT:\n"
        "mbarrier.try_wait.parity.shared::cta.b64 p, [%0], %1;\n"
        "@!p bra LAB_WAIT;\n"
        "}\n" ::"r"(bar), "r"(parity) : "memory");
}
__device__ __forceinline__ bool mbar_test(uint32_t bar, uint32_t parity) {
    uint32_t ok;
    asm volatile("{\n.reg .pred p;\n"
                 "mbarrier.test_wait.parity.shared::cta.b64 p, [%1], %2;\n"
                 "selp.u32 %0, 1, 0, p;\n}\n" : "=r"(ok) : "r"(bar), "r"(parity) : "memory");
    return ok != 0;
}
__device__ __forceinline__ uint32_t mapa(uint32_t addr, uint32_t rank) {
    uint32_t r;
    asm volatile("mapa.shared::cluster.u32 %0, %1, %2;\n" : "=r"(r) : "r"(addr), "r"(rank));
    return r;
}
__device__ __forceinline__ void bulk_g2s(uint32_t dst, const void* src, uint32_t bytes, uint32_t bar) {
    asm volatile("cp.async.bulk.shared::cluster.global.mbarrier::complete_tx::bytes [%0], [%1], %2, [%3];\n"
                 ::"r"(dst), "l"(src), "r"(bytes), "r"(bar) : "memory");
}
__device__ __forceinline__ void bulk_g2s_mc(uint32_t dst, const void* src, uint32_t bytes, uint32_t bar, uint16_t mask) {
    asm volatile("cp.async.bulk.shared::cluster.global.mbarrier::complete_tx::bytes.multicast::cluster [%0], [%1], %2, [%3], %4;\n"
                 ::"r"(dst), "l"(src), "r"(bytes), "r"(bar), "h"(mask) : "memory");
}
__device__ __forceinline__ void tma2(uint32_t dst, const CUtensorMap* map, int c0, int c1, uint32_t bar) {
    asm volatile("cp.async.bulk.tensor.2d.shared::cluster.global.tile.mbarrier::complete_tx::bytes [%0], [%1, {%2, %3}], [%4];\n"
                 ::"r"(dst), "l"(map), "r"(c0), "r"(c1), "r"(bar) : "memory");
}
template <bool ACQ>
__device__ __forceinline__ uint32_t flag_wait(const unsigned* p, unsigned target) {
    unsigned v, n = 0;
    do {
        if (ACQ) asm volatile("ld.acquire.gpu.global.u32 %0, [%1];\n" : "=r"(v) : "l"(p) : "memory");
        else asm volatile("ld.relaxed.gpu.global.u32 %0, [%1];\n" : "=r"(v) : "l"(p) : "memory");
        n++;
    } while (v < target);
    return n == 1;
}
__device__ __forceinline__ void ldsm4t(uint32_t (&r)[4], uint32_t addr) {
    asm volatile("ldmatrix.sync.aligned.m8n8.x4.trans.shared.b16 {%0,%1,%2,%3}, [%4];\n"
                 : "=r"(r[0]), "=r"(r[1]), "=r"(r[2]), "=r"(r[3]) : "r"(addr) : "memory");
}
__device__ __forceinline__ void bulk_s2g(void* dst, uint32_t src, uint32_t bytes) {
    asm volatile("cp.async.bulk.global.shared::cta.bulk_group [%0], [%1], %2;\n" ::"l"(dst), "r"(src), "r"(bytes) : "memory");
}
__device__ __forceinline__ void cluster_sync_relaxed() {
    asm volatile("barrier.cluster.arrive.relaxed.aligned;\nbarrier.cluster.wait.aligned;\n" ::: "memory");
}
__device__ __forceinline__ void gdc_wait() { asm volatile("griddepcontrol.wait;\n" ::: "memory"); }
__device__ __forceinline__ void gdc_launch() { asm volatile("griddepcontrol.launch_dependents;\n" ::: "memory"); }
__device__ __forceinline__ uint32_t cluster_rank() {
    uint32_t r;
    asm volatile("mov.u32 %0, %%cluster_ctarank;\n" : "=r"(r));
    return r;
}
__device__ __forceinline__ bool elect_one() {
    uint32_t pred;
    asm volatile("{\n.reg .pred p;\nelect.sync _|p, 0xffffffff;\nselp.u32 %0, 1, 0, p;\n}\n" : "=r"(pred));
    return pred != 0;
}
__device__ __forceinline__ void wg_fence() { asm volatile("wgmma.fence.sync.aligned;\n" ::: "memory"); }
__device__ __forceinline__ void wg_commit() { asm volatile("wgmma.commit_group.sync.aligned;\n" ::: "memory"); }
template <int N> __device__ __forceinline__ void wg_wait() {
    asm volatile("wgmma.wait_group.sync.aligned %0;\n" ::"n"(N) : "memory");
}
template <int R> __device__ __forceinline__ void reg_inc() { asm volatile("setmaxnreg.inc.sync.aligned.u32 %0;\n" ::"n"(R)); }
template <int R> __device__ __forceinline__ void reg_dec() { asm volatile("setmaxnreg.dec.sync.aligned.u32 %0;\n" ::"n"(R)); }
__device__ __forceinline__ void bar_sync(int id, int n) { asm volatile("bar.sync %0, %1;\n" ::"r"(id), "r"(n) : "memory"); }
__device__ __forceinline__ void bar_arrive(int id, int n) { asm volatile("bar.arrive %0, %1;\n" ::"r"(id), "r"(n) : "memory"); }

__device__ __forceinline__ uint64_t make_desc(uint32_t saddr, uint32_t lbo, uint32_t sbo) {
    return (uint64_t)((saddr & 0x3FFFF) >> 4) | ((uint64_t)(lbo >> 4) << 16) | ((uint64_t)(sbo >> 4) << 32);
}

__device__ __forceinline__ void stg128_cs(void* p, uint32_t a, uint32_t b, uint32_t c, uint32_t d) {
    asm volatile("st.global.cs.v4.u32 [%0], {%1,%2,%3,%4};\n" ::"l"(p), "r"(a), "r"(b), "r"(c), "r"(d) : "memory");
}
__device__ __forceinline__ uint32_t pack_bf16(float lo, float hi) {
    uint32_t r;
    asm("cvt.rn.bf16x2.f32 %0, %1, %2;\n" : "=r"(r) : "f"(hi), "f"(lo));
    return r;
}
__device__ __forceinline__ float bf_lo(uint32_t v) { return __uint_as_float(v << 16); }
__device__ __forceinline__ float bf_hi(uint32_t v) { return __uint_as_float(v & 0xffff0000u); }
__device__ __forceinline__ uint32_t bf2_mul(uint32_t a, uint32_t b) {
    uint32_t r;
    asm("mul.rn.bf16x2 %0, %1, %2;\n" : "=r"(r) : "r"(a), "r"(b));
    return r;
}
__device__ __forceinline__ uint32_t bf2_fma(uint32_t a, uint32_t b, uint32_t c) {
    uint32_t r;
    asm("fma.rn.bf16x2 %0, %1, %2, %3;\n" : "=r"(r) : "r"(a), "r"(b), "r"(c));
    return r;
}
__device__ __forceinline__ uint32_t bf2_add(uint32_t a, uint32_t b) {
    uint32_t r;
    asm("add.rn.bf16x2 %0, %1, %2;\n" : "=r"(r) : "r"(a), "r"(b));
    return r;
}
constexpr float KAPPA = 0.3292034911525734f;
constexpr float GELU_C = 2.423681954311584f;
constexpr float HSCALE = 1.0f / (2.0f * KAPPA);
__device__ __forceinline__ uint32_t acc_exp(float z) { return max(__float_as_uint(z) >> 23, 10u); }
__device__ __forceinline__ void sched_break(int zero) {
    asm volatile("{\n.reg .pred p;\nsetp.ne.s32 p, %0, 0;\nSB_LOOP:\n@p nanosleep.u32 1;\n@p bra SB_LOOP;\n}\n" ::"r"(zero));
}

#define ACC8(d, o) "+f"(d[o + 0]), "+f"(d[o + 1]), "+f"(d[o + 2]), "+f"(d[o + 3]), "+f"(d[o + 4]), "+f"(d[o + 5]), "+f"(d[o + 6]), "+f"(d[o + 7])

#define ACCR8(d, o) "+r"(d[o + 0]), "+r"(d[o + 1]), "+r"(d[o + 2]), "+r"(d[o + 3]), "+r"(d[o + 4]), "+r"(d[o + 5]), "+r"(d[o + 6]), "+r"(d[o + 7])
__device__ __forceinline__ void mma_rs_n128(uint32_t (&d)[32], const uint32_t (&a)[4], uint64_t desc, int scale_d) {
    asm volatile(
        "{\n.reg .pred p;\nsetp.ne.b32 p, %37, 0;\n"
        "wgmma.mma_async.sync.aligned.m64n128k16.f16.f16.f16 "
        "{%0,%1,%2,%3,%4,%5,%6,%7,%8,%9,%10,%11,%12,%13,%14,%15,"
        "%16,%17,%18,%19,%20,%21,%22,%23,%24,%25,%26,%27,%28,%29,%30,%31},"
        "{%32,%33,%34,%35}, %36, p, 1, 1, 0;\n}\n"
        : ACCR8(d, 0), ACCR8(d, 8), ACCR8(d, 16), ACCR8(d, 24)
        : "r"(a[0]), "r"(a[1]), "r"(a[2]), "r"(a[3]), "l"(desc), "r"(scale_d));
}
__device__ __forceinline__ void mma_ss_n128(uint32_t (&d)[32], uint64_t da, uint64_t db) {
    asm volatile(
        "{\n.reg .pred p;\nsetp.ne.b32 p, %34, 0;\n"
        "wgmma.mma_async.sync.aligned.m64n128k16.f16.f16.f16 "
        "{%0,%1,%2,%3,%4,%5,%6,%7,%8,%9,%10,%11,%12,%13,%14,%15,"
        "%16,%17,%18,%19,%20,%21,%22,%23,%24,%25,%26,%27,%28,%29,%30,%31},"
        "%32, %33, p, 1, 1, 0, 0;\n}\n"
        : ACCR8(d, 0), ACCR8(d, 8), ACCR8(d, 16), ACCR8(d, 24)
        : "l"(da), "l"(db), "r"(1));
}
__device__ __forceinline__ uint32_t bf2_as_h2(uint32_t v) { return (v & 0x0fff0fffu) * 7u + v; }
__device__ __forceinline__ float h_lo(uint32_t v) {
    float r;
    asm("{\n.reg .b16 l, h;\nmov.b32 {l, h}, %1;\ncvt.f32.f16 %0, l;\n}\n" : "=f"(r) : "r"(v));
    return r;
}
__device__ __forceinline__ float h_hi(uint32_t v) {
    float r;
    asm("{\n.reg .b16 l, h;\nmov.b32 {l, h}, %1;\ncvt.f32.f16 %0, h;\n}\n" : "=f"(r) : "r"(v));
    return r;
}

__device__ __forceinline__ void mma_rs_n192(uint32_t (&d)[48], const uint4& a, uint64_t db, int scale_d) {
    asm volatile(
        "{\n.reg .pred p;\nsetp.ne.b32 p, %53, 0;\n"
        "wgmma.mma_async.sync.aligned.m64n192k16.f16.f16.f16 "
        "{%0,%1,%2,%3,%4,%5,%6,%7,%8,%9,%10,%11,%12,%13,%14,%15,"
        "%16,%17,%18,%19,%20,%21,%22,%23,%24,%25,%26,%27,%28,%29,%30,%31,"
        "%32,%33,%34,%35,%36,%37,%38,%39,%40,%41,%42,%43,%44,%45,%46,%47},"
        "{%48,%49,%50,%51}, %52, p, 1, 1, 0;\n}\n"
        : ACCR8(d, 0), ACCR8(d, 8), ACCR8(d, 16), ACCR8(d, 24), ACCR8(d, 32), ACCR8(d, 40)
        : "r"(a.x), "r"(a.y), "r"(a.z), "r"(a.w), "l"(db), "r"(scale_d));
}

__device__ __forceinline__ uint32_t pack_f16(float lo, float hi) {
    uint32_t r;
    asm("cvt.rn.f16x2.f32 %0, %1, %2;\n" : "=r"(r) : "f"(hi), "f"(lo));
    return r;
}

#define P1_IMG 900
constexpr int P1_SLOT = LN_TILE / 2, P1_NST = 4;
constexpr int P1_X = 16 * C_DIM * 2;
constexpr int P1_OFF_X = P1_SLOT * P1_NST;
constexpr int P1_OFF_A = P1_OFF_X + 2 * P1_X;
constexpr int P1_OFF_BAR = P1_OFF_A + 3 * 2048;
constexpr int P1_OFF_TILE = P1_OFF_BAR + (2 * P1_NST + 3 + 2 + 3 + 2) * 8;
constexpr int P1_OFF_DW = P1_OFF_TILE + 64;
constexpr int P1_OFF_RAW = P1_OFF_DW + C_DIM * 2;
constexpr int P1_SMEM = P1_OFF_RAW + 4 * C_DIM * 2;

__device__ __forceinline__ float rsqrt_fast(float x) {
    float r;
    asm("rsqrt.approx.ftz.f32 %0, %1;\n" : "=f"(r) : "f"(x));
    return r;
}
__device__ __forceinline__ float sum8(const uint32_t (&c)[4]) {
    const uint32_t u = bf2_add(bf2_add(c[0], c[1]), bf2_add(c[2], c[3]));
    return bf_lo(u) + bf_hi(u);
}
__device__ __forceinline__ void lds128(uint32_t (&v)[4], uint32_t a) {
    asm volatile("ld.shared.v4.u32 {%0,%1,%2,%3}, [%4];\n" : "=r"(v[0]), "=r"(v[1]), "=r"(v[2]), "=r"(v[3]) : "r"(a) : "memory");
}
template <class F>
__device__ __forceinline__ void ln_row(uint32_t (&v)[6][4], uint32_t sdw, F after_loads) {
    uint32_t c[4], s[4], d[4], nm;
#pragma unroll
    for (int i = 0; i < 6; i++) {
        lds128(d, sdw + i * 128);
        if (i == 0) {
#pragma unroll
            for (int k = 0; k < 4; k++) c[k] = bf2_mul(v[0][k], d[k]);
            const float p = sum8(c) * -0.125f;
            nm = pack_bf16(p, p);
        }
#pragma unroll
        for (int k = 0; k < 4; k++) {
            v[i][k] = bf2_fma(v[i][k], d[k], nm);
            s[k] = i ? bf2_add(v[i][k], s[k]) : v[i][k];
            c[k] = i ? bf2_fma(v[i][k], v[i][k], c[k]) : bf2_mul(v[i][k], v[i][k]);
        }
    }
    after_loads(c[0]);
    float m = fmaf(sum8(s), 1.0f / 48, -bf_lo(nm));
    float q = fmaf(-bf_lo(nm), fmaf(2.f, m, bf_lo(nm)), sum8(c) * (1.0f / 48));
#pragma unroll
    for (int o = 1; o < 8; o <<= 1) {
        m += __shfl_xor_sync(0xffffffffu, m, o);
        q += __shfl_xor_sync(0xffffffffu, q, o);
    }
    m *= 0.125f;
    const float r = KAPPA * rsqrt_fast(fmaxf(fmaf(-m, m, q * 0.125f), 0.f) + 1e-5f);
    const float e = (-bf_lo(nm) - m) * r * 0x1p-112f;
    const bool two = __any_sync(0xffffffffu, r < 0x1p-14f);
    const float r1 = r * (two ? 0x1p-56f : 0x1p-112f);
    uint32_t mul = pack_bf16(r1, r1), add = two ? 0u : pack_bf16(e, e);
#pragma unroll 1
    for (int it = !two; it < 2; it++) {
#pragma unroll
        for (int i = 0; i < 6; i++)
#pragma unroll
            for (int k = 0; k < 4; k++) v[i][k] = bf2_fma(v[i][k], mul, add);
        mul = 0x23802380u;
        add = pack_bf16(e, e);
    }
#pragma unroll
    for (int i = 0; i < 6; i++)
#pragma unroll
        for (int k = 0; k < 4; k++) v[i][k] = bf2_as_h2(v[i][k]);
}

__device__ __forceinline__ float gelu_s(float y) {
    float u = y * fmaf(y, y, GELU_C);
    float t;
    asm volatile("tanh.approx.f32 %0, %1;\n" : "=f"(t) : "f"(u));
    return fmaf(y, t, y);
}
__device__ __forceinline__ void p1_pack(int c, uint32_t (&p)[4], uint32_t (&dd)[4]) {
#pragma unroll
    for (int u = 0; u < 4; u++) {
        if ((c & 3) == 0) dd[u] = p[u];
        else {
            uint32_t n = dd[u];
            if ((c & 3) == 1) n = __byte_perm(n, 0, 0x2301);
            if ((c & 3) == 2) {
                dd[u] = __byte_perm(n >> 3, n >> 1, 0x6341);
                n = __byte_perm(n >> 3, n >> 1, 0x7250);
            }
            asm("lop3.b32 %0, %0, %1, 0x40074007, 0xd8;\n" : "+r"(p[u]) : "r"(n));
        }
    }
}
__device__ __forceinline__ void p1_store(int c, const uint32_t (&p)[4], uint8_t* hptr) {
    if (c & 3) stg128_cs(hptr + (c >> 2) * H_HALF + ((c & 3) - 1) * 512, p[0], p[1], p[2], p[3]);
}

template <bool GEN>
__device__ __forceinline__ void p1_epilogue(uint32_t (&acc)[32], float (&ssq)[2], uint32_t sc2, uint8_t* hp, int zero) {
    uint32_t sq[2], dd[4];
#pragma unroll
    for (int c = 0; c < 8; c++) {
        if (GEN) sched_break(zero);
        uint32_t p[4];
#pragma unroll
        for (int u = 0; u < 4; u++) {
            const uint32_t y = acc[8 * (c >> 1) + 2 * u + (c & 1)];
            if (GEN) {
                const float sc = c & 1 ? bf_hi(sc2) : bf_lo(sc2), fs = __uint_as_float(0x78000000u - __float_as_uint(sc));
                const float g0 = gelu_s(h_lo(y) * fs), g1 = gelu_s(h_hi(y) * fs);
                ssq[c & 1] = fmaf(g1, g1, fmaf(g0, g0, ssq[c & 1]));
                p[u] = pack_f16(g0 * sc, g1 * sc);
            } else {
                uint32_t g;
                asm("{\n.reg .b32 w;\n"
                    "fma.rn.f16x2 w, %1, %1, %2;\n"
                    "mul.rn.f16x2 w, w, %1;\n"
                    "tanh.approx.f16x2 w, w;\n"
                    "fma.rn.f16x2 %0, %1, w, %1;\n}\n" : "=r"(g) : "r"(y), "r"(0x40d940d9u));
                acc[8 * (c >> 1) + 2 * u + (c & 1)] = g;
                if (c < 2 && u == 0) asm("mul.rn.f16x2 %0, %1, %1;\n" : "=r"(sq[c & 1]) : "r"(g));
                else asm("fma.rn.f16x2 %0, %1, %1, %0;\n" : "+r"(sq[c & 1]) : "r"(g));
                if (c & 1) asm("{\n.reg .b16 l, h;\n.reg .b32 f;\nmov.b32 {l, h}, %2;\nmov.b32 f, {h, h};\nmul.rn.f16x2 %0, %1, f;\n}\n" : "=r"(p[u]) : "r"(g), "r"(sc2));
                else asm("{\n.reg .b16 l, h;\n.reg .b32 f;\nmov.b32 {l, h}, %2;\nmov.b32 f, {l, l};\nmul.rn.f16x2 %0, %1, f;\n}\n" : "=r"(p[u]) : "r"(g), "r"(sc2));
            }
        }
        p1_pack(c, p, dd);
        if (c & 3) {
#pragma unroll
            for (int u = 0; u < 4; u++) acc[4 * (c - 1 - (c >> 2)) + u] = p[u];
        }
        p1_store(c, p, hp);
    }
    if (!GEN) {
#pragma unroll
        for (int r = 0; r < 2; r++) ssq[r] += h_lo(sq[r]) + h_hi(sq[r]);
    }
}
__device__ __forceinline__ void p1_consumer(const uint32_t (&a)[24][4], uint32_t sc2, bool gen, uint32_t sbase, int wg, int nwg, int cb, int first,
                                            int w, int lane, int zero) {
    const uint32_t bar_full = sbase + P1_OFF_BAR, bar_empty = bar_full + P1_NST * 8;
    const uint32_t empty_remote = mapa(bar_empty, lane & 1);
    const int g = lane >> 2, q = lane & 3, turn = wg + 1 == nwg ? 1 : wg + 2;
    float ssq[2] = {0.f, 0.f};
    uint32_t acc[32] = {};
    TSTAMP(0, 1);

    uint8_t* hp = reinterpret_cast<uint8_t*>(g_h) + (size_t)first * (2 * H_TILE) + ((cb * 2 + (w >> 1)) * H_STEP + (w & 1) * 1536) + g * 64 + (q ^ (g >> 1)) * 16;
    const uint64_t desc_base = make_desc(sbase, 16, 1024) | (1ull << 62);
    const uint64_t da = make_desc(sbase + P1_OFF_A + wg * 2048, 128, 256);
#pragma unroll 1
    for (int i = 0;; i++) {
        const int s0 = (i & 1) * 16, par = (i >> 1) & 1;
        const uint64_t d0 = desc_base + (uint64_t)((i & 1) * (LN_TILE / 16));
        TRACE(wg, i, 0);
        mbar_wait(bar_full + s0, par);
        bar_sync(1 + wg, 256);
        TRACE(wg, i, 1);
        uint32_t step, more;
        wg_fence();
#pragma unroll
        for (int k = 0; k < 24; k++) {
            if (k == 12) mbar_wait(bar_full + s0 + 8, par);
            const uint64_t db = d0 + (uint64_t)((k >> 2) * 1024 + (k & 3) * 2);
            if (k < 23) mma_rs_n128(acc, a[k], db, k ? 1 : zero);
            else mma_ss_n128(acc, da, db);
            if (k == 23) bar_arrive(turn, 256);
            if (k % 12 == 11) wg_commit();
        }
        asm volatile("ld.shared.v2.u32 {%0, %1}, [%2];\n" : "=r"(step), "=r"(more) : "r"(sbase + P1_OFF_TILE + (i & 3) * 16) : "memory");
        TRACE(wg, i, 2);
        wg_wait<1>();
        if (lane < 2) mbar_arrive_cluster(empty_remote + s0);
        hp += step;
        TRACE(wg, i, 3);
        wg_wait<0>();
        TRACE(wg, i, 4);
        if (lane < 2) mbar_arrive_cluster(empty_remote + s0 + 8);
        if (gen) p1_epilogue<true>(acc, ssq, sc2, hp, zero);
        else p1_epilogue<false>(acc, ssq, sc2, hp, zero);
        if (!more) break;
    }
    TSTAMP(0, 21);
    if (wg == 0) bar_sync(1, 256);
    uint32_t par;
    asm volatile("ld.shared.u32 %0, [%1];\n" : "=r"(par) : "r"(sbase + P1_OFF_TILE - 4) : "memory");
    float* sums = g_sums[par];
#pragma unroll
    for (int r = 0; r < 2; r++) {
        ssq[r] += __shfl_xor_sync(0xffffffffu, ssq[r], 1);
        ssq[r] += __shfl_xor_sync(0xffffffffu, ssq[r], 2);
        if (q == 0) atomicAdd(sums + cb * 64 + w * 16 + r * 8 + g, ssq[r]);
    }
}

__device__ __forceinline__ void p1_w2(const __nv_bfloat16* __restrict__ w2, const __nv_bfloat16* __restrict__ grn_b, int w, int lane) {
    const int gw = (blockIdx.x - 8 * NGRP) * 4 + w;
    float* sums = g_sums[__ldcg(&g_epoch) & 1] + HID;
    flag_wait<true>(&g_flag[40][1][0], 12);
    {
        const int col = gw % 6 * 64 + lane * 2;
        float bsum[2] = {0.f, 0.f}, asum[2] = {0.f, 0.f};
#pragma unroll 4
        for (int kk = 0; kk < 192; kk++) {
            const int k = gw / 6 * 192 + kk;
            const uint32_t v = *reinterpret_cast<const uint32_t*>(w2 + k * C_DIM + col);
            const float b = __bfloat162float(grn_b[k]), f = __uint_as_float(__ldcg(&g_ex[k]) << 23);
            bsum[0] = fmaf(b, bf_lo(v), bsum[0]);
            bsum[1] = fmaf(b, bf_hi(v), bsum[1]);
            asum[0] = fmaf(f, fabsf(bf_lo(v)), asum[0]);
            asum[1] = fmaf(f, fabsf(bf_hi(v)), asum[1]);
        }
#pragma unroll
        for (int j = 0; j < 2; j++) {
            atomicAdd(sums + col + j, bsum[j]);
            atomicAdd(sums + C_DIM + col + j, asum[j]);
        }
        __threadfence();
        __syncwarp();
        if (lane == 0) asm volatile("red.relaxed.gpu.global.add.u32 [%0], 1;\n" ::"l"(&g_flag[LN_RING + 2][0][0]) : "memory");
    }
    while (*(volatile unsigned*)&g_flag[P1_IMG % LN_RING][1][0] < 12 * (P1_IMG / LN_RING + 1)) {
        __nanosleep(2000);
        SAFE_BREAK
    }
    flag_wait<true>(&g_flag[LN_RING + 2][0][0], 48);
    float z = 0.f;
#pragma unroll
    for (int j = 0; j < C_DIM / 32; j++) z = fmaxf(z, __ldcg(sums + C_DIM + j * 32 + lane));
    const float sc = __uint_as_float((263u - acc_exp(__uint_as_float(__reduce_max_sync(0xffffffffu, __float_as_uint(z))))) << 23);
    const int np = gw % 6 * 64 + lane * 2;
#pragma unroll 2
    for (int cc = 0; cc < 24; cc++) {
        const int c = gw / 6 * 24 + cc;
        uint32_t v[8], o[2][4];
#pragma unroll
        for (int e = 0; e < 8; e++) v[e] = *reinterpret_cast<const uint32_t*>(w2 + (c * 8 + e) * C_DIM + perm32(np));
#pragma unroll
        for (int e = 0; e < 4; e++) {
            const uint2 t = __ldcg(reinterpret_cast<const uint2*>(g_ex) + c * 4 + e);
            const float f0 = __uint_as_float(t.x << 23), f1 = __uint_as_float(t.y << 23);
            o[0][e] = pack_f16(bf_lo(v[2 * e]) * f0 * sc, bf_lo(v[2 * e + 1]) * f1 * sc);
            o[1][e] = pack_f16(bf_hi(v[2 * e]) * f0 * sc, bf_hi(v[2 * e + 1]) * f1 * sc);
        }
#pragma unroll
        for (int j = 0; j < 2; j++)
            g_w2img[0][(((c >> 1) * 48 + (np >> 3)) * 2 + (c & 1)) * 8 + (np & 7) + j] = make_uint4(o[j][0], o[j][1], o[j][2], o[j][3]);
    }
    asm volatile("fence.proxy.async.global;\n" ::: "memory");
    __threadfence();
    __syncwarp();
    if (lane == 0) asm volatile("red.relaxed.gpu.global.add.u32 [%0], 1;\n" ::"l"(&g_img[0]) : "memory");
}

__global__ void __cluster_dims__(2, 1, 1) __launch_bounds__(512, 1)
pass1_kernel(const __grid_constant__ CUtensorMap wmap, const __nv_bfloat16* __restrict__ x, const __nv_bfloat16* __restrict__ dw,
             const __nv_bfloat16* __restrict__ w1, const __nv_bfloat16* __restrict__ w2, const __nv_bfloat16* __restrict__ grn_b, int zero) {
    extern __shared__ __align__(1024) uint8_t smem[];
    const uint32_t sbase = smem_u32(smem);
    const uint32_t bar_full = sbase + P1_OFF_BAR, bar_empty = bar_full + P1_NST * 8, bar_w = bar_empty + P1_NST * 8;
    const uint32_t bar_xfull = bar_w + 24, bar_raw = bar_xfull + 16, bar_done = bar_raw + 8, bar_peer = bar_raw + 16;
    const int tid = threadIdx.x;
    const int warp = __shfl_sync(0xffffffffu, tid >> 5, 0), lane = tid & 31;
    const uint32_t rank = cluster_rank();
    const int cl = blockIdx.x >> 1, first = min(cl >> 2, NGRP);
    const bool small = cl >= 4 * NGRP;
    const int nwg = small ? 2 : 3, cb0 = small ? (blockIdx.x - 8 * NGRP) * 2 : (blockIdx.x & 7) * 3;
    const int tile1 = p1_tile(small ? 0 : first, small), tile2 = p1_tile(small ? 1 : first + NGRP, small);
    uint8_t* const ring = reinterpret_cast<uint8_t*>(g_ln);
    const uint32_t sdw = sbase + P1_OFF_DW + (lane & 7) * 16;
    const uint8_t* xsrc = reinterpret_cast<const uint8_t*>(x) + (size_t)(NFIRST * 4 + blockIdx.x) * (2 * P1_X);
    auto ring_row = [&](int p) {
        const int n = (blockIdx.x & 2) * 32 + (lane >> 3) * 8 + p * 2 + (blockIdx.x & 1);
        return n * 128 + (((lane ^ n) & 7) << 4);
    };
    const int n1 = (warp & 1) * 32 + (lane & 24) + (warp & 6) + (warp >> 3);
    const int px = tid >> 3;
    const uint32_t src1 = sbase + (px < 60 ? (rank ^ 1) * 8192 + px / 10 * (16384 - 7680) : P1_OFF_RAW - 60 * 768) + px * 768 + (lane & 7) * 16;
    const uint32_t dst1 = sbase + (rank * 64 + n1) * 128 + (((lane ^ n1) & 7) << 4);
    auto store_row = [&](const uint32_t (&v)[6][4], uint8_t* dst, bool local) {
        if (local) {
#pragma unroll
            for (int j = 0; j < 6; j++)
                asm volatile("st.shared.v4.u32 [%4], {%0,%1,%2,%3};\n" ::"r"(v[j][0]), "r"(v[j][1]), "r"(v[j][2]), "r"(v[j][3]), "r"(dst1 + j * 16384) : "memory");
        } else {
#pragma unroll
            for (int j = 0; j < 6; j++)
                asm volatile("st.global.v4.u32 [%4], {%0,%1,%2,%3};\n" ::"r"(v[j][0]), "r"(v[j][1]), "r"(v[j][2]), "r"(v[j][3]), "l"(dst + j * 16384) : "memory");
        }
    };
    auto load_w1 = [&](int i) {
        mbar_expect_tx(bar_w + i * 8, P1_SLOT);
        tma2(sbase + (2 + (i & 1)) * P1_SLOT, &wmap, (cb0 + i) * 64, 0, bar_w + i * 8);
        tma2(sbase + (2 + (i & 1)) * P1_SLOT + P1_SLOT / 2, &wmap, (cb0 + i) * 64, 192, bar_w + i * 8);
    };

    TSTAMP(0, 0);
    TRACEW(110 + warp, 0);

    if (warp >= 12) {
        reg_dec<56>();
        asm volatile("barrier.cluster.arrive.relaxed.aligned;\n" ::: "memory");
        asm volatile("barrier.cluster.wait.aligned;\n" ::: "memory");
        {
            const uint32_t xbar = bar_xfull + (warp & 1) * 8, xdst = sbase + P1_OFF_X + (warp & 1) * P1_X;
            uint32_t src = src1;
            const int row0 = ring_row((warp & 1) * 2);
            int slot = blockIdx.x >> 2, used = 0;
            xsrc += (warp & 1) * P1_X;
            auto next = [&]() {
                xsrc += (size_t)LN_STEP * 8 * P1_X;
                if (elect_one()) {
                    mbar_expect_tx(xbar, P1_X);
                    bulk_g2s(xdst, xsrc, P1_X, xbar);
                }
                __syncwarp();
            };
#pragma unroll 1
            for (int i = -1; i * LN_STEP + (int)(blockIdx.x >> 2) < NT_RING; i++) {
                if (warp == 14) TRACEW(128 + i, 0);
#pragma unroll 1
                for (int ps = i < 0 ? -4 : 0; ps < (i > 0 ? 4 : i + 2); ps += i < 0 ? 4 : 1) {
                    if (ps == 0) {
                        if (i < 0) mbar_wait(bar_raw, 0);
                        else {
                            if (i == 1) {
                                bar_sync(9, 192);
                                next();
                            }
                            if (used) flag_wait<false>(&g_flag[slot][1][0], used);
                            mbar_wait(xbar, i & 1);
                        }
                        if (warp == 14) TRACEW(128 + i, 1);
                    }
                    uint32_t v[6][4];
#pragma unroll
                    for (int j = 0; j < 6; j++) lds128(v[j], src + (ps & 3) * (4 * C_DIM * 2) + j * 128);
                    ln_row(v, sdw, [&](uint32_t dep) {
                        if (i < 0 && ps == 0 && lane == 0) mbar_arrive_cluster(mapa(bar_peer, rank ^ 1) + (dep & zero));
                        if (ps == 3 && (i + 1) * LN_STEP + (blockIdx.x >> 2) < NT_RING && !__any_sync(0xffffffffu, dep & zero)) next();
                    });
                    store_row(v, ring + (slot * LN_TILE + (ps & 1) * 4096 + (row0 ^ (ps & 2) * 144)), i < 0);
                }
                if (warp == 14) TRACEW(128 + i, 2);
                if (i < 0) {
                    asm volatile("fence.proxy.async.shared::cta;\n" ::: "memory");
                    bar_arrive(8, 512);
                    if (warp != 13) bar_arrive(4, 512);
                    if (warp < 14 || small) break;
                    src = xdst + (lane >> 3) * (C_DIM * 2) + (lane & 7) * 16;
                } else {
                    asm volatile("fence.proxy.async.global;\nfence.acq_rel.cta;\n" ::: "memory");
                    if (i) mbar_wait(bar_done, ~i & 1);
                    __syncwarp();
                    if (lane == 0) mbar_arrive(bar_done);
                    if ((slot += LN_STEP) >= LN_RING) { slot -= LN_RING; used += 12; }
                }
            }
        }
        if (warp == 12) {
            const uint32_t ep = g_epoch & 1;
            asm volatile("st.shared.u32 [%0], %1;\n" ::"r"(sbase + P1_OFF_TILE - 4), "r"(ep) : "memory");
            if (blockIdx.x == 18) g_par = ep;
            if (blockIdx.x < 18) reinterpret_cast<float4*>(g_sums[ep ^ 1])[blockIdx.x * 32 + lane] = make_float4(0.f, 0.f, 0.f, 0.f);
            int prev = first - NFIRST, t = tile1, next = tile2;
            const uint32_t rbase = mapa(sbase, lane & 1);
            int i = 1;
#pragma unroll 1
            for (; t < NT_RING; i++) {
                const int s0 = (i & 1) * 2, par = ((i + 1) >> 1 & 1) ^ 1;
                const int round = t / LN_RING, slot = t - round * LN_RING;
                const uint8_t* src = ring + slot * LN_TILE + rank * (P1_SLOT / 2);
                int draw = i + 1;
                if (rank == 0 && lane == 0 && !small) draw = 2 * NGRP + atomicAdd(&g_flag[LN_RING + ((cl >> 1) & 1)][cl & 1][0], 1u);
                flag_wait<true>(&g_flag[slot][0][0], 4 * round + 4);
                TRACEW(i, 2);
                asm volatile("fence.proxy.async.global;\n" ::: "memory");
                draw = p1_tile(__shfl_sync(0xffffffffu, draw, 0), small);
#pragma unroll
                for (int h = 0; h < 2; h++) {
                    mbar_wait(bar_empty + (s0 + h) * 8, par);
                    TRACEW(i, 4 + h);
                    if (elect_one()) {
                        mbar_expect_tx(bar_full + (s0 + h) * 8, P1_SLOT + 16 - 16 * h);
                        bulk_g2s_mc(sbase + (s0 + h) * P1_SLOT + rank * (P1_SLOT / 2), src + h * P1_SLOT, P1_SLOT / 2, bar_full + (s0 + h) * 8, (uint16_t)3);
                    }
                    __syncwarp();
                    if (h == 0 && rank == 0 && lane < 2)
                        asm volatile("st.async.shared::cluster.mbarrier::complete_tx::bytes.v4.u32 [%0], {%1, %2, %3, %3}, [%4];\n"
                                     ::"r"(rbase + P1_OFF_TILE + (i & 3) * 16), "r"((t - prev) * (2 * H_TILE)), "r"((int)(next < NT_RING)), "r"(draw),
                                       "r"(rbase + P1_OFF_BAR + s0 * 8) : "memory");
                }
                prev = t;
                t = next;
                next = draw;
                if (rank != 0) {
                    mbar_wait(bar_full + s0 * 8, (i >> 1) & 1);
                    mbar_wait(bar_full + s0 * 8 + 8, (i >> 1) & 1);
                    if (lane == 0) asm volatile("red.relaxed.gpu.global.add.u32 [%0], %1;\n" ::"l"(&g_flag[slot][1][0]), "r"(nwg) : "memory");
                    asm volatile("ld.shared.u32 %0, [%1];\n" : "=r"(next) : "r"(sbase + P1_OFF_TILE + (i & 3) * 16 + 8) : "memory");
                    TRACEW(i, 3);
                }
            }
#pragma unroll 1
            for (int j = 2 * i; j < 2 * i + 4; j++) mbar_wait(bar_empty + (j & 3) * 8, ((j + 2) >> 2 & 1) ^ 1);
        } else if (warp == 13) {
            {
                bar_sync(4, 512);
                mbar_wait(bar_peer, 0);
                const uint32_t o = lane * 16384 + rank * 8192, peer = mapa(sbase, rank ^ 1);
                if (lane < 6)
                    asm volatile("cp.async.bulk.shared::cluster.shared::cta.mbarrier::complete_tx::bytes [%0], [%1], 8192, [%2];\n"
                                 ::"r"(peer + o), "r"(sbase + o), "r"(peer + P1_OFF_BAR + (lane >= 3 ? 8 : 0)) : "memory");
                __syncwarp();
            }
#pragma unroll 1
            for (int i = 0; !small && i * LN_STEP + (blockIdx.x >> 2) < NT_RING; i++) {
                mbar_wait(bar_done, i & 1);
                asm volatile("fence.proxy.async.global;\n" ::: "memory");
                if (lane == 0) {
                    mbar_arrive(bar_done);
                    asm volatile("red.release.gpu.global.add.u32 [%0], 1;\n" ::"l"(&g_flag[(blockIdx.x >> 2) + i % LN_DEPTH * LN_STEP][0][0]) : "memory");
                }
                __syncwarp();
                TRACEW(128 + i, 3);
            }
            flag_wait<true>(&g_flag[LN_RING + 2][0][0], 48);
        }
    } else {
        if (tid == 0) {
            mbar_init(bar_raw, 1);
            mbar_init(bar_xfull, 1);
            mbar_init(bar_xfull + 8, 1);
            mbar_init(bar_w, 1);
            mbar_init(bar_w + 8, 1);
            asm volatile("fence.mbarrier_init.release.cluster;\n" ::: "memory");
            mbar_expect_tx(bar_raw, P1_SLOT + C_DIM * 2);
            bulk_g2s(sbase + P1_OFF_DW, dw, C_DIM * 2, bar_raw);
            for (int i = 0; i < 7; i++)
                bulk_g2s(sbase + (i < 6 ? i * 16384 + (rank ^ 1) * 8192 : P1_OFF_RAW), x + (size_t)(first * 128 + rank * 64 + i * 10) * C_DIM, i < 6 ? 7680 : 3072, bar_raw);
            if (blockIdx.x < 128)
                asm volatile("cp.async.bulk.prefetch.L2.global [%0], 9216;\n" ::"l"(w1 + blockIdx.x * 4608) : "memory");
            load_w1(0);
            for (int i = 0; i < 2 && !small; i++) {
                mbar_expect_tx(bar_xfull + i * 8, P1_X);
                bulk_g2s(sbase + P1_OFF_X + i * P1_X, xsrc + i * P1_X, P1_X, bar_xfull + i * 8);
            }
            load_w1(1);
        }
        if (tid == 32) {
            mbar_init(bar_done, 3);
            mbar_init(bar_peer, 16);
            mbar_init(bar_w + 16, 1);
            asm volatile("fence.mbarrier_init.release.cluster;\n" ::: "memory");
        }
        if (tid == 64) {
            asm volatile("st.shared.v2.u32 [%0], {0, 1};\n" ::"r"(sbase + P1_OFF_TILE) : "memory");
            for (int i = 0; i < P1_NST; i++) {
                mbar_init(bar_full + i * 8, 1);
                mbar_init(bar_empty + i * 8, 8 * nwg);
                if (i < 2) mbar_expect_tx(bar_full + i * 8, P1_SLOT / 2);
            }
            asm volatile("fence.mbarrier_init.release.cluster;\n" ::: "memory");
            if (blockIdx.x < 64) (&g_half[0][0])[blockIdx.x] = 0;
            else if (blockIdx.x == 64) g_prog = 0;
            else if (blockIdx.x < 67) g_img[blockIdx.x - 65] = 0;
        }
        __syncwarp();
        asm volatile("barrier.cluster.arrive.relaxed.aligned;\n" ::: "memory");
        reg_inc<152>();
        TRACEW(110 + warp, 1);
        const int wg = warp >> 2, w = warp & 3;
        gdc_launch();
        asm volatile("barrier.cluster.wait.aligned;\n" ::: "memory");
        uint32_t a[24][4], ex[2], gen = 0;
        const uint32_t wsrc = sbase + (2 + (wg & 1)) * P1_SLOT + ((lane >> 4) * 8 + (lane & 7)) * 128 + (((2 * w + ((lane >> 3) & 1)) ^ (lane & 7)) << 4);
#pragma unroll 1
        for (int it = 0; it < 2; it++) {
#pragma unroll 1
            for (int ps = it - 1; ps < (it ? (wg == 2 && !small ? 2 : 1) : wg - 2); ps++) {
                if (ps == 0) mbar_wait(bar_raw, 0);
                if (ps == 1) mbar_wait(bar_xfull + (w >> 1) * 8, 0);
                TRACEW(110 + warp, 2 + (ps == 0));
                uint32_t v[6][4];
                const uint32_t src = ps < 1 ? src1 : sbase + P1_OFF_X + ((w >> 1) * 16 + (w & 1) * 4 + 8 + (lane >> 3)) * 768 + (lane & 7) * 16;
#pragma unroll
                for (int j = 0; j < 6; j++) lds128(v[j], src + j * 128);
                ln_row(v, sdw, [&](uint32_t dep) {
                    if (ps == 0 && lane == 0) mbar_arrive_cluster(mapa(bar_peer, rank ^ 1) + (dep & zero));
                    if (ps == 1) bar_arrive(9, 192);
                });
                store_row(v, ring + ((blockIdx.x >> 2) * LN_TILE + (w & 1) * 4096 + ring_row((w & 2) + 1)), ps < 1);
                if (ps == 0) {
                    asm volatile("fence.proxy.async.shared::cta;\n" ::: "memory");
                    bar_arrive(4, 512);
                    if (wg) bar_arrive(8, 512);
                    if (wg == 1) bar_arrive(1, 256);
                    TRACEW(110 + warp, 4);
                }
                if (ps == 1) {
                    asm volatile("fence.proxy.async.global;\n" ::: "memory");
                    bar_sync(7, 128);
                    if (tid == 256) mbar_arrive(bar_done);
                }
            }
            if (it) {
                if (wg == nwg) {
                    p1_w2(w2, grn_b, w, lane);
                    return;
                }
                mbar_wait(bar_w + wg * 8, 0);
            }
            TRACEW(110 + warp, 5);
            if (it || wg == 0) {
#pragma unroll
            for (int k = 0; k < 24; k++) ldsm4t(a[k], wsrc + k * 2048);
            if (it && wg == 0 && !small) {
                bar_sync(5, 128);
                if (tid == 0) load_w1(2);
                __syncwarp();
            }
#pragma unroll
            for (int r = 0; r < 2; r++) {
                float t = 0.f;
#pragma unroll
                for (int j = 0; j < 6; j++) {
                    uint32_t c = bf2_mul(a[4 * j][r], a[4 * j][r]);
#pragma unroll
                    for (int k = 1; k < 8; k++) c = bf2_fma(a[4 * j + k / 2][r + (k & 1) * 2], a[4 * j + k / 2][r + (k & 1) * 2], c);
                    t += bf_lo(c) + bf_hi(c);
                }
                t += __shfl_xor_sync(0xffffffffu, t, 1);
                t += __shfl_xor_sync(0xffffffffu, t, 2);
                asm("sqrt.approx.f32 %0, %0;\n" : "+f"(t));
                ex[r] = min(max(__float_as_uint(13.9f * t) >> 23, 72u), 198u);
            }
            asm volatile("{\n.reg .pred p;\nsetp.gt.u32 p, %1, 7;\nbar.red.or.pred p, %2, 128, p;\nselp.u32 %0, 1, 0, p;\n}\n"
                         : "=r"(gen) : "r"(max(ex[0] - 125u, ex[1] - 125u)), "r"(5 + wg) : "memory");
            gen = __shfl_sync(0xffffffffu, gen, 0) & it;
            if (it) {
                if ((lane & 3) < 2) g_ex[(cb0 + wg) * 64 + w * 16 + (lane & 1) * 8 + (lane >> 2)] = lane & 1 ? ex[1] : ex[0];
                if (lane < 4) mbar_arrive_cluster(mapa(bar_empty, lane & 1) + (2 + (lane >> 1)) * 8);
                __syncwarp();
            }
            }
            if (gen) {
#pragma unroll
                for (int k = 0; k < 24; k++)
#pragma unroll
                    for (int j = 0; j < 4; j++) a[k][j] = bf2_mul(a[k][j], (268u - ex[j & 1]) * 0x00800080u);
            }
            if (it || wg == 1) {
#pragma unroll
                for (int k = 0; k < 24; k++)
#pragma unroll
                    for (int j = 0; j < 4; j++) {
                        a[k][j] = bf2_as_h2(bf2_mul(a[k][j], 0x07800780u));
                        asm volatile("" : "+r"(a[k][j]));
                    }
            }
            TRACEW(110 + warp, 6);
        }
#pragma unroll
        for (int j = 0; j < 4; j++)
            asm volatile("st.shared.u32 [%0], %1;\n" ::"r"(sbase + P1_OFF_A + warp * 512 + (j & 1) * 256 + (j >> 1) * 128 + lane * 4), "r"(a[23][j]) : "memory");
        asm volatile("fence.proxy.async.shared::cta;\n" ::: "memory");
        if (wg == 0) bar_sync(8, 512);
        TRACEW(110 + warp, 7);
        const uint32_t ex2 = ex[0] | ex[1] << 16;
        p1_consumer(a, gen ? 0x7f007f00u - (ex2 << 7) : (0x008e008eu - ex2) << 10, gen, sbase, wg, nwg, cb0 + wg, first, w, lane, zero);
        TSTAMP(0, 30);
    }
}

#define P2_NB_ 5
#define P2_NA_ 5
#define P2_DELTA_ 7
#define P2_EXTRA 0
#define P2_HSLEEP 64
#define P2_PSLEEP 100
#define P2_T0 5
#define P2_TS 11
constexpr int P2_B = 24576, P2_NB = P2_NB_;
constexpr int P2_A = 3072, P2_NA = P2_NA_;
constexpr int P2_XROW = C_DIM * 2;
constexpr int P2_OFF_A = P2_B * P2_NB;
constexpr int P2_OFF_X = P2_OFF_A + 3 * P2_NA * P2_A;
constexpr int P2_XHALF = 32 * P2_XROW + 64;
constexpr int P2_OFF_BIAS = P2_OFF_X + 64 * P2_XROW + 64;
constexpr int P2_OFF_GRN = P2_OFF_BIAS + C_DIM * 4;
constexpr int P2_OFF_BAR = P2_OFF_GRN + HID * 2;
constexpr int P2_SMEM = P2_OFF_BAR + (2 * P2_NB + 6 * P2_NA + 3) * 8;
#define P2_LAG_ 17
constexpr int P2_LAG = P2_LAG_;
constexpr int P2_NCL = NUM_CTAS / 2, P2_ITEMS = NT128 / P2_NCL, P2_SHARED = NT128 - P2_ITEMS * P2_NCL;
constexpr int P2_POS = P2_LAG * (P2_ITEMS - 1) + 48;
__device__ __forceinline__ int p2_start(int n) { return n < 0 ? 0 : n == P2_ITEMS ? P2_POS - 24 : P2_LAG * n; }
constexpr int P2_FOLD = P2_LAG - 1 + (P2_LAG & 1);
constexpr int P2_XC = 8 * P2_XROW;
constexpr int P2_DELTA = P2_DELTA_;
__device__ __forceinline__ int p2_tile(int cl, int n) {
    return n == 0 ? NT128 - 1 - cl : n < 0 || n == P2_ITEMS ? NT128 - 1 - P2_NCL - (cl >> 1) : cl + P2_NCL * (n - 1);
}

constexpr int P2_EG = 2;
__device__ __forceinline__ void p2_epilogue(const uint32_t (&acc0)[48], const uint32_t (&acc1)[48], uint32_t sx, uint32_t sb, float up, int zero) {
    uint32_t v[2][P2_EG][4];
    float b[2][8];
    auto load = [&](int c, uint32_t a) {
#pragma unroll
        for (int j = 0; j < 2; j++)
            asm volatile("ld.shared.v4.f32 {%0,%1,%2,%3}, [%4];\n" : "=f"(b[c & 1][4 * j]), "=f"(b[c & 1][4 * j + 1]), "=f"(b[c & 1][4 * j + 2]), "=f"(b[c & 1][4 * j + 3])
                         : "r"(sb + c * 128 + j * 16) : "memory");
#pragma unroll
        for (int j = 0; j < P2_EG; j++) {
            const int u = c * P2_EG + j;
            asm volatile("ld.shared.v4.u32 {%0,%1,%2,%3}, [%4];\n" : "=r"(v[c & 1][j][0]), "=r"(v[c & 1][j][1]), "=r"(v[c & 1][j][2]), "=r"(v[c & 1][j][3])
                         : "r"(a + (u >> 1) * 64 + (u & 1) * 4 * P2_XROW) : "memory");
        }
    };
    load(0, sx);
#pragma unroll
    for (int c = 0; c < 24 / P2_EG; c++) {
        if (c + 1 < 24 / P2_EG) load(c + 1, sx + (v[c & 1][P2_EG - 1][0] & zero));
#pragma unroll
        for (int j = 0; j < P2_EG; j++) {
            const int u = c * P2_EG + j, i = 8 * ((u >> 1) % 6) + (u & 1);
            const uint32_t (&acc)[48] = u < 12 ? acc0 : acc1;
            uint32_t (&w)[4] = v[c & 1][j];
#pragma unroll
            for (int e = 0; e < 4; e++)
                w[e] = bf2_add(pack_bf16(fmaf(h_lo(acc[i + 2 * e]), up, b[c & 1][2 * e]), fmaf(h_hi(acc[i + 2 * e]), up, b[c & 1][2 * e + 1])), w[e]);
            asm volatile("st.shared.v4.u32 [%4], {%0,%1,%2,%3};\n" ::"r"(w[0]), "r"(w[1]), "r"(w[2]), "r"(w[3]),
                         "r"(sx + (u >> 1) * 64 + (u & 1) * 4 * P2_XROW) : "memory");
        }
    }
}

__device__ __forceinline__ void p2_unpack(uint4& u, uint32_t o1, uint32_t o2, uint32_t o3) {
    u.z = o1 & 0xbff8bff8u;
    u.y = o2 & 0xbff8bff8u;
    u.w = o3 & 0xbff8bff8u;
    u.x = (__byte_perm(o1, 0, 0x2301) & 0x07400740u) | ((__byte_perm(o2, o3, 0x6240) << 3) & 0x38383838u) | ((__byte_perm(o2, o3, 0x3715) << 1) & 0x80808080u);
}
__device__ __forceinline__ uint32_t h2_mul(uint32_t a, uint32_t b) {
    uint32_t r;
    asm("mul.rn.f16x2 %0, %1, %2;\n" : "=r"(r) : "r"(a), "r"(b));
    return r;
}
__device__ __forceinline__ void p2_epilogue_add(const uint32_t (&acc)[48], uint8_t* o, float f, int zero) {
#pragma unroll
    for (int t = 0; t < 12; t++) {
        uint32_t v[4];
#pragma unroll
        for (int e = 0; e < 4; e++) {
            v[e] = acc[8 * (t >> 1) + (t & 1) + 2 * e];
            asm volatile("" : "+r"(v[e]));
            v[e] = pack_bf16(h_lo(v[e]) * f, h_hi(v[e]) * f);
        }
        asm volatile("red.global.add.noftz.v4.bf16x2 [%0], {%1,%2,%3,%4};\n" ::"l"(o + (t >> 1) * 64 + (t & 1) * 4 * P2_XROW),
                     "r"(v[0]), "r"(v[1]), "r"(v[2]), "r"(v[3]) : "memory");
        if (t % 3 == 2) sched_break(zero);
    }
}

__global__ void __cluster_dims__(2, 1, 1) __launch_bounds__(512, 1)
pass2_kernel(const __nv_bfloat16* __restrict__ x, const __nv_bfloat16* __restrict__ grn_g, __nv_bfloat16* __restrict__ out, int zero) {
    extern __shared__ __align__(1024) uint8_t smem[];
    const uint32_t sbase = smem_u32(smem);
    const uint32_t bar_bfull = sbase + P2_OFF_BAR, bar_bempty = bar_bfull + P2_NB * 8;
    const uint32_t bar_afull = bar_bempty + P2_NB * 8, bar_aempty = bar_afull + 3 * P2_NA * 8;
    const uint32_t bar_xfull = bar_aempty + 3 * P2_NA * 8, bar_oready = bar_xfull + 8, s_pos = bar_xfull + 16;
    int tid;
    asm volatile("mov.u32 %0, %%tid.x;\n" : "=r"(tid));
    const int warp = __shfl_sync(0xffffffffu, tid >> 5, 0), lane = tid & 31;
    const uint32_t rank = cluster_rank();
    const int cl = blockIdx.x >> 1, pair = cl >> 1;
    const int k0 = (4 * pair + (cl & 1) * (48 - P2_POS % 48)) % 48;
    const int head = pair < P2_SHARED && !(cl & 1), tail = pair < P2_SHARED && (cl & 1);

    uint32_t par, gg[4];
    float pre[4];
    if (warp < 12) {
        asm volatile("ld.global.cg.u32 %0, [%1];\n" : "=r"(par) : "l"(&g_par) : "memory");
#pragma unroll
        for (int i = 0; i < 4; i++) {
            asm volatile("ld.global.cg.f32 %0, [%1];\n" : "=f"(pre[i]) : "l"(&g_sums[i & 1][HID + (i >> 1) * C_DIM + tid]) : "memory");
            asm volatile("ld.global.nc.u16 %0, [%1];\n" : "=r"(gg[i]) : "l"(grn_g + tid + 384 * i) : "memory");
        }
    }
    TSTAMP(1, 0);
    if (tid == 384) {
        for (int i = 0; i < P2_NB; i++) {
            mbar_init(bar_bfull + i * 8, 1);
            mbar_init(bar_bempty + i * 8, 24);
        }
        for (int i = 0; i < 3 * P2_NA; i++) {
            mbar_init(bar_afull + i * 8, 1);
            mbar_init(bar_aempty + i * 8, 4);
        }
        mbar_init(bar_xfull, 2);
        mbar_init(bar_oready, 4);
        asm volatile("st.shared.u32 [%0], 0;\n" ::"r"(s_pos) : "memory");
        asm volatile("fence.mbarrier_init.release.cluster;\n" ::: "memory");
    }
    __syncthreads();
    cluster_sync_relaxed();

    if (warp >= 12) {
        reg_dec<32>();
        if (warp == 12) {
            const uint8_t* wsrc = reinterpret_cast<const uint8_t*>(g_w2img) + rank * (P2_B / 2);
            int st = 0, ph = 1, kb = k0, m = 0, r = 0;
            const int busy = head ? 0 : tail ? P2_POS - 24 : P2_POS;
#pragma unroll 1
            for (int p = 0; p < P2_POS; p++) {
                if (p == 0 || p == P2_FOLD) {
                    flag_wait<true>(&g_img[p != 0], p ? 96 * 4 : 48);
                    asm volatile("fence.proxy.async.global;\n" ::: "memory");
                    if (p) wsrc += sizeof(g_w2img[0]);
                }
                mbar_wait(bar_bempty + st * 8, ph);
                TR2P(p, 0);
                if (elect_one()) {
                    mbar_expect_tx(bar_bfull + st * 8, P2_B);
                    bulk_g2s_mc(sbase + st * P2_B + rank * (P2_B / 2), wsrc + kb * P2_B, P2_B / 2, bar_bfull + st * 8, (uint16_t)3);
                    asm volatile("st.volatile.shared.u32 [%0], %1;\n" ::"r"(s_pos), "r"(p) : "memory");
                    const int idle = 2 - min(m, P2_ITEMS - 1) + max(m - 2 + (r >= 48 - 2 * P2_LAG), 0) - ((unsigned)(p - busy) < 24);
                    if (idle) asm volatile("mbarrier.arrive.shared::cta.b64 _, [%0], %1;\n" ::"r"(bar_bempty + st * 8), "r"(idle * 8) : "memory");
                    if (rank == 0) asm volatile("red.relaxed.gpu.global.add.u32 [%0], 1;\n" ::"l"(&g_prog) : "memory");
                }
                __syncwarp();
                if (++st == P2_NB) { st = 0; ph ^= 1; }
                if (++kb == 48) kb = 0;
                if (++r == P2_LAG) { r = 0; m++; }
            }
            mbar_wait(bar_bempty + st * 8, ph);
            if (lane == 0) mbar_arrive(bar_bfull + st * 8);
#pragma unroll 1
            for (int p = 1; p < P2_NB; p++) {
                if (++st == P2_NB) { st = 0; ph ^= 1; }
                mbar_wait(bar_bempty + st * 8, ph);
            }
        } else if (warp == 13) {
            const uint8_t* src[3];
            int n[3], left[3], wrap[3];
            uint32_t st[3];
            auto item = [&](int w) {
                const int u = (k0 + p2_start(n[w])) % 48;
                left[w] = n[w] < 0 || n[w] == P2_ITEMS ? 24 : 48;
                wrap[w] = left[w] - (48 - u);
                src[w] = reinterpret_cast<const uint8_t*>(g_h) + (size_t)p2_tile(cl, n[w]) * (2 * H_TILE) + rank * H_HALF + u * H_STEP;
            };
#pragma unroll
            for (int w = 0; w < 3; w++) {
                n[w] = w == 2 && head ? -1 : w;
                st[w] = 0x80000000u;
                item(w);
            }
            gdc_wait();
#pragma unroll 1
            for (int done = 0; done < 3;) {
                bool idle = true;
#pragma unroll
                for (int w = 0; w < 3; w++) {
                    const uint32_t o = (st[w] & 0xff) + w * P2_NA * 8;
                    if (left[w] >= 0 && mbar_test(bar_aempty + o, st[w] >> 31)) {
                        idle = false;
                        if (left[w] == 0) {
                            if (lane == 0) mbar_arrive(bar_afull + o);
                            left[w] = -1;
                            done++;
                        } else {
                            if (elect_one()) {
                                mbar_expect_tx(bar_afull + o, P2_A);
                                bulk_g2s(sbase + P2_OFF_A + o * (P2_A / 8), src[w], P2_A, bar_afull + o);
                            }
                            __syncwarp();
                            src[w] += H_STEP;
                            st[w] += 8;
                            if ((st[w] & 0xff) == P2_NA * 8) st[w] ^= 0x80000000u | (P2_NA * 8);
                            if (--left[w] == wrap[w]) src[w] -= 48 * H_STEP;
                            if (left[w] == 0 && (n[w] += 3) < P2_ITEMS + tail) item(w);
                        }
                    }
                }
                if (idle) __nanosleep(P2_HSLEEP);
                SAFE_BREAK
            }
        } else if (warp == 14) {
            const uint32_t sx = sbase + P2_OFF_X;
            size_t o = 0;
            auto pace = [&](int target) {
                int v;
                while (true) {
                    asm volatile("ld.volatile.shared.u32 %0, [%1];\n" : "=r"(v) : "r"(s_pos) : "memory");
                    if (v * 16 >= target) break;
                    __nanosleep(P2_PSLEEP);
                    SAFE_BREAK
                }
            };
#pragma unroll 1
            for (int n = -head; n <= P2_ITEMS; n++) {
                const size_t on = (size_t)(2 * p2_tile(cl, n) + rank) * (64 * C_DIM * 2);
                const bool st = n + head > 0, ld = n < P2_ITEMS;
                if (st) mbar_wait(bar_oready, (n - 1 + head) & 1);
                TR2P(n + 1, 1);
                if (lane == 0) {
                    if (n == 1 && head) {
                        asm volatile("cp.async.bulk.wait_group 0;\nfence.proxy.async.global;\n" ::: "memory");
                        asm volatile("st.release.gpu.global.u32 [%0], 1;\n" ::"l"(&g_half[pair][rank]) : "memory");
                    }
                    if (ld) mbar_expect_tx(bar_xfull, 64 * C_DIM * 2);
                    int t = st && n < P2_ITEMS - 1 ? (P2_LAG * (n - 1) + 48 + P2_T0 - 1) * 16 : -1024;
#pragma unroll 1
                    for (int c = 0; st && c < 64 * P2_XROW; c += P2_XC) {
                        pace(t += P2_TS);
                        bulk_s2g(reinterpret_cast<uint8_t*>(out) + o + c, sx + c + (c >= 32 * P2_XROW ? 64 : 0), P2_XC);
                    }
                    asm volatile("cp.async.bulk.commit_group;\ncp.async.bulk.wait_group.read 0;\n" ::: "memory");
#pragma unroll 1
                    for (int c = 0; ld && c < 64 * P2_XROW; c += P2_XC) {
                        pace(t += P2_TS);
                        bulk_g2s(sx + c + (c >= 32 * P2_XROW ? 64 : 0), reinterpret_cast<const uint8_t*>(x) + on + c, P2_XC, bar_xfull);
                    }
                    TR2P(n + 1, 2);
                    if (rank == 0 && n > 0 && n < P2_ITEMS - 2)
                        flag_wait<false>(&g_prog, P2_NCL * (P2_LAG * n + 48 + P2_EXTRA) + (tail ? P2_SHARED - P2_NCL : P2_SHARED) * P2_DELTA);
                    if (ld) mbar_arrive(bar_xfull);
                    TR2P(n + 1, 3);
                }
                __syncwarp();
                o = on;
            }
            asm volatile("cp.async.bulk.wait_group 0;\n" ::: "memory");
            TR2P(30, 1);
        }
    } else {
        reg_inc<160>();
        const int wg = warp >> 2, w = warp & 3, g = lane >> 2, q = lane & 3;
        const uint32_t sx = sbase + P2_OFF_X + (g & 1) * P2_XHALF + (w * 8 + (g >> 1)) * P2_XROW + q * 16;
        const uint32_t af = bar_afull + wg * P2_NA * 8, ae = bar_aempty + wg * P2_NA * 8;
        const uint32_t s_a = sbase + P2_OFF_A - bar_afull * (P2_A / 8) + (lane >> 3) * 512 + (lane & 7) * 64 +
                             ((w ^ ((lane & 7) >> 1)) << 4);
        uint32_t acc0[48], acc1[48];
        float up;
        uint4 a0[2], a1[2];
        int st = 0, ph = 0;

        {
            float4* s_red = reinterpret_cast<float4*>(smem + P2_OFF_BIAS);
            const float* sums = g_sums[par];
            float gx[4], part = 0.f, mx = 0.f;
            TSTAMP(1, 27);
            gdc_wait();
            TSTAMP(1, 1);
#pragma unroll
            for (int i = 0; i < 4; i++) gx[i] = __ldcg(sums + tid + 384 * i);
            if (blockIdx.x == 120 && tid < (LN_RING + 3) * 2) (&g_flag[0][0][0])[tid * 8] = 0;
            if (blockIdx.x == 121 && tid == 0) atomicAdd(&g_epoch, 1u);
            float z = __uint_as_float(__reduce_max_sync(0xffffffffu, __float_as_uint(pre[2] + pre[3])));
#pragma unroll
            for (int i = 0; i < 4; i++) {
                asm("sqrt.approx.f32 %0, %1;\n" : "=f"(gx[i]) : "f"(fmaf(gx[i], HSCALE * HSCALE, 1e-6f)));
                part += gx[i];
                gx[i] *= bf_lo(gg[i]);
                mx = fmaxf(mx, fabsf(gx[i]));
            }
#pragma unroll
            for (int o = 16; o > 0; o >>= 1) part += __shfl_xor_sync(0xffffffffu, part, o);
            mx = __uint_as_float(__reduce_max_sync(0xffffffffu, __float_as_uint(mx)));
            TSTAMP(1, 26);
            if (lane == 0) s_red[warp] = make_float4(part, mx, z, 0.f);
            bar_sync(1, 384);
            float tot = 0.f;
            {
                const float4 t = s_red[min(lane & 15, 11)];
                tot = (lane & 15) < 12 ? t.x : 0.f;
#pragma unroll
                for (int o = 8; o > 0; o >>= 1) tot += __shfl_xor_sync(0xffffffffu, tot, o);
                mx = __uint_as_float(__reduce_max_sync(0xffffffffu, __float_as_uint(t.y)));
                z = __uint_as_float(__reduce_max_sync(0xffffffffu, __float_as_uint(t.z)));
            }
            const float inv = __fdividef(1.0f, fmaf(tot, 1.0f / HID, 1e-6f));
            const uint32_t j = max(__float_as_uint(fmaf(mx, inv, 1.0f) * 1.01f) >> 23, 130u) - 130u;
            const float dn = __uint_as_float((127u - j) << 23);
#pragma unroll
            for (int i = 0; i < 4; i++)
                *reinterpret_cast<uint16_t*>(smem + P2_OFF_GRN + (tid + 384 * i) * 2) = pack_f16(fmaf(gx[i], inv, 1.0f) * dn, 0.f);
            up = (HSCALE * 1.00235f) * __uint_as_float(min(acc_exp(z) - 9u + j, 253u) << 23);
            TSTAMP(1, 25);
            bar_sync(1, 384);
            reinterpret_cast<float*>(smem + P2_OFF_BIAS)[tid] = pre[0] + pre[1];
            if (wg == 1 && blockIdx.x < 96) {
                const uint4* src = g_w2img[0] + blockIdx.x * 768 + tid - 128;
                const uint4 fk = *reinterpret_cast<const uint4*>(smem + P2_OFF_GRN + blockIdx.x * 32 + (tid & 8) * 2);
                uint4 v[6];
#pragma unroll
                for (int i = 0; i < 6; i++) v[i] = __ldcg(src + i * 128);
                auto fold = [&](uint32_t b, uint32_t f) { return (h2_mul(b, f) + 0x00040004u) & 0xfff8fff8u; };
#pragma unroll
                for (int i = 0; i < 6; i++)
                    g_w2img[1][blockIdx.x * 768 + tid - 128 + i * 128] = make_uint4(fold(v[i].x, fk.x), fold(v[i].y, fk.y), fold(v[i].z, fk.z), fold(v[i].w, fk.w));
                asm volatile("fence.proxy.async.global;\n" ::: "memory");
                __threadfence();
                __syncwarp();
                if (lane == 0) asm volatile("red.release.gpu.global.add.u32 [%0], 1;\n" ::"l"(&g_img[1]) : "memory");
            }
        }
        TSTAMP(1, 28);
        int kt = k0, pos;
        const int who = __shfl_sync(0xffffffffu, lane == 2 ? 0 : lane < 2 ? 1 : 2, lane);
        const uint32_t rel0 = who ? mapa(bar_bempty, lane & 1) : mapa(ae, rank), rel1 = rel0 + (who ? P2_NB : P2_NA) * 8;
        uint32_t rel = rel1 - 8;
        auto next_rel = [&](bool go) {
            if (go) rel += 8;
            if (rel == rel1) rel = rel0;
        };
        auto release_b = [&]() {
            next_rel(who == 1);
            if (who == 1) mbar_arrive_cluster(rel);
        };
        auto seek = [&](int p) {
            pos = p;
            st = p % P2_NB;
            ph = p / P2_NB & 1;
            if (who == 1) rel = (st ? rel0 + st * 8 : rel1) - 8;
            int v;
            while (true) {
                asm volatile("ld.volatile.shared.u32 %0, [%1];\n" : "=r"(v) : "r"(s_pos) : "memory");
                if (v >= p) break;
                __nanosleep(200);
                SAFE_BREAK
            }
        };
        auto publish = [&]() {
            asm volatile("fence.proxy.async.shared::cta;\n" ::: "memory");
            __syncwarp();
            if (who == 0) mbar_arrive(bar_oready);
        };
        bool ok_a;
        uint32_t abar = af, pa = 0;
        auto fetch = [&](uint4 (&a)[2], bool early) {
            const uint32_t src = s_a + abar * (P2_A / 8);
            abar += 8;
            if (abar == af + P2_NA * 8) { abar = af; pa ^= 0x80000000u; }
            const bool ok_b = mbar_test(bar_bfull + st * 8, ph);
            ok_a = mbar_test(abar, pa >> 31);
            uint32_t o[6];
            asm volatile("ldmatrix.sync.aligned.m8n8.x4.trans.shared.b16 {%0,%1,%2,%3}, [%4];\n"
                         : "=r"(o[0]), "=r"(o[1]), "=r"(o[2]), "=r"(o[3]) : "r"(src) : "memory");
            asm volatile("ldmatrix.sync.aligned.m8n8.x2.trans.shared.b16 {%0,%1}, [%2];\n"
                         : "=r"(o[4]), "=r"(o[5]) : "r"(src + 2048) : "memory");
            p2_unpack(a[0], o[0], o[1], o[2]);
            p2_unpack(a[1], o[3], o[4], o[5]);
            if (early) {
                const uint32_t* t = reinterpret_cast<const uint32_t*>(smem + P2_OFF_GRN) + kt * 16 + q;
#pragma unroll
                for (int i = 0; i < 2; i++)
                    a[i] = make_uint4(h2_mul(a[i].x, t[8 * i]), h2_mul(a[i].y, t[8 * i]), h2_mul(a[i].z, t[8 * i + 4]), h2_mul(a[i].w, t[8 * i + 4]));
                if (++kt == 48) kt = 0;
            }
            if (!ok_b) mbar_wait(bar_bfull + st * 8, ph);
        };
        auto step = [&](const uint4 (&a)[2], uint4 (&an)[2], int thr, bool early) {
            TR2(0);
            const uint64_t db = make_desc(sbase + st * P2_B, 128, 256);
            wg_fence();
            mma_rs_n192(acc0, a[0], db, thr - 1);
            mma_rs_n192(acc1, a[0], db + 384, thr - 1);
            mma_rs_n192(acc0, a[1], db + 768, 1);
            mma_rs_n192(acc1, a[1], db + 768 + 384, 1);
            wg_commit();
            next_rel(who < thr);
            if (++st == P2_NB) { st = 0; ph ^= 1; }
            wg_wait<1>();
            if (!ok_a) {
                if (who < thr) mbar_arrive_cluster(rel);
                thr = 0;
                mbar_wait(abar, pa >> 31);
            }
            if (who < thr) mbar_arrive_cluster(rel);
            fetch(an, early);
            pos++;
        };
        int n = wg == 2 && head ? -1 : wg;
        mbar_wait(af, 0);
        seek(p2_start(n));
        fetch(a0, n <= 0);
#pragma unroll 1
        for (;; n += 3) {
            TSTAMP(1, 2 + n);
            const int p0 = n < 0 || n == P2_ITEMS ? 12 : 0, pe = n <= 0 ? p0 + P2_FOLD / 2 : 0;
            const bool more = n + 3 < P2_ITEMS + tail;
#pragma unroll 1
            for (int p = p0; p < 24; p++) {
                step(a0, a1, p == p0 ? 1 : 2, p < pe);
                step(a1, a0, 2, p < pe);
            }
            if (n == P2_ITEMS) {
                flag_wait<true>(&g_half[pair][rank], 1);
                TR2(1);
                wg_wait<0>();
                TR2(2);
                release_b();
                uint8_t* o = reinterpret_cast<uint8_t*>(out) + (size_t)((2 * p2_tile(cl, -1) + rank) * 64 + (g & 1) * 32 + w * 8 + (g >> 1)) * P2_XROW + q * 16;
                p2_epilogue_add(acc0, o, up, zero);
                p2_epilogue_add(acc1, o + 384, up, zero);
                TR2(3);
                break;
            }
            mbar_wait(bar_xfull, (n + head) & 1);
            TR2(1);
            wg_wait<0>();
            TR2(2);
            release_b();
            __syncwarp();
            p2_epilogue(acc0, acc1, sx, sbase + P2_OFF_BIAS + q * 32, up, zero);
            TR2(3);
            publish();
            if (!more) break;
            seek(p2_start(n + 3));
            mbar_wait(bar_bfull + st * 8, ph);
        }
        TSTAMP(1, 30);
    }
}

}

extern "C" void kernel_launch(void* const* d_in, const int* in_sizes, int n_in, void* d_out, int out_size) {
    const __nv_bfloat16* x = (const __nv_bfloat16*)d_in[0];
    const __nv_bfloat16* dw = (const __nv_bfloat16*)d_in[1];
    const __nv_bfloat16* w1 = (const __nv_bfloat16*)d_in[2];
    const __nv_bfloat16* w2 = (const __nv_bfloat16*)d_in[3];
    const __nv_bfloat16* grn_g = (const __nv_bfloat16*)d_in[4];
    const __nv_bfloat16* grn_b = (const __nv_bfloat16*)d_in[5];
    __nv_bfloat16* out = (__nv_bfloat16*)d_out;

    cudaFuncSetAttribute(pass1_kernel, cudaFuncAttributeMaxDynamicSharedMemorySize, P1_SMEM);
    cudaFuncSetAttribute(pass2_kernel, cudaFuncAttributeMaxDynamicSharedMemorySize, P2_SMEM);

    typedef CUresult (*EncodeFn)(CUtensorMap*, CUtensorMapDataType, cuuint32_t, void*, const cuuint64_t*, const cuuint64_t*,
                                 const cuuint32_t*, const cuuint32_t*, CUtensorMapInterleave, CUtensorMapSwizzle,
                                 CUtensorMapL2promotion, CUtensorMapFloatOOBfill);
    static EncodeFn encode = nullptr;
    if (!encode) {
        cudaDriverEntryPointQueryResult qres;
        cudaGetDriverEntryPoint("cuTensorMapEncodeTiled", (void**)&encode, cudaEnableDefault, &qres);
    }
    CUtensorMap wmap;
    const cuuint64_t gdim[2] = {HID, C_DIM};
    const cuuint64_t gstr[1] = {HID * 2};
    const cuuint32_t box[2] = {64, 192}, estr[2] = {1, 1};
    CUresult er = encode(&wmap, CU_TENSOR_MAP_DATA_TYPE_BFLOAT16, 2, (void*)w1, gdim, gstr, box, estr, CU_TENSOR_MAP_INTERLEAVE_NONE,
           CU_TENSOR_MAP_SWIZZLE_128B, CU_TENSOR_MAP_L2_PROMOTION_L2_128B, CU_TENSOR_MAP_FLOAT_OOB_FILL_NONE);
    if (er != CUDA_SUCCESS) printf("tensor map encode failed %d\n", (int)er);

    pass1_kernel<<<NUM_CTAS, 512, P1_SMEM>>>(wmap, x, dw, w1, w2, grn_b, 0);

    cudaLaunchAttribute attr[1];
    attr[0].id = cudaLaunchAttributeProgrammaticStreamSerialization;
    attr[0].val.programmaticStreamSerializationAllowed = 1;
    cudaLaunchConfig_t cfg = {};
    cfg.gridDim = dim3(NUM_CTAS);
    cfg.stream = 0;
    cfg.attrs = attr;
    cfg.numAttrs = 1;
    cfg.blockDim = dim3(512);
    cfg.dynamicSmemBytes = P2_SMEM;
    cudaLaunchKernelEx(&cfg, pass2_kernel, x, grn_g, out, 0);
}
```

```cpp
#include <cuda.h>
#include <cuda_runtime.h>
#include <cuda_bf16.h>
#include <stdint.h>
#include <stdio.h>

namespace {

constexpr int M_TOTAL = 384 * 384;
constexpr int C_DIM   = 384;
constexpr int HID     = 1536;
constexpr int NT128   = M_TOTAL / 128;
constexpr int NUM_CTAS = 132;

constexpr int NGRP = 15;
#define LN_DEPTH 2
constexpr int LN_STEP = 2 * NGRP, LN_RING = LN_DEPTH * LN_STEP;
#define P1_M 101
#define P1_D 10
__device__ __forceinline__ int p1_tile(int t, bool small) {
    return t + (small ? ((t + 1) * P1_M + P1_D - 1) / P1_D : t * P1_D / P1_M);
}
constexpr int LN_TILE = 128 * C_DIM * 2;
constexpr int H_TILE = 64 * HID * 3 / 2;
constexpr int H_HALF = 3072, H_STEP = 6144;

__device__ __align__(1024) uint4 g_h[(size_t)M_TOTAL * HID * 3 / 32];
__device__ __align__(1024) uint4 g_ln[LN_RING * LN_TILE / 16];
__device__ __align__(1024) uint4 g_w2img[2][HID * C_DIM * 2 / 16];
__device__ __align__(16) float g_sums[2][HID + 2 * C_DIM];
__device__ __align__(16) unsigned g_ex[HID];
__device__ unsigned g_epoch, g_par;
__device__ __align__(128) unsigned g_img[2];
__device__ __align__(128) unsigned g_prog;
__device__ __align__(128) unsigned g_half[32][2];
__device__ unsigned g_flag[LN_RING + 3][2][8];
#define TSTAMP(k, i)
#define TRACE(wg, pos, i)
#define TRACEW(pos, i)

#define TR2(i)
#define TR2P(pos, i)
__host__ __device__ __forceinline__ int perm32(int n) {
    return (n & ~31) | (((n >> 1) & 3) << 3) | (((n >> 3) & 3) << 1) | (n & 1);
}

__device__ __forceinline__ uint32_t smem_u32(const void* p) { return (uint32_t)__cvta_generic_to_shared(p); }

__device__ __forceinline__ void mbar_init(uint32_t bar, uint32_t count) {
    asm volatile("mbarrier.init.shared::cta.b64 [%0], %1;\n" ::"r"(bar), "r"(count) : "memory");
}
__device__ __forceinline__ void mbar_expect_tx(uint32_t bar, uint32_t bytes) {
    asm volatile("mbarrier.arrive.expect_tx.shared::cta.b64 _, [%0], %1;\n" ::"r"(bar), "r"(bytes) : "memory");
}
__device__ __forceinline__ void mbar_arrive(uint32_t bar) {
    asm volatile("mbarrier.arrive.shared::cta.b64 _, [%0];\n" ::"r"(bar) : "memory");
}
__device__ __forceinline__ void mbar_arrive_cluster(uint32_t bar_cluster_addr) {
    asm volatile("mbarrier.arrive.shared::cluster.b64 _, [%0];\n" ::"r"(bar_cluster_addr) : "memory");
}
#define SAFE_BREAK
__device__ __forceinline__ void mbar_wait(uint32_t bar, uint32_t parity) {
    asm volatile(
        "{\n"
        ".reg .pred p;\n"
        "LAB_WAIT:\n"
        "mbarrier.try_wait.parity.shared::cta.b64 p, [%0], %1;\n"
        "@!p bra LAB_WAIT;\n"
        "}\n" ::"r"(bar), "r"(parity) : "memory");
}
__device__ __forceinline__ bool mbar_test(uint32_t bar, uint32_t parity) {
    uint32_t ok;
    asm volatile("{\n.reg .pred p;\n"
                 "mbarrier.test_wait.parity.shared::cta.b64 p, [%1], %2;\n"
                 "selp.u32 %0, 1, 0, p;\n}\n" : "=r"(ok) : "r"(bar), "r"(parity) : "memory");
    return ok != 0;
}
__device__ __forceinline__ uint32_t mapa(uint32_t addr, uint32_t rank) {
    uint32_t r;
    asm volatile("mapa.shared::cluster.u32 %0, %1, %2;\n" : "=r"(r) : "r"(addr), "r"(rank));
    return r;
}
__device__ __forceinline__ void bulk_g2s(uint32_t dst, const void* src, uint32_t bytes, uint32_t bar) {
    asm volatile("cp.async.bulk.shared::cluster.global.mbarrier::complete_tx::bytes [%0], [%1], %2, [%3];\n"
                 ::"r"(dst), "l"(src), "r"(bytes), "r"(bar) : "memory");
}
__device__ __forceinline__ void bulk_g2s_mc(uint32_t dst, const void* src, uint32_t bytes, uint32_t bar, uint16_t mask) {
    asm volatile("cp.async.bulk.shared::cluster.global.mbarrier::complete_tx::bytes.multicast::cluster [%0], [%1], %2, [%3], %4;\n"
                 ::"r"(dst), "l"(src), "r"(bytes), "r"(bar), "h"(mask) : "memory");
}
__device__ __forceinline__ void tma2(uint32_t dst, const CUtensorMap* map, int c0, int c1, uint32_t bar) {
    asm volatile("cp.async.bulk.tensor.2d.shared::cluster.global.tile.mbarrier::complete_tx::bytes [%0], [%1, {%2, %3}], [%4];\n"
                 ::"r"(dst), "l"(map), "r"(c0), "r"(c1), "r"(bar) : "memory");
}
template <bool ACQ>
__device__ __forceinline__ uint32_t flag_wait(const unsigned* p, unsigned target) {
    unsigned v, n = 0;
    do {
        if (ACQ) asm volatile("ld.acquire.gpu.global.u32 %0, [%1];\n" : "=r"(v) : "l"(p) : "memory");
        else asm volatile("ld.relaxed.gpu.global.u32 %0, [%1];\n" : "=r"(v) : "l"(p) : "memory");
        n++;
    } while (v < target);
    return n == 1;
}
__device__ __forceinline__ void ldsm4t(uint32_t (&r)[4], uint32_t addr) {
    asm volatile("ldmatrix.sync.aligned.m8n8.x4.trans.shared.b16 {%0,%1,%2,%3}, [%4];\n"
                 : "=r"(r[0]), "=r"(r[1]), "=r"(r[2]), "=r"(r[3]) : "r"(addr) : "memory");
}
__device__ __forceinline__ void bulk_s2g(void* dst, uint32_t src, uint32_t bytes) {
    asm volatile("cp.async.bulk.global.shared::cta.bulk_group [%0], [%1], %2;\n" ::"l"(dst), "r"(src), "r"(bytes) : "memory");
}
__device__ __forceinline__ void cluster_sync_relaxed() {
    asm volatile("barrier.cluster.arrive.relaxed.aligned;\nbarrier.cluster.wait.aligned;\n" ::: "memory");
}
__device__ __forceinline__ void gdc_wait() { asm volatile("griddepcontrol.wait;\n" ::: "memory"); }
__device__ __forceinline__ void gdc_launch() { asm volatile("griddepcontrol.launch_dependents;\n" ::: "memory"); }
__device__ __forceinline__ uint32_t cluster_rank() {
    uint32_t r;
    asm volatile("mov.u32 %0, %%cluster_ctarank;\n" : "=r"(r));
    return r;
}
__device__ __forceinline__ bool elect_one() {
    uint32_t pred;
    asm volatile("{\n.reg .pred p;\nelect.sync _|p, 0xffffffff;\nselp.u32 %0, 1, 0, p;\n}\n" : "=r"(pred));
    return pred != 0;
}
__device__ __forceinline__ void wg_fence() { asm volatile("wgmma.fence.sync.aligned;\n" ::: "memory"); }
__device__ __forceinline__ void wg_commit() { asm volatile("wgmma.commit_group.sync.aligned;\n" ::: "memory"); }
template <int N> __device__ __forceinline__ void wg_wait() {
    asm volatile("wgmma.wait_group.sync.aligned %0;\n" ::"n"(N) : "memory");
}
template <int R> __device__ __forceinline__ void reg_inc() { asm volatile("setmaxnreg.inc.sync.aligned.u32 %0;\n" ::"n"(R)); }
template <int R> __device__ __forceinline__ void reg_dec() { asm volatile("setmaxnreg.dec.sync.aligned.u32 %0;\n" ::"n"(R)); }
__device__ __forceinline__ void bar_sync(int id, int n) { asm volatile("bar.sync %0, %1;\n" ::"r"(id), "r"(n) : "memory"); }
__device__ __forceinline__ void bar_arrive(int id, int n) { asm volatile("bar.arrive %0, %1;\n" ::"r"(id), "r"(n) : "memory"); }

__device__ __forceinline__ uint64_t make_desc(uint32_t saddr, uint32_t lbo, uint32_t sbo) {
    return (uint64_t)((saddr & 0x3FFFF) >> 4) | ((uint64_t)(lbo >> 4) << 16) | ((uint64_t)(sbo >> 4) << 32);
}

__device__ __forceinline__ void stg128_cs(void* p, uint32_t a, uint32_t b, uint32_t c, uint32_t d) {
    asm volatile("st.global.cs.v4.u32 [%0], {%1,%2,%3,%4};\n" ::"l"(p), "r"(a), "r"(b), "r"(c), "r"(d) : "memory");
}
__device__ __forceinline__ uint32_t pack_bf16(float lo, float hi) {
    uint32_t r;
    asm("cvt.rn.bf16x2.f32 %0, %1, %2;\n" : "=r"(r) : "f"(hi), "f"(lo));
    return r;
}
__device__ __forceinline__ float bf_lo(uint32_t v) { return __uint_as_float(v << 16); }
__device__ __forceinline__ float bf_hi(uint32_t v) { return __uint_as_float(v & 0xffff0000u); }
__device__ __forceinline__ uint32_t bf2_mul(uint32_t a, uint32_t b) {
    uint32_t r;
    asm("mul.rn.bf16x2 %0, %1, %2;\n" : "=r"(r) : "r"(a), "r"(b));
    return r;
}
__device__ __forceinline__ uint32_t bf2_fma(uint32_t a, uint32_t b, uint32_t c) {
    uint32_t r;
    asm("fma.rn.bf16x2 %0, %1, %2, %3;\n" : "=r"(r) : "r"(a), "r"(b), "r"(c));
    return r;
}
__device__ __forceinline__ uint32_t bf2_add(uint32_t a, uint32_t b) {
    uint32_t r;
    asm("add.rn.bf16x2 %0, %1, %2;\n" : "=r"(r) : "r"(a), "r"(b));
    return r;
}
constexpr float KAPPA = 0.3292034911525734f;
constexpr float GELU_C = 2.423681954311584f;
constexpr float HSCALE = 1.0f / (2.0f * KAPPA);
__device__ __forceinline__ uint32_t acc_exp(float z) { return max(__float_as_uint(z) >> 23, 10u); }
__device__ __forceinline__ void sched_break(int zero) {
    asm volatile("{\n.reg .pred p;\nsetp.ne.s32 p, %0, 0;\nSB_LOOP:\n@p nanosleep.u32 1;\n@p bra SB_LOOP;\n}\n" ::"r"(zero));
}

#define ACC8(d, o) "+f"(d[o + 0]), "+f"(d[o + 1]), "+f"(d[o + 2]), "+f"(d[o + 3]), "+f"(d[o + 4]), "+f"(d[o + 5]), "+f"(d[o + 6]), "+f"(d[o + 7])

#define ACCR8(d, o) "+r"(d[o + 0]), "+r"(d[o + 1]), "+r"(d[o + 2]), "+r"(d[o + 3]), "+r"(d[o + 4]), "+r"(d[o + 5]), "+r"(d[o + 6]), "+r"(d[o + 7])
__device__ __forceinline__ void mma_rs_n128(uint32_t (&d)[32], const uint32_t (&a)[4], uint64_t desc, int scale_d) {
    asm volatile(
        "{\n.reg .pred p;\nsetp.ne.b32 p, %37, 0;\n"
        "wgmma.mma_async.sync.aligned.m64n128k16.f16.f16.f16 "
        "{%0,%1,%2,%3,%4,%5,%6,%7,%8,%9,%10,%11,%12,%13,%14,%15,"
        "%16,%17,%18,%19,%20,%21,%22,%23,%24,%25,%26,%27,%28,%29,%30,%31},"
        "{%32,%33,%34,%35}, %36, p, 1, 1, 0;\n}\n"
        : ACCR8(d, 0), ACCR8(d, 8), ACCR8(d, 16), ACCR8(d, 24)
        : "r"(a[0]), "r"(a[1]), "r"(a[2]), "r"(a[3]), "l"(desc), "r"(scale_d));
}
__device__ __forceinline__ void mma_ss_n128(uint32_t (&d)[32], uint64_t da, uint64_t db) {
    asm volatile(
        "{\n.reg .pred p;\nsetp.ne.b32 p, %34, 0;\n"
        "wgmma.mma_async.sync.aligned.m64n128k16.f16.f16.f16 "
        "{%0,%1,%2,%3,%4,%5,%6,%7,%8,%9,%10,%11,%12,%13,%14,%15,"
        "%16,%17,%18,%19,%20,%21,%22,%23,%24,%25,%26,%27,%28,%29,%30,%31},"
        "%32, %33, p, 1, 1, 0, 0;\n}\n"
        : ACCR8(d, 0), ACCR8(d, 8), ACCR8(d, 16), ACCR8(d, 24)
        : "l"(da), "l"(db), "r"(1));
}
__device__ __forceinline__ uint32_t bf2_as_h2(uint32_t v) { return (v & 0x0fff0fffu) * 7u + v; }
__device__ __forceinline__ float h_lo(uint32_t v) {
    float r;
    asm("{\n.reg .b16 l, h;\nmov.b32 {l, h}, %1;\ncvt.f32.f16 %0, l;\n}\n" : "=f"(r) : "r"(v));
    return r;
}
__device__ __forceinline__ float h_hi(uint32_t v) {
    float r;
    asm("{\n.reg .b16 l, h;\nmov.b32 {l, h}, %1;\ncvt.f32.f16 %0, h;\n}\n" : "=f"(r) : "r"(v));
    return r;
}

__device__ __forceinline__ void mma_rs_n192(uint32_t (&d)[48], const uint4& a, uint64_t db, int scale_d) {
    asm volatile(
        "{\n.reg .pred p;\nsetp.ne.b32 p, %53, 0;\n"
        "wgmma.mma_async.sync.aligned.m64n192k16.f16.f16.f16 "
        "{%0,%1,%2,%3,%4,%5,%6,%7,%8,%9,%10,%11,%12,%13,%14,%15,"
        "%16,%17,%18,%19,%20,%21,%22,%23,%24,%25,%26,%27,%28,%29,%30,%31,"
        "%32,%33,%34,%35,%36,%37,%38,%39,%40,%41,%42,%43,%44,%45,%46,%47},"
        "{%48,%49,%50,%51}, %52, p, 1, 1, 0;\n}\n"
        : ACCR8(d, 0), ACCR8(d, 8), ACCR8(d, 16), ACCR8(d, 24), ACCR8(d, 32), ACCR8(d, 40)
        : "r"(a.x), "r"(a.y), "r"(a.z), "r"(a.w), "l"(db), "r"(scale_d));
}

__device__ __forceinline__ uint32_t pack_f16(float lo, float hi) {
    uint32_t r;
    asm("cvt.rn.f16x2.f32 %0, %1, %2;\n" : "=r"(r) : "f"(hi), "f"(lo));
    return r;
}

#define P1_IMG 900
constexpr int P1_SLOT = LN_TILE / 2, P1_NST = 4;
constexpr int P1_X = 16 * C_DIM * 2;
constexpr int P1_OFF_X = P1_SLOT * P1_NST;
constexpr int P1_OFF_A = P1_OFF_X + 2 * P1_X;
constexpr int P1_OFF_BAR = P1_OFF_A + 3 * 2048;
constexpr int P1_OFF_TILE = P1_OFF_BAR + (2 * P1_NST + 3 + 2 + 3 + 2) * 8;
constexpr int P1_OFF_DW = P1_OFF_TILE + 64;
constexpr int P1_SMEM = P1_OFF_DW + C_DIM * 2;

__device__ __forceinline__ float rsqrt_fast(float x) {
    float r;
    asm("rsqrt.approx.ftz.f32 %0, %1;\n" : "=f"(r) : "f"(x));
    return r;
}
__device__ __forceinline__ float sum8(const uint32_t (&c)[4]) {
    const uint32_t u = bf2_add(bf2_add(c[0], c[1]), bf2_add(c[2], c[3]));
    return bf_lo(u) + bf_hi(u);
}
__device__ __forceinline__ void lds128(uint32_t (&v)[4], uint32_t a) {
    asm volatile("ld.shared.v4.u32 {%0,%1,%2,%3}, [%4];\n" : "=r"(v[0]), "=r"(v[1]), "=r"(v[2]), "=r"(v[3]) : "r"(a) : "memory");
}
template <class F>
__device__ __forceinline__ void ln_row(uint32_t (&v)[6][4], uint32_t sdw, F after_loads) {
    uint32_t c[4], s[4], d[4], nm;
#pragma unroll
    for (int i = 0; i < 6; i++) {
        lds128(d, sdw + i * 128);
        if (i == 0) {
#pragma unroll
            for (int k = 0; k < 4; k++) c[k] = bf2_mul(v[0][k], d[k]);
            const float p = sum8(c) * -0.125f;
            nm = pack_bf16(p, p);
        }
#pragma unroll
        for (int k = 0; k < 4; k++) {
            v[i][k] = bf2_fma(v[i][k], d[k], nm);
            s[k] = i ? bf2_add(v[i][k], s[k]) : v[i][k];
            c[k] = i ? bf2_fma(v[i][k], v[i][k], c[k]) : bf2_mul(v[i][k], v[i][k]);
        }
    }
    after_loads(c[0]);
    float m = fmaf(sum8(s), 1.0f / 48, -bf_lo(nm));
    float q = fmaf(-bf_lo(nm), fmaf(2.f, m, bf_lo(nm)), sum8(c) * (1.0f / 48));
#pragma unroll
    for (int o = 1; o < 8; o <<= 1) {
        m += __shfl_xor_sync(0xffffffffu, m, o);
        q += __shfl_xor_sync(0xffffffffu, q, o);
    }
    m *= 0.125f;
    const float r = KAPPA * rsqrt_fast(fmaxf(fmaf(-m, m, q * 0.125f), 0.f) + 1e-5f);
    const float e = (-bf_lo(nm) - m) * r * 0x1p-112f;
    const bool two = __any_sync(0xffffffffu, r < 0x1p-14f);
    const float r1 = r * (two ? 0x1p-56f : 0x1p-112f);
    uint32_t mul = pack_bf16(r1, r1), add = two ? 0u : pack_bf16(e, e);
#pragma unroll 1
    for (int it = !two; it < 2; it++) {
#pragma unroll
        for (int i = 0; i < 6; i++)
#pragma unroll
            for (int k = 0; k < 4; k++) v[i][k] = bf2_fma(v[i][k], mul, add);
        mul = 0x23802380u;
        add = pack_bf16(e, e);
    }
#pragma unroll
    for (int i = 0; i < 6; i++)
#pragma unroll
        for (int k = 0; k < 4; k++) v[i][k] = bf2_as_h2(v[i][k]);
}

__device__ __forceinline__ float gelu_s(float y) {
    float u = y * fmaf(y, y, GELU_C);
    float t;
    asm volatile("tanh.approx.f32 %0, %1;\n" : "=f"(t) : "f"(u));
    return fmaf(y, t, y);
}
__device__ __forceinline__ void p1_pack(int c, uint32_t (&p)[4], uint32_t (&dd)[4]) {
#pragma unroll
    for (int u = 0; u < 4; u++) {
        if ((c & 3) == 0) dd[u] = p[u];
        else {
            uint32_t n = dd[u];
            if ((c & 3) == 1) n = __byte_perm(n, 0, 0x2301);
            if ((c & 3) == 2) {
                dd[u] = __byte_perm(n >> 3, n >> 1, 0x6341);
                n = __byte_perm(n >> 3, n >> 1, 0x7250);
            }
            asm("lop3.b32 %0, %0, %1, 0x40074007, 0xd8;\n" : "+r"(p[u]) : "r"(n));
        }
    }
}
__device__ __forceinline__ void p1_store(int c, const uint32_t (&p)[4], uint8_t* hptr) {
    if (c & 3) stg128_cs(hptr + (c >> 2) * H_HALF + ((c & 3) - 1) * 512, p[0], p[1], p[2], p[3]);
}

template <bool GEN>
__device__ __forceinline__ void p1_epilogue(uint32_t (&acc)[32], float (&ssq)[2], uint32_t sc2, uint8_t* hp, int zero) {
    uint32_t sq[2], dd[4];
#pragma unroll
    for (int c = 0; c < 8; c++) {
        if (GEN) sched_break(zero);
        uint32_t p[4];
#pragma unroll
        for (int u = 0; u < 4; u++) {
            const uint32_t y = acc[8 * (c >> 1) + 2 * u + (c & 1)];
            if (GEN) {
                const float sc = c & 1 ? bf_hi(sc2) : bf_lo(sc2), fs = __uint_as_float(0x78000000u - __float_as_uint(sc));
                const float g0 = gelu_s(h_lo(y) * fs), g1 = gelu_s(h_hi(y) * fs);
                ssq[c & 1] = fmaf(g1, g1, fmaf(g0, g0, ssq[c & 1]));
                p[u] = pack_f16(g0 * sc, g1 * sc);
            } else {
                uint32_t g;
                asm("{\n.reg .b32 w;\n"
                    "fma.rn.f16x2 w, %1, %1, %2;\n"
                    "mul.rn.f16x2 w, w, %1;\n"
                    "tanh.approx.f16x2 w, w;\n"
                    "fma.rn.f16x2 %0, %1, w, %1;\n}\n" : "=r"(g) : "r"(y), "r"(0x40d940d9u));
                acc[8 * (c >> 1) + 2 * u + (c & 1)] = g;
                if (c < 2 && u == 0) asm("mul.rn.f16x2 %0, %1, %1;\n" : "=r"(sq[c & 1]) : "r"(g));
                else asm("fma.rn.f16x2 %0, %1, %1, %0;\n" : "+r"(sq[c & 1]) : "r"(g));
                if (c & 1) asm("{\n.reg .b16 l, h;\n.reg .b32 f;\nmov.b32 {l, h}, %2;\nmov.b32 f, {h, h};\nmul.rn.f16x2 %0, %1, f;\n}\n" : "=r"(p[u]) : "r"(g), "r"(sc2));
                else asm("{\n.reg .b16 l, h;\n.reg .b32 f;\nmov.b32 {l, h}, %2;\nmov.b32 f, {l, l};\nmul.rn.f16x2 %0, %1, f;\n}\n" : "=r"(p[u]) : "r"(g), "r"(sc2));
            }
        }
        p1_pack(c, p, dd);
        if (c & 3) {
#pragma unroll
            for (int u = 0; u < 4; u++) acc[4 * (c - 1 - (c >> 2)) + u] = p[u];
        }
        p1_store(c, p, hp);
    }
    if (!GEN) {
#pragma unroll
        for (int r = 0; r < 2; r++) ssq[r] += h_lo(sq[r]) + h_hi(sq[r]);
    }
}
__device__ __forceinline__ void p1_consumer(const uint32_t (&a)[24][4], uint32_t sc2, bool gen, uint32_t sbase, int wg, int nwg, int cb,
                                            int w, int lane, int zero) {
    const uint32_t bar_full = sbase + P1_OFF_BAR, bar_empty = bar_full + P1_NST * 8;
    const uint32_t empty_remote = mapa(bar_empty, lane & 1);
    const int g = lane >> 2, q = lane & 3, turn = wg + 1 == nwg ? 1 : wg + 2;
    float ssq[2] = {0.f, 0.f};
    uint32_t acc[32] = {};
    TSTAMP(0, 1);

    uint8_t* hp = reinterpret_cast<uint8_t*>(g_h) + ((cb * 2 + (w >> 1)) * H_STEP + (w & 1) * 1536) + g * 64 + (q ^ (g >> 1)) * 16;
    const uint64_t desc_base = make_desc(sbase, 16, 1024) | (1ull << 62);
    const uint64_t da = make_desc(sbase + P1_OFF_A + wg * 2048, 128, 256);
#pragma unroll 1
    for (int i = 0;; i++) {
        const int s0 = (i & 1) * 16, par = (i >> 1) & 1;
        const uint64_t d0 = desc_base + (uint64_t)((i & 1) * (LN_TILE / 16));
        TRACE(wg, i, 0);
        mbar_wait(bar_full + s0, par);
        bar_sync(1 + wg, 256);
        TRACE(wg, i, 1);
        uint32_t step, more;
        wg_fence();
#pragma unroll
        for (int k = 0; k < 24; k++) {
            if (k == 12) mbar_wait(bar_full + s0 + 8, par);
            const uint64_t db = d0 + (uint64_t)((k >> 2) * 1024 + (k & 3) * 2);
            if (k < 23) mma_rs_n128(acc, a[k], db, k ? 1 : zero);
            else mma_ss_n128(acc, da, db);
            if (k == 23) bar_arrive(turn, 256);
            if (k % 12 == 11) wg_commit();
        }
        asm volatile("ld.shared.v2.u32 {%0, %1}, [%2];\n" : "=r"(step), "=r"(more) : "r"(sbase + P1_OFF_TILE + (i & 3) * 16) : "memory");
        TRACE(wg, i, 2);
        wg_wait<1>();
        if (lane < 2) mbar_arrive_cluster(empty_remote + s0);
        hp += step;
        TRACE(wg, i, 3);
        wg_wait<0>();
        TRACE(wg, i, 4);
        if (lane < 2) mbar_arrive_cluster(empty_remote + s0 + 8);
        if (gen) p1_epilogue<true>(acc, ssq, sc2, hp, zero);
        else p1_epilogue<false>(acc, ssq, sc2, hp, zero);
        if (!more) break;
    }
    TSTAMP(0, 21);
    if (wg == 0) bar_sync(1, 256);
    uint32_t par;
    asm volatile("ld.shared.u32 %0, [%1];\n" : "=r"(par) : "r"(sbase + P1_OFF_TILE - 4) : "memory");
    float* sums = g_sums[par];
#pragma unroll
    for (int r = 0; r < 2; r++) {
        ssq[r] += __shfl_xor_sync(0xffffffffu, ssq[r], 1);
        ssq[r] += __shfl_xor_sync(0xffffffffu, ssq[r], 2);
        if (q == 0) atomicAdd(sums + cb * 64 + w * 16 + r * 8 + g, ssq[r]);
    }
}

__device__ __forceinline__ void p1_w2(const __nv_bfloat16* __restrict__ w2, const __nv_bfloat16* __restrict__ grn_b, int w, int lane) {
    const int gw = (blockIdx.x - 8 * NGRP) * 4 + w;
    float* sums = g_sums[__ldcg(&g_epoch) & 1] + HID;
    flag_wait<true>(&g_flag[40][1][0], 12);
    {
        const int col = gw % 6 * 64 + lane * 2;
        float bsum[2] = {0.f, 0.f}, asum[2] = {0.f, 0.f};
#pragma unroll 4
        for (int kk = 0; kk < 192; kk++) {
            const int k = gw / 6 * 192 + kk;
            const uint32_t v = *reinterpret_cast<const uint32_t*>(w2 + k * C_DIM + col);
            const float b = __bfloat162float(grn_b[k]), f = __uint_as_float(__ldcg(&g_ex[k]) << 23);
            bsum[0] = fmaf(b, bf_lo(v), bsum[0]);
            bsum[1] = fmaf(b, bf_hi(v), bsum[1]);
            asum[0] = fmaf(f, fabsf(bf_lo(v)), asum[0]);
            asum[1] = fmaf(f, fabsf(bf_hi(v)), asum[1]);
        }
#pragma unroll
        for (int j = 0; j < 2; j++) {
            atomicAdd(sums + col + j, bsum[j]);
            atomicAdd(sums + C_DIM + col + j, asum[j]);
        }
        __threadfence();
        __syncwarp();
        if (lane == 0) asm volatile("red.relaxed.gpu.global.add.u32 [%0], 1;\n" ::"l"(&g_flag[LN_RING + 2][0][0]) : "memory");
    }
    while (*(volatile unsigned*)&g_flag[P1_IMG % LN_RING][1][0] < 12 * (P1_IMG / LN_RING + 1)) {
        __nanosleep(2000);
        SAFE_BREAK
    }
    flag_wait<true>(&g_flag[LN_RING + 2][0][0], 48);
    float z = 0.f;
#pragma unroll
    for (int j = 0; j < C_DIM / 32; j++) z = fmaxf(z, __ldcg(sums + C_DIM + j * 32 + lane));
    const float sc = __uint_as_float((263u - acc_exp(__uint_as_float(__reduce_max_sync(0xffffffffu, __float_as_uint(z))))) << 23);
    const int np = gw % 6 * 64 + lane * 2;
#pragma unroll 2
    for (int cc = 0; cc < 24; cc++) {
        const int c = gw / 6 * 24 + cc;
        uint32_t v[8], o[2][4];
#pragma unroll
        for (int e = 0; e < 8; e++) v[e] = *reinterpret_cast<const uint32_t*>(w2 + (c * 8 + e) * C_DIM + perm32(np));
#pragma unroll
        for (int e = 0; e < 4; e++) {
            const uint2 t = __ldcg(reinterpret_cast<const uint2*>(g_ex) + c * 4 + e);
            const float f0 = __uint_as_float(t.x << 23), f1 = __uint_as_float(t.y << 23);
            o[0][e] = pack_f16(bf_lo(v[2 * e]) * f0 * sc, bf_lo(v[2 * e + 1]) * f1 * sc);
            o[1][e] = pack_f16(bf_hi(v[2 * e]) * f0 * sc, bf_hi(v[2 * e + 1]) * f1 * sc);
        }
#pragma unroll
        for (int j = 0; j < 2; j++)
            g_w2img[0][(((c >> 1) * 48 + (np >> 3)) * 2 + (c & 1)) * 8 + (np & 7) + j] = make_uint4(o[j][0], o[j][1], o[j][2], o[j][3]);
    }
    asm volatile("fence.proxy.async.global;\n" ::: "memory");
    __threadfence();
    __syncwarp();
    if (lane == 0) asm volatile("red.relaxed.gpu.global.add.u32 [%0], 1;\n" ::"l"(&g_img[0]) : "memory");
}

__global__ void __cluster_dims__(2, 1, 1) __launch_bounds__(512, 1)
pass1_kernel(const __grid_constant__ CUtensorMap wmap, const __nv_bfloat16* __restrict__ x, const __nv_bfloat16* __restrict__ dw,
             const __nv_bfloat16* __restrict__ w1, const __nv_bfloat16* __restrict__ w2, const __nv_bfloat16* __restrict__ grn_b, int zero) {
    extern __shared__ __align__(1024) uint8_t smem[];
    const uint32_t sbase = smem_u32(smem);
    const uint32_t bar_full = sbase + P1_OFF_BAR, bar_empty = bar_full + P1_NST * 8, bar_w = bar_empty + P1_NST * 8;
    const uint32_t bar_xfull = bar_w + 24, bar_raw = bar_xfull + 16, bar_done = bar_raw + 8;
    const int tid = threadIdx.x;
    const int warp = __shfl_sync(0xffffffffu, tid >> 5, 0), lane = tid & 31;
    const uint32_t rank = cluster_rank();
    const int cl = blockIdx.x >> 1;
    const bool small = cl >= 4 * NGRP;
    const int nwg = small ? 2 : 3, cb0 = small ? (blockIdx.x - 8 * NGRP) * 2 : (blockIdx.x & 7) * 3;
    uint8_t* const ring = reinterpret_cast<uint8_t*>(g_ln);

    TSTAMP(0, 0);
    TRACEW(110 + warp, 0);

    if (warp >= 12) {
        reg_dec<56>();
        asm volatile("barrier.cluster.arrive.relaxed.aligned;\n" ::: "memory");
        asm volatile("barrier.cluster.wait.aligned;\n" ::: "memory");
        {
            auto ring_row = [&](int p) {
                const int n = (p & 8) * 8 + (lane >> 3) * 8 + (p & 3) * 2 + (p >> 2 & 1);
                return n * 128 + (((lane ^ n) & 7) << 4);
            };
            const uint8_t* xsrc = reinterpret_cast<const uint8_t*>(x) + (size_t)(blockIdx.x * 2 + (warp & 1)) * P1_X;
            const uint32_t xbar = bar_xfull + (warp & 1) * 8, xdst = sbase + P1_OFF_X + (warp & 1) * P1_X;
            const uint32_t src = xdst + (lane >> 3) * (C_DIM * 2) + (lane & 7) * 16, sdw = sbase + P1_OFF_DW + (lane & 7) * 16;
            int row0 = ring_row((blockIdx.x & 7) * 2 + (warp & 1)) ^ 288, slot = blockIdx.x >> 3, used = 0;
            auto next = [&]() {
                xsrc += (size_t)LN_STEP * 8 * P1_X;
                if (elect_one()) {
                    mbar_expect_tx(xbar, P1_X);
                    bulk_g2s(xdst, xsrc, P1_X, xbar);
                }
                __syncwarp();
            };
#pragma unroll 1
            for (int i = -1; i * LN_STEP + (int)(blockIdx.x >> 2) < NT128 && blockIdx.x < 128; i++) {
                if (warp == 14) TRACEW(128 + i, 0);
                const int last = i > 0 ? 3 : i ? 2 + (warp >> 1 & 1) : blockIdx.x < 112 ? 1 : -1;
#pragma unroll 1
                for (int ps = i < 0 ? last - 4 : 0; ps <= last; ps += i < 0 ? 4 : 1) {
                    if (i < 0 && ps > 0) mbar_wait(bar_raw, 0);
                    if (ps == 0) {
                        if (used) flag_wait<false>(&g_flag[slot][1][0], used);
                        mbar_wait(xbar, i & 1);
                        if (warp == 14) TRACEW(128 + i, 1);
                    }
                    uint32_t v[6][4];
#pragma unroll
                    for (int j = 0; j < 6; j++) lds128(v[j], src + (ps & 3) * (4 * C_DIM * 2) + j * 128);
                    ln_row(v, sdw, [&](uint32_t dep) {
                        if (ps == 3 && i > 0 && (i + 1) * LN_STEP + (blockIdx.x >> 2) < NT128 && !__any_sync(0xffffffffu, dep & zero)) next();
                    });
                    uint8_t* dst = ring + (slot * LN_TILE + (ps & 1) * 4096 + (row0 ^ (ps & 2) * 144));
#pragma unroll
                    for (int j = 0; j < 6; j++)
                        asm volatile("{\n.reg .pred p;\nsetp.ge.s32 p, %5, 0;\n@p st.global.v4.u32 [%0], {%1,%2,%3,%4};\n}\n"
                                     ::"l"(dst + j * 16384), "r"(v[j][0]), "r"(v[j][1]), "r"(v[j][2]), "r"(v[j][3]), "r"(ps) : "memory");
                }
                if (warp == 14) TRACEW(128 + i, 2);
                asm volatile("fence.proxy.async.global;\nfence.acq_rel.cta;\n" ::: "memory");
                if (i < 0) {
                    bar_sync(4, 128);
                    if (warp < 14 || small) break;
                    row0 ^= 288;
                    slot += 16;
                } else {
                    if (i) mbar_wait(bar_done, ~i & 1);
                    else {
                        mbar_wait(xbar, 0);
                        next();
                        slot = blockIdx.x >> 2;
                        row0 = ring_row((blockIdx.x & 3) * 4 + (warp & 1) * 2);
                    }
                    __syncwarp();
                    if (lane == 0) mbar_arrive(bar_done);
                    if ((slot += LN_STEP) >= LN_RING) { slot -= LN_RING; used += 12; }
                }
            }
        }
        if (warp == 12) {
            int prev = 0, t = p1_tile(small ? 0 : cl >> 2, small), next = p1_tile(small ? 1 : (cl >> 2) + NGRP, small);
            const uint32_t rbase = mapa(sbase, lane & 1);
            int i = 0;
#pragma unroll 1
            for (; t < NT128; i++) {
                const int s0 = (i & 1) * 2, par = (i >> 1) & 1;
                const int round = t / LN_RING, slot = t - round * LN_RING;
                const uint8_t* src = ring + slot * LN_TILE + rank * (P1_SLOT / 2);
                int draw = i + 2;
                if (rank == 0 && lane == 0 && !small) draw = 2 * NGRP + atomicAdd(&g_flag[LN_RING + ((cl >> 1) & 1)][cl & 1][0], 1u);
                flag_wait<true>(&g_flag[slot][0][0], 8 * round + 8);
                TRACEW(i, 2);
                asm volatile("fence.proxy.async.global;\n" ::: "memory");
                draw = p1_tile(__shfl_sync(0xffffffffu, draw, 0), small);
#pragma unroll
                for (int h = 0; h < 2; h++) {
                    mbar_wait(bar_empty + (s0 + h) * 8, par);
                    TRACEW(i, 4 + h);
                    if (elect_one()) {
                        mbar_expect_tx(bar_full + (s0 + h) * 8, P1_SLOT + 16 - 16 * h);
                        bulk_g2s_mc(sbase + (s0 + h) * P1_SLOT + rank * (P1_SLOT / 2), src + h * P1_SLOT, P1_SLOT / 2, bar_full + (s0 + h) * 8, (uint16_t)3);
                    }
                    __syncwarp();
                    if (h == 0 && rank == 0 && lane < 2)
                        asm volatile("st.async.shared::cluster.mbarrier::complete_tx::bytes.v4.u32 [%0], {%1, %2, %3, %3}, [%4];\n"
                                     ::"r"(rbase + P1_OFF_TILE + (i & 3) * 16), "r"((t - prev) * (2 * H_TILE)), "r"((int)(next < NT128)), "r"(draw),
                                       "r"(rbase + P1_OFF_BAR + s0 * 8) : "memory");
                }
                prev = t;
                t = next;
                next = draw;
                if (rank != 0) {
                    mbar_wait(bar_full + s0 * 8, (i >> 1) & 1);
                    mbar_wait(bar_full + s0 * 8 + 8, (i >> 1) & 1);
                    if (lane == 0) asm volatile("red.relaxed.gpu.global.add.u32 [%0], %1;\n" ::"l"(&g_flag[slot][1][0]), "r"(nwg) : "memory");
                    asm volatile("ld.shared.u32 %0, [%1];\n" : "=r"(next) : "r"(sbase + P1_OFF_TILE + (i & 3) * 16 + 8) : "memory");
                    TRACEW(i, 3);
                }
            }
#pragma unroll 1
            for (int j = 2 * i; j < 2 * i + 4; j++) mbar_wait(bar_empty + (j & 3) * 8, (j >> 2) & 1);
        } else if (warp == 13) {
            if (lane == 0 && blockIdx.x < 128) asm volatile("red.release.gpu.global.add.u32 [%0], 1;\n" ::"l"(&g_flag[blockIdx.x >> 3][0][0]) : "memory");
            __syncwarp();
            const uint32_t ep = g_epoch & 1;
            asm volatile("st.shared.u32 [%0], %1;\n" ::"r"(sbase + P1_OFF_TILE - 4), "r"(ep) : "memory");
            if (blockIdx.x == 18) g_par = ep;
            if (blockIdx.x < 18) reinterpret_cast<float4*>(g_sums[ep ^ 1])[blockIdx.x * 32 + lane] = make_float4(0.f, 0.f, 0.f, 0.f);
#pragma unroll 1
            for (int i = 0; !small && i * LN_STEP + (blockIdx.x >> 2) < NT128; i++) {
                mbar_wait(bar_done, i & 1);
                asm volatile("fence.proxy.async.global;\n" ::: "memory");
                if (lane == 0) {
                    mbar_arrive(bar_done);
                    asm volatile("red.release.gpu.global.add.u32 [%0], %1;\n"
                                 ::"l"(&g_flag[i ? (blockIdx.x >> 2) + i % LN_DEPTH * LN_STEP : 16 + (blockIdx.x >> 3)][0][0]), "r"(i ? 2 : (int)(blockIdx.x < 112)) : "memory");
                }
                __syncwarp();
                TRACEW(128 + i, 3);
            }
            flag_wait<true>(&g_flag[LN_RING + 2][0][0], 48);
        }
    } else {
        if (tid == 0) {
            mbar_init(bar_raw, 1);
            mbar_init(bar_xfull, 1);
            mbar_init(bar_xfull + 8, 1);
            for (int i = 0; i < 3; i++) mbar_init(bar_w + i * 8, 1);
            asm volatile("fence.mbarrier_init.release.cluster;\n" ::: "memory");
            mbar_expect_tx(bar_raw, P1_X + C_DIM * 2);
            bulk_g2s(sbase + P1_OFF_DW, dw, C_DIM * 2, bar_raw);
            for (int i = 0; i < 2; i++) bulk_g2s(sbase + P1_OFF_X + i * P1_X + P1_X / 2, x + (size_t)(blockIdx.x * 16 + i * 8) * C_DIM, P1_X / 2, bar_raw);
            if (blockIdx.x < 128)
                asm volatile("cp.async.bulk.prefetch.L2.global [%0], 9216;\n" ::"l"(w1 + blockIdx.x * 4608) : "memory");
            for (int i = 0; i < 2; i++) {
                mbar_expect_tx(bar_xfull + i * 8, P1_X / 2);
                bulk_g2s(sbase + P1_OFF_X + i * P1_X, x + (size_t)(16 * 128 + blockIdx.x * 16 + i * 8) * C_DIM, P1_X / 2, bar_xfull + i * 8);
            }
            for (int i = 0; i < nwg; i++) {
                mbar_expect_tx(bar_w + i * 8, P1_SLOT);
                tma2(sbase + (1 + i) * P1_SLOT, &wmap, (cb0 + i) * 64, 0, bar_w + i * 8);
                tma2(sbase + (1 + i) * P1_SLOT + P1_SLOT / 2, &wmap, (cb0 + i) * 64, 192, bar_w + i * 8);
            }
        }
        if (tid == 32) {
            mbar_init(bar_done, 3);
            mbar_arrive(bar_done);
            asm volatile("fence.mbarrier_init.release.cluster;\n" ::: "memory");
        }
        if (tid == 64) {
            for (int i = 0; i < P1_NST; i++) {
                mbar_init(bar_full + i * 8, 1);
                mbar_init(bar_empty + i * 8, 8 * nwg);
            }
            asm volatile("fence.mbarrier_init.release.cluster;\n" ::: "memory");
            if (blockIdx.x < 64) (&g_half[0][0])[blockIdx.x] = 0;
            else if (blockIdx.x == 64) g_prog = 0;
            else if (blockIdx.x < 67) g_img[blockIdx.x - 65] = 0;
        }
        __syncwarp();
        asm volatile("barrier.cluster.arrive.relaxed.aligned;\n" ::: "memory");
        reg_inc<152>();
        TRACEW(110 + warp, 1);
        const int wg = warp >> 2, w = warp & 3;
        gdc_launch();
        asm volatile("barrier.cluster.wait.aligned;\n" ::: "memory");
        if (wg == nwg) {
            p1_w2(w2, grn_b, w, lane);
            return;
        }
        const uint32_t slot_free = mapa(bar_empty, lane & 1) + (lane >> 1) * 8;
        if (lane < 8 && (lane >> 1) != 1 + wg) mbar_arrive_cluster(slot_free);
        if (wg == 1) bar_arrive(1, 256);
        uint32_t a[24][4], ex[2], gen = 0;
        const uint32_t wsrc = sbase + (1 + wg) * P1_SLOT + ((lane >> 4) * 8 + (lane & 7)) * 128 + (((2 * w + ((lane >> 3) & 1)) ^ (lane & 7)) << 4);
#pragma unroll 1
        for (int it = 0; it < 2; it++) {
            if (it) mbar_wait(bar_w + wg * 8, 0);
            TRACEW(110 + warp, 5);
            if (it || wg == 0) {
#pragma unroll
            for (int k = 0; k < 24; k++) ldsm4t(a[k], wsrc + k * 2048);
#pragma unroll
            for (int r = 0; r < 2; r++) {
                float t = 0.f;
#pragma unroll
                for (int j = 0; j < 6; j++) {
                    uint32_t c = bf2_mul(a[4 * j][r], a[4 * j][r]);
#pragma unroll
                    for (int k = 1; k < 8; k++) c = bf2_fma(a[4 * j + k / 2][r + (k & 1) * 2], a[4 * j + k / 2][r + (k & 1) * 2], c);
                    t += bf_lo(c) + bf_hi(c);
                }
                t += __shfl_xor_sync(0xffffffffu, t, 1);
                t += __shfl_xor_sync(0xffffffffu, t, 2);
                asm("sqrt.approx.f32 %0, %0;\n" : "+f"(t));
                ex[r] = min(max(__float_as_uint(13.9f * t) >> 23, 72u), 198u);
            }
            asm volatile("{\n.reg .pred p;\nsetp.gt.u32 p, %1, 7;\nbar.red.or.pred p, %2, 128, p;\nselp.u32 %0, 1, 0, p;\n}\n"
                         : "=r"(gen) : "r"(max(ex[0] - 125u, ex[1] - 125u)), "r"(5 + wg) : "memory");
            gen = __shfl_sync(0xffffffffu, gen, 0) & it;
            if (it) {
                if ((lane & 3) < 2) g_ex[(cb0 + wg) * 64 + w * 16 + (lane & 1) * 8 + (lane >> 2)] = lane & 1 ? ex[1] : ex[0];
                if ((lane >> 1) == 1 + wg) mbar_arrive_cluster(slot_free);
                __syncwarp();
            }
            }
            if (gen) {
#pragma unroll
                for (int k = 0; k < 24; k++)
#pragma unroll
                    for (int j = 0; j < 4; j++) a[k][j] = bf2_mul(a[k][j], (268u - ex[j & 1]) * 0x00800080u);
            }
            if (it || wg == 1) {
#pragma unroll
                for (int k = 0; k < 24; k++)
#pragma unroll
                    for (int j = 0; j < 4; j++) {
                        a[k][j] = bf2_as_h2(bf2_mul(a[k][j], 0x07800780u));
                        asm volatile("" : "+r"(a[k][j]));
                    }
            }
            TRACEW(110 + warp, 6);
        }
#pragma unroll
        for (int j = 0; j < 4; j++)
            asm volatile("st.shared.u32 [%0], %1;\n" ::"r"(sbase + P1_OFF_A + warp * 512 + (j & 1) * 256 + (j >> 1) * 128 + lane * 4), "r"(a[23][j]) : "memory");
        asm volatile("fence.proxy.async.shared::cta;\n" ::: "memory");
        TRACEW(110 + warp, 7);
        const uint32_t ex2 = ex[0] | ex[1] << 16;
        p1_consumer(a, gen ? 0x7f007f00u - (ex2 << 7) : (0x008e008eu - ex2) << 10, gen, sbase, wg, nwg, cb0 + wg, w, lane, zero);
        TSTAMP(0, 30);
    }
}

#define P2_NB_ 5
#define P2_NA_ 5
#define P2_DELTA_ 7
#define P2_EXTRA 0
#define P2_HSLEEP 64
#define P2_PSLEEP 100
#define P2_T0 5
#define P2_TS 11
constexpr int P2_B = 24576, P2_NB = P2_NB_;
constexpr int P2_A = 3072, P2_NA = P2_NA_;
constexpr int P2_XROW = C_DIM * 2;
constexpr int P2_OFF_A = P2_B * P2_NB;
constexpr int P2_OFF_X = P2_OFF_A + 3 * P2_NA * P2_A;
constexpr int P2_XHALF = 32 * P2_XROW + 64;
constexpr int P2_OFF_BIAS = P2_OFF_X + 64 * P2_XROW + 64;
constexpr int P2_OFF_GRN = P2_OFF_BIAS + C_DIM * 4;
constexpr int P2_OFF_BAR = P2_OFF_GRN + HID * 2;
constexpr int P2_SMEM = P2_OFF_BAR + (2 * P2_NB + 6 * P2_NA + 3) * 8;
#define P2_LAG_ 17
constexpr int P2_LAG = P2_LAG_;
constexpr int P2_NCL = NUM_CTAS / 2, P2_ITEMS = NT128 / P2_NCL, P2_SHARED = NT128 - P2_ITEMS * P2_NCL;
constexpr int P2_POS = P2_LAG * (P2_ITEMS - 1) + 48;
__device__ __forceinline__ int p2_start(int n) { return n < 0 ? 0 : n == P2_ITEMS ? P2_POS - 24 : P2_LAG * n; }
constexpr int P2_FOLD = P2_LAG - 1 + (P2_LAG & 1);
constexpr int P2_XC = 8 * P2_XROW;
constexpr int P2_DELTA = P2_DELTA_;
__device__ __forceinline__ int p2_tile(int cl, int n) {
    return n == 0 ? NT128 - 1 - cl : n < 0 || n == P2_ITEMS ? NT128 - 1 - P2_NCL - (cl >> 1) : cl + P2_NCL * (n - 1);
}

constexpr int P2_EG = 2;
__device__ __forceinline__ void p2_epilogue(const uint32_t (&acc0)[48], const uint32_t (&acc1)[48], uint32_t sx, uint32_t sb, float up, int zero) {
    uint32_t v[2][P2_EG][4];
    float b[2][8];
    auto load = [&](int c, uint32_t a) {
#pragma unroll
        for (int j = 0; j < 2; j++)
            asm volatile("ld.shared.v4.f32 {%0,%1,%2,%3}, [%4];\n" : "=f"(b[c & 1][4 * j]), "=f"(b[c & 1][4 * j + 1]), "=f"(b[c & 1][4 * j + 2]), "=f"(b[c & 1][4 * j + 3])
                         : "r"(sb + c * 128 + j * 16) : "memory");
#pragma unroll
        for (int j = 0; j < P2_EG; j++) {
            const int u = c * P2_EG + j;
            asm volatile("ld.shared.v4.u32 {%0,%1,%2,%3}, [%4];\n" : "=r"(v[c & 1][j][0]), "=r"(v[c & 1][j][1]), "=r"(v[c & 1][j][2]), "=r"(v[c & 1][j][3])
                         : "r"(a + (u >> 1) * 64 + (u & 1) * 4 * P2_XROW) : "memory");
        }
    };
    load(0, sx);
#pragma unroll
    for (int c = 0; c < 24 / P2_EG; c++) {
        if (c + 1 < 24 / P2_EG) load(c + 1, sx + (v[c & 1][P2_EG - 1][0] & zero));
#pragma unroll
        for (int j = 0; j < P2_EG; j++) {
            const int u = c * P2_EG + j, i = 8 * ((u >> 1) % 6) + (u & 1);
            const uint32_t (&acc)[48] = u < 12 ? acc0 : acc1;
            uint32_t (&w)[4] = v[c & 1][j];
#pragma unroll
            for (int e = 0; e < 4; e++)
                w[e] = bf2_add(pack_bf16(fmaf(h_lo(acc[i + 2 * e]), up, b[c & 1][2 * e]), fmaf(h_hi(acc[i + 2 * e]), up, b[c & 1][2 * e + 1])), w[e]);
            asm volatile("st.shared.v4.u32 [%4], {%0,%1,%2,%3};\n" ::"r"(w[0]), "r"(w[1]), "r"(w[2]), "r"(w[3]),
                         "r"(sx + (u >> 1) * 64 + (u & 1) * 4 * P2_XROW) : "memory");
        }
    }
}

__device__ __forceinline__ void p2_unpack(uint4& u, uint32_t o1, uint32_t o2, uint32_t o3) {
    u.z = o1 & 0xbff8bff8u;
    u.y = o2 & 0xbff8bff8u;
    u.w = o3 & 0xbff8bff8u;
    u.x = (__byte_perm(o1, 0, 0x2301) & 0x07400740u) | ((__byte_perm(o2, o3, 0x6240) << 3) & 0x38383838u) | ((__byte_perm(o2, o3, 0x3715) << 1) & 0x80808080u);
}
__device__ __forceinline__ uint32_t h2_mul(uint32_t a, uint32_t b) {
    uint32_t r;
    asm("mul.rn.f16x2 %0, %1, %2;\n" : "=r"(r) : "r"(a), "r"(b));
    return r;
}
__device__ __forceinline__ void p2_epilogue_add(const uint32_t (&acc)[48], uint8_t* o, float f, int zero) {
#pragma unroll
    for (int t = 0; t < 12; t++) {
        uint32_t v[4];
#pragma unroll
        for (int e = 0; e < 4; e++) {
            v[e] = acc[8 * (t >> 1) + (t & 1) + 2 * e];
            asm volatile("" : "+r"(v[e]));
            v[e] = pack_bf16(h_lo(v[e]) * f, h_hi(v[e]) * f);
        }
        asm volatile("red.global.add.noftz.v4.bf16x2 [%0], {%1,%2,%3,%4};\n" ::"l"(o + (t >> 1) * 64 + (t & 1) * 4 * P2_XROW),
                     "r"(v[0]), "r"(v[1]), "r"(v[2]), "r"(v[3]) : "memory");
        if (t % 3 == 2) sched_break(zero);
    }
}

__global__ void __cluster_dims__(2, 1, 1) __launch_bounds__(512, 1)
pass2_kernel(const __nv_bfloat16* __restrict__ x, const __nv_bfloat16* __restrict__ grn_g, __nv_bfloat16* __restrict__ out, int zero) {
    extern __shared__ __align__(1024) uint8_t smem[];
    const uint32_t sbase = smem_u32(smem);
    const uint32_t bar_bfull = sbase + P2_OFF_BAR, bar_bempty = bar_bfull + P2_NB * 8;
    const uint32_t bar_afull = bar_bempty + P2_NB * 8, bar_aempty = bar_afull + 3 * P2_NA * 8;
    const uint32_t bar_xfull = bar_aempty + 3 * P2_NA * 8, bar_oready = bar_xfull + 8, s_pos = bar_xfull + 16;
    int tid;
    asm volatile("mov.u32 %0, %%tid.x;\n" : "=r"(tid));
    const int warp = __shfl_sync(0xffffffffu, tid >> 5, 0), lane = tid & 31;
    const uint32_t rank = cluster_rank();
    const int cl = blockIdx.x >> 1, pair = cl >> 1;
    const int k0 = (4 * pair + (cl & 1) * (48 - P2_POS % 48)) % 48;
    const int head = pair < P2_SHARED && !(cl & 1), tail = pair < P2_SHARED && (cl & 1);

    uint32_t par, gg[4];
    float pre[4];
    if (warp < 12) {
        asm volatile("ld.global.cg.u32 %0, [%1];\n" : "=r"(par) : "l"(&g_par) : "memory");
#pragma unroll
        for (int i = 0; i < 4; i++) {
            asm volatile("ld.global.cg.f32 %0, [%1];\n" : "=f"(pre[i]) : "l"(&g_sums[i & 1][HID + (i >> 1) * C_DIM + tid]) : "memory");
            asm volatile("ld.global.nc.u16 %0, [%1];\n" : "=r"(gg[i]) : "l"(grn_g + tid + 384 * i) : "memory");
        }
    }
    TSTAMP(1, 0);
    if (tid == 384) {
        for (int i = 0; i < P2_NB; i++) {
            mbar_init(bar_bfull + i * 8, 1);
            mbar_init(bar_bempty + i * 8, 24);
        }
        for (int i = 0; i < 3 * P2_NA; i++) {
            mbar_init(bar_afull + i * 8, 1);
            mbar_init(bar_aempty + i * 8, 4);
        }
        mbar_init(bar_xfull, 2);
        mbar_init(bar_oready, 4);
        asm volatile("st.shared.u32 [%0], 0;\n" ::"r"(s_pos) : "memory");
        asm volatile("fence.mbarrier_init.release.cluster;\n" ::: "memory");
    }
    __syncthreads();
    cluster_sync_relaxed();

    if (warp >= 12) {
        reg_dec<32>();
        if (warp == 12) {
            const uint8_t* wsrc = reinterpret_cast<const uint8_t*>(g_w2img) + rank * (P2_B / 2);
            int st = 0, ph = 1, kb = k0, m = 0, r = 0;
            const int busy = head ? 0 : tail ? P2_POS - 24 : P2_POS;
#pragma unroll 1
            for (int p = 0; p < P2_POS; p++) {
                if (p == 0 || p == P2_FOLD) {
                    flag_wait<true>(&g_img[p != 0], p ? 96 * 4 : 48);
                    asm volatile("fence.proxy.async.global;\n" ::: "memory");
                    if (p) wsrc += sizeof(g_w2img[0]);
                }
                mbar_wait(bar_bempty + st * 8, ph);
                TR2P(p, 0);
                if (elect_one()) {
                    mbar_expect_tx(bar_bfull + st * 8, P2_B);
                    bulk_g2s_mc(sbase + st * P2_B + rank * (P2_B / 2), wsrc + kb * P2_B, P2_B / 2, bar_bfull + st * 8, (uint16_t)3);
                    asm volatile("st.volatile.shared.u32 [%0], %1;\n" ::"r"(s_pos), "r"(p) : "memory");
                    const int idle = 2 - min(m, P2_ITEMS - 1) + max(m - 2 + (r >= 48 - 2 * P2_LAG), 0) - ((unsigned)(p - busy) < 24);
                    if (idle) asm volatile("mbarrier.arrive.shared::cta.b64 _, [%0], %1;\n" ::"r"(bar_bempty + st * 8), "r"(idle * 8) : "memory");
                    if (rank == 0) asm volatile("red.relaxed.gpu.global.add.u32 [%0], 1;\n" ::"l"(&g_prog) : "memory");
                }
                __syncwarp();
                if (++st == P2_NB) { st = 0; ph ^= 1; }
                if (++kb == 48) kb = 0;
                if (++r == P2_LAG) { r = 0; m++; }
            }
            mbar_wait(bar_bempty + st * 8, ph);
            if (lane == 0) mbar_arrive(bar_bfull + st * 8);
#pragma unroll 1
            for (int p = 1; p < P2_NB; p++) {
                if (++st == P2_NB) { st = 0; ph ^= 1; }
                mbar_wait(bar_bempty + st * 8, ph);
            }
        } else if (warp == 13) {
            const uint8_t* src[3];
            int n[3], left[3], wrap[3];
            uint32_t st[3];
            auto item = [&](int w) {
                const int u = (k0 + p2_start(n[w])) % 48;
                left[w] = n[w] < 0 || n[w] == P2_ITEMS ? 24 : 48;
                wrap[w] = left[w] - (48 - u);
                src[w] = reinterpret_cast<const uint8_t*>(g_h) + (size_t)p2_tile(cl, n[w]) * (2 * H_TILE) + rank * H_HALF + u * H_STEP;
            };
#pragma unroll
            for (int w = 0; w < 3; w++) {
                n[w] = w == 2 && head ? -1 : w;
                st[w] = 0x80000000u;
                item(w);
            }
            gdc_wait();
#pragma unroll 1
            for (int done = 0; done < 3;) {
                bool idle = true;
#pragma unroll
                for (int w = 0; w < 3; w++) {
                    const uint32_t o = (st[w] & 0xff) + w * P2_NA * 8;
                    if (left[w] >= 0 && mbar_test(bar_aempty + o, st[w] >> 31)) {
                        idle = false;
                        if (left[w] == 0) {
                            if (lane == 0) mbar_arrive(bar_afull + o);
                            left[w] = -1;
                            done++;
                        } else {
                            if (elect_one()) {
                                mbar_expect_tx(bar_afull + o, P2_A);
                                bulk_g2s(sbase + P2_OFF_A + o * (P2_A / 8), src[w], P2_A, bar_afull + o);
                            }
                            __syncwarp();
                            src[w] += H_STEP;
                            st[w] += 8;
                            if ((st[w] & 0xff) == P2_NA * 8) st[w] ^= 0x80000000u | (P2_NA * 8);
                            if (--left[w] == wrap[w]) src[w] -= 48 * H_STEP;
                            if (left[w] == 0 && (n[w] += 3) < P2_ITEMS + tail) item(w);
                        }
                    }
                }
                if (idle) __nanosleep(P2_HSLEEP);
                SAFE_BREAK
            }
        } else if (warp == 14) {
            const uint32_t sx = sbase + P2_OFF_X;
            size_t o = 0;
            auto pace = [&](int target) {
                int v;
                while (true) {
                    asm volatile("ld.volatile.shared.u32 %0, [%1];\n" : "=r"(v) : "r"(s_pos) : "memory");
                    if (v * 16 >= target) break;
                    __nanosleep(P2_PSLEEP);
                    SAFE_BREAK
                }
            };
#pragma unroll 1
            for (int n = -head; n <= P2_ITEMS; n++) {
                const size_t on = (size_t)(2 * p2_tile(cl, n) + rank) * (64 * C_DIM * 2);
                const bool st = n + head > 0, ld = n < P2_ITEMS;
                if (st) mbar_wait(bar_oready, (n - 1 + head) & 1);
                TR2P(n + 1, 1);
                if (lane == 0) {
                    if (n == 1 && head) {
                        asm volatile("cp.async.bulk.wait_group 0;\nfence.proxy.async.global;\n" ::: "memory");
                        asm volatile("st.release.gpu.global.u32 [%0], 1;\n" ::"l"(&g_half[pair][rank]) : "memory");
                    }
                    if (ld) mbar_expect_tx(bar_xfull, 64 * C_DIM * 2);
                    int t = st && n < P2_ITEMS - 1 ? (P2_LAG * (n - 1) + 48 + P2_T0 - 1) * 16 : -1024;
#pragma unroll 1
                    for (int c = 0; st && c < 64 * P2_XROW; c += P2_XC) {
                        pace(t += P2_TS);
                        bulk_s2g(reinterpret_cast<uint8_t*>(out) + o + c, sx + c + (c >= 32 * P2_XROW ? 64 : 0), P2_XC);
                    }
                    asm volatile("cp.async.bulk.commit_group;\ncp.async.bulk.wait_group.read 0;\n" ::: "memory");
#pragma unroll 1
                    for (int c = 0; ld && c < 64 * P2_XROW; c += P2_XC) {
                        pace(t += P2_TS);
                        bulk_g2s(sx + c + (c >= 32 * P2_XROW ? 64 : 0), reinterpret_cast<const uint8_t*>(x) + on + c, P2_XC, bar_xfull);
                    }
                    TR2P(n + 1, 2);
                    if (rank == 0 && n > 0 && n < P2_ITEMS - 2)
                        flag_wait<false>(&g_prog, P2_NCL * (P2_LAG * n + 48 + P2_EXTRA) + (tail ? P2_SHARED - P2_NCL : P2_SHARED) * P2_DELTA);
                    if (ld) mbar_arrive(bar_xfull);
                    TR2P(n + 1, 3);
                }
                __syncwarp();
                o = on;
            }
            asm volatile("cp.async.bulk.wait_group 0;\n" ::: "memory");
            TR2P(30, 1);
        }
    } else {
        reg_inc<160>();
        const int wg = warp >> 2, w = warp & 3, g = lane >> 2, q = lane & 3;
        const uint32_t sx = sbase + P2_OFF_X + (g & 1) * P2_XHALF + (w * 8 + (g >> 1)) * P2_XROW + q * 16;
        const uint32_t af = bar_afull + wg * P2_NA * 8, ae = bar_aempty + wg * P2_NA * 8;
        const uint32_t s_a = sbase + P2_OFF_A - bar_afull * (P2_A / 8) + (lane >> 3) * 512 + (lane & 7) * 64 +
                             ((w ^ ((lane & 7) >> 1)) << 4);
        uint32_t acc0[48], acc1[48];
        float up;
        uint4 a0[2], a1[2];
        int st = 0, ph = 0;

        {
            float4* s_red = reinterpret_cast<float4*>(smem + P2_OFF_BIAS);
            const float* sums = g_sums[par];
            float gx[4], part = 0.f, mx = 0.f;
            TSTAMP(1, 27);
            gdc_wait();
            TSTAMP(1, 1);
#pragma unroll
            for (int i = 0; i < 4; i++) gx[i] = __ldcg(sums + tid + 384 * i);
            if (blockIdx.x == 120 && tid < (LN_RING + 3) * 2) (&g_flag[0][0][0])[tid * 8] = 0;
            if (blockIdx.x == 121 && tid == 0) atomicAdd(&g_epoch, 1u);
            float z = __uint_as_float(__reduce_max_sync(0xffffffffu, __float_as_uint(pre[2] + pre[3])));
#pragma unroll
            for (int i = 0; i < 4; i++) {
                asm("sqrt.approx.f32 %0, %1;\n" : "=f"(gx[i]) : "f"(fmaf(gx[i], HSCALE * HSCALE, 1e-6f)));
                part += gx[i];
                gx[i] *= bf_lo(gg[i]);
                mx = fmaxf(mx, fabsf(gx[i]));
            }
#pragma unroll
            for (int o = 16; o > 0; o >>= 1) part += __shfl_xor_sync(0xffffffffu, part, o);
            mx = __uint_as_float(__reduce_max_sync(0xffffffffu, __float_as_uint(mx)));
            TSTAMP(1, 26);
            if (lane == 0) s_red[warp] = make_float4(part, mx, z, 0.f);
            bar_sync(1, 384);
            float tot = 0.f;
            {
                const float4 t = s_red[min(lane & 15, 11)];
                tot = (lane & 15) < 12 ? t.x : 0.f;
#pragma unroll
                for (int o = 8; o > 0; o >>= 1) tot += __shfl_xor_sync(0xffffffffu, tot, o);
                mx = __uint_as_float(__reduce_max_sync(0xffffffffu, __float_as_uint(t.y)));
                z = __uint_as_float(__reduce_max_sync(0xffffffffu, __float_as_uint(t.z)));
            }
            const float inv = __fdividef(1.0f, fmaf(tot, 1.0f / HID, 1e-6f));
            const uint32_t j = max(__float_as_uint(fmaf(mx, inv, 1.0f) * 1.01f) >> 23, 130u) - 130u;
            const float dn = __uint_as_float((127u - j) << 23);
#pragma unroll
            for (int i = 0; i < 4; i++)
                *reinterpret_cast<uint16_t*>(smem + P2_OFF_GRN + (tid + 384 * i) * 2) = pack_f16(fmaf(gx[i], inv, 1.0f) * dn, 0.f);
            up = (HSCALE * 1.00235f) * __uint_as_float(min(acc_exp(z) - 9u + j, 253u) << 23);
            TSTAMP(1, 25);
            bar_sync(1, 384);
            reinterpret_cast<float*>(smem + P2_OFF_BIAS)[tid] = pre[0] + pre[1];
            if (wg == 1 && blockIdx.x < 96) {
                const uint4* src = g_w2img[0] + blockIdx.x * 768 + tid - 128;
                const uint4 fk = *reinterpret_cast<const uint4*>(smem + P2_OFF_GRN + blockIdx.x * 32 + (tid & 8) * 2);
                uint4 v[6];
#pragma unroll
                for (int i = 0; i < 6; i++) v[i] = __ldcg(src + i * 128);
                auto fold = [&](uint32_t b, uint32_t f) { return (h2_mul(b, f) + 0x00040004u) & 0xfff8fff8u; };
#pragma unroll
                for (int i = 0; i < 6; i++)
                    g_w2img[1][blockIdx.x * 768 + tid - 128 + i * 128] = make_uint4(fold(v[i].x, fk.x), fold(v[i].y, fk.y), fold(v[i].z, fk.z), fold(v[i].w, fk.w));
                asm volatile("fence.proxy.async.global;\n" ::: "memory");
                __threadfence();
                __syncwarp();
                if (lane == 0) asm volatile("red.release.gpu.global.add.u32 [%0], 1;\n" ::"l"(&g_img[1]) : "memory");
            }
        }
        TSTAMP(1, 28);
        int kt = k0, pos;
        const int who = __shfl_sync(0xffffffffu, lane == 2 ? 0 : lane < 2 ? 1 : 2, lane);
        const uint32_t rel0 = who ? mapa(bar_bempty, lane & 1) : mapa(ae, rank), rel1 = rel0 + (who ? P2_NB : P2_NA) * 8;
        uint32_t rel = rel1 - 8;
        auto next_rel = [&](bool go) {
            if (go) rel += 8;
            if (rel == rel1) rel = rel0;
        };
        auto release_b = [&]() {
            next_rel(who == 1);
            if (who == 1) mbar_arrive_cluster(rel);
        };
        auto seek = [&](int p) {
            pos = p;
            st = p % P2_NB;
            ph = p / P2_NB & 1;
            if (who == 1) rel = (st ? rel0 + st * 8 : rel1) - 8;
            int v;
            while (true) {
                asm volatile("ld.volatile.shared.u32 %0, [%1];\n" : "=r"(v) : "r"(s_pos) : "memory");
                if (v >= p) break;
                __nanosleep(200);
                SAFE_BREAK
            }
        };
        auto publish = [&]() {
            asm volatile("fence.proxy.async.shared::cta;\n" ::: "memory");
            __syncwarp();
            if (who == 0) mbar_arrive(bar_oready);
        };
        bool ok_a;
        uint32_t abar = af, pa = 0;
        auto fetch = [&](uint4 (&a)[2], bool early) {
            const uint32_t src = s_a + abar * (P2_A / 8);
            abar += 8;
            if (abar == af + P2_NA * 8) { abar = af; pa ^= 0x80000000u; }
            const bool ok_b = mbar_test(bar_bfull + st * 8, ph);
            ok_a = mbar_test(abar, pa >> 31);
            uint32_t o[6];
            asm volatile("ldmatrix.sync.aligned.m8n8.x4.trans.shared.b16 {%0,%1,%2,%3}, [%4];\n"
                         : "=r"(o[0]), "=r"(o[1]), "=r"(o[2]), "=r"(o[3]) : "r"(src) : "memory");
            asm volatile("ldmatrix.sync.aligned.m8n8.x2.trans.shared.b16 {%0,%1}, [%2];\n"
                         : "=r"(o[4]), "=r"(o[5]) : "r"(src + 2048) : "memory");
            p2_unpack(a[0], o[0], o[1], o[2]);
            p2_unpack(a[1], o[3], o[4], o[5]);
            if (early) {
                const uint32_t* t = reinterpret_cast<const uint32_t*>(smem + P2_OFF_GRN) + kt * 16 + q;
#pragma unroll
                for (int i = 0; i < 2; i++)
                    a[i] = make_uint4(h2_mul(a[i].x, t[8 * i]), h2_mul(a[i].y, t[8 * i]), h2_mul(a[i].z, t[8 * i + 4]), h2_mul(a[i].w, t[8 * i + 4]));
                if (++kt == 48) kt = 0;
            }
            if (!ok_b) mbar_wait(bar_bfull + st * 8, ph);
        };
        auto step = [&](const uint4 (&a)[2], uint4 (&an)[2], int thr, bool early) {
            TR2(0);
            const uint64_t db = make_desc(sbase + st * P2_B, 128, 256);
            wg_fence();
            mma_rs_n192(acc0, a[0], db, thr - 1);
            mma_rs_n192(acc1, a[0], db + 384, thr - 1);
            mma_rs_n192(acc0, a[1], db + 768, 1);
            mma_rs_n192(acc1, a[1], db + 768 + 384, 1);
            wg_commit();
            next_rel(who < thr);
            if (++st == P2_NB) { st = 0; ph ^= 1; }
            wg_wait<1>();
            if (!ok_a) {
                if (who < thr) mbar_arrive_cluster(rel);
                thr = 0;
                mbar_wait(abar, pa >> 31);
            }
            if (who < thr) mbar_arrive_cluster(rel);
            fetch(an, early);
            pos++;
        };
        int n = wg == 2 && head ? -1 : wg;
        mbar_wait(af, 0);
        seek(p2_start(n));
        fetch(a0, n <= 0);
#pragma unroll 1
        for (;; n += 3) {
            TSTAMP(1, 2 + n);
            const int p0 = n < 0 || n == P2_ITEMS ? 12 : 0, pe = n <= 0 ? p0 + P2_FOLD / 2 : 0;
            const bool more = n + 3 < P2_ITEMS + tail;
#pragma unroll 1
            for (int p = p0; p < 24; p++) {
                step(a0, a1, p == p0 ? 1 : 2, p < pe);
                step(a1, a0, 2, p < pe);
            }
            if (n == P2_ITEMS) {
                flag_wait<true>(&g_half[pair][rank], 1);
                TR2(1);
                wg_wait<0>();
                TR2(2);
                release_b();
                uint8_t* o = reinterpret_cast<uint8_t*>(out) + (size_t)((2 * p2_tile(cl, -1) + rank) * 64 + (g & 1) * 32 + w * 8 + (g >> 1)) * P2_XROW + q * 16;
                p2_epilogue_add(acc0, o, up, zero);
                p2_epilogue_add(acc1, o + 384, up, zero);
                TR2(3);
                break;
            }
            mbar_wait(bar_xfull, (n + head) & 1);
            TR2(1);
            wg_wait<0>();
            TR2(2);
            release_b();
            __syncwarp();
            p2_epilogue(acc0, acc1, sx, sbase + P2_OFF_BIAS + q * 32, up, zero);
            TR2(3);
            publish();
            if (!more) break;
            seek(p2_start(n + 3));
            mbar_wait(bar_bfull + st * 8, ph);
        }
        TSTAMP(1, 30);
    }
}

}

extern "C" void kernel_launch(void* const* d_in, const int* in_sizes, int n_in, void* d_out, int out_size) {
    const __nv_bfloat16* x = (const __nv_bfloat16*)d_in[0];
    const __nv_bfloat16* dw = (const __nv_bfloat16*)d_in[1];
    const __nv_bfloat16* w1 = (const __nv_bfloat16*)d_in[2];
    const __nv_bfloat16* w2 = (const __nv_bfloat16*)d_in[3];
    const __nv_bfloat16* grn_g = (const __nv_bfloat16*)d_in[4];
    const __nv_bfloat16* grn_b = (const __nv_bfloat16*)d_in[5];
    __nv_bfloat16* out = (__nv_bfloat16*)d_out;

    cudaFuncSetAttribute(pass1_kernel, cudaFuncAttributeMaxDynamicSharedMemorySize, P1_SMEM);
    cudaFuncSetAttribute(pass2_kernel, cudaFuncAttributeMaxDynamicSharedMemorySize, P2_SMEM);

    typedef CUresult (*EncodeFn)(CUtensorMap*, CUtensorMapDataType, cuuint32_t, void*, const cuuint64_t*, const cuuint64_t*,
                                 const cuuint32_t*, const cuuint32_t*, CUtensorMapInterleave, CUtensorMapSwizzle,
                                 CUtensorMapL2promotion, CUtensorMapFloatOOBfill);
    static EncodeFn encode = nullptr;
    if (!encode) {
        cudaDriverEntryPointQueryResult qres;
        cudaGetDriverEntryPoint("cuTensorMapEncodeTiled", (void**)&encode, cudaEnableDefault, &qres);
    }
    CUtensorMap wmap;
    const cuuint64_t gdim[2] = {HID, C_DIM};
    const cuuint64_t gstr[1] = {HID * 2};
    const cuuint32_t box[2] = {64, 192}, estr[2] = {1, 1};
    CUresult er = encode(&wmap, CU_TENSOR_MAP_DATA_TYPE_BFLOAT16, 2, (void*)w1, gdim, gstr, box, estr, CU_TENSOR_MAP_INTERLEAVE_NONE,
           CU_TENSOR_MAP_SWIZZLE_128B, CU_TENSOR_MAP_L2_PROMOTION_L2_128B, CU_TENSOR_MAP_FLOAT_OOB_FILL_NONE);
    if (er != CUDA_SUCCESS) printf("tensor map encode failed %d\n", (int)er);

    pass1_kernel<<<NUM_CTAS, 512, P1_SMEM>>>(wmap, x, dw, w1, w2, grn_b, 0);

    cudaLaunchAttribute attr[1];
    attr[0].id = cudaLaunchAttributeProgrammaticStreamSerialization;
    attr[0].val.programmaticStreamSerializationAllowed = 1;
    cudaLaunchConfig_t cfg = {};
    cfg.gridDim = dim3(NUM_CTAS);
    cfg.stream = 0;
    cfg.attrs = attr;
    cfg.numAttrs = 1;
    cfg.blockDim = dim3(512);
    cfg.dynamicSmemBytes = P2_SMEM;
    cudaLaunchKernelEx(&cfg, pass2_kernel, x, grn_g, out, 0);
}
```

```cpp
#include <cuda.h>
#include <cuda_runtime.h>
#include <cuda_bf16.h>
#include <stdint.h>
#include <stdio.h>

namespace {

constexpr int M_TOTAL = 384 * 384;
constexpr int C_DIM   = 384;
constexpr int HID     = 1536;
constexpr int NT128   = M_TOTAL / 128;
constexpr int NUM_CTAS = 132;

constexpr int NGRP = 15;
#define LN_DEPTH 2
constexpr int LN_STEP = 2 * NGRP, LN_RING = LN_DEPTH * LN_STEP;
#define P1_M 101
#define P1_D 10
__device__ __forceinline__ int p1_tile(int t, bool small) {
    return t + (small ? ((t + 1) * P1_M + P1_D - 1) / P1_D : t * P1_D / P1_M);
}
constexpr int LN_TILE = 128 * C_DIM * 2;
constexpr int H_TILE = 64 * HID * 3 / 2;
constexpr int H_HALF = 3072, H_STEP = 6144;

__device__ __align__(1024) uint4 g_h[(size_t)M_TOTAL * HID * 3 / 32];
__device__ __align__(1024) uint4 g_ln[LN_RING * LN_TILE / 16];
__device__ __align__(1024) uint4 g_w2img[2][HID * C_DIM * 2 / 16];
__device__ __align__(16) float g_sums[2][HID + 2 * C_DIM];
__device__ __align__(16) unsigned g_ex[HID];
__device__ unsigned g_epoch, g_par;
__device__ __align__(128) unsigned g_img[2];
__device__ __align__(128) unsigned g_prog;
__device__ __align__(128) unsigned g_half[32][2];
__device__ unsigned g_flag[LN_RING + 3][2][8];
#define TSTAMP(k, i)
#define STAMPT(t, i)
#define TRACE(wg, pos, i)
#define TRACEW(pos, i)

#define TR2(i)
#define TR2P(pos, i)
__host__ __device__ __forceinline__ int perm32(int n) {
    return (n & ~31) | (((n >> 1) & 3) << 3) | (((n >> 3) & 3) << 1) | (n & 1);
}

__device__ __forceinline__ uint32_t smem_u32(const void* p) { return (uint32_t)__cvta_generic_to_shared(p); }

__device__ __forceinline__ void mbar_init(uint32_t bar, uint32_t count) {
    asm volatile("mbarrier.init.shared::cta.b64 [%0], %1;\n" ::"r"(bar), "r"(count) : "memory");
}
__device__ __forceinline__ void mbar_expect_tx(uint32_t bar, uint32_t bytes) {
    asm volatile("mbarrier.arrive.expect_tx.shared::cta.b64 _, [%0], %1;\n" ::"r"(bar), "r"(bytes) : "memory");
}
__device__ __forceinline__ void mbar_arrive(uint32_t bar) {
    asm volatile("mbarrier.arrive.shared::cta.b64 _, [%0];\n" ::"r"(bar) : "memory");
}
__device__ __forceinline__ void mbar_arrive_cluster(uint32_t bar_cluster_addr) {
    asm volatile("mbarrier.arrive.shared::cluster.b64 _, [%0];\n" ::"r"(bar_cluster_addr) : "memory");
}
#define SAFE_BREAK
__device__ __forceinline__ void mbar_wait(uint32_t bar, uint32_t parity) {
    asm volatile(
        "{\n"
        ".reg .pred p;\n"
        "LAB_WAIT:\n"
        "mbarrier.try_wait.parity.shared::cta.b64 p, [%0], %1;\n"
        "@!p bra LAB_WAIT;\n"
        "}\n" ::"r"(bar), "r"(parity) : "memory");
}
__device__ __forceinline__ bool mbar_test(uint32_t bar, uint32_t parity) {
    uint32_t ok;
    asm volatile("{\n.reg .pred p;\n"
                 "mbarrier.test_wait.parity.shared::cta.b64 p, [%1], %2;\n"
                 "selp.u32 %0, 1, 0, p;\n}\n" : "=r"(ok) : "r"(bar), "r"(parity) : "memory");
    return ok != 0;
}
__device__ __forceinline__ uint32_t mapa(uint32_t addr, uint32_t rank) {
    uint32_t r;
    asm volatile("mapa.shared::cluster.u32 %0, %1, %2;\n" : "=r"(r) : "r"(addr), "r"(rank));
    return r;
}
__device__ __forceinline__ void bulk_g2s(uint32_t dst, const void* src, uint32_t bytes, uint32_t bar) {
    asm volatile("cp.async.bulk.shared::cluster.global.mbarrier::complete_tx::bytes [%0], [%1], %2, [%3];\n"
                 ::"r"(dst), "l"(src), "r"(bytes), "r"(bar) : "memory");
}
__device__ __forceinline__ void bulk_g2s_mc(uint32_t dst, const void* src, uint32_t bytes, uint32_t bar, uint16_t mask) {
    asm volatile("cp.async.bulk.shared::cluster.global.mbarrier::complete_tx::bytes.multicast::cluster [%0], [%1], %2, [%3], %4;\n"
                 ::"r"(dst), "l"(src), "r"(bytes), "r"(bar), "h"(mask) : "memory");
}
__device__ __forceinline__ void tma2(uint32_t dst, const CUtensorMap* map, int c0, int c1, uint32_t bar) {
    asm volatile("cp.async.bulk.tensor.2d.shared::cluster.global.tile.mbarrier::complete_tx::bytes [%0], [%1, {%2, %3}], [%4];\n"
                 ::"r"(dst), "l"(map), "r"(c0), "r"(c1), "r"(bar) : "memory");
}
template <bool ACQ>
__device__ __forceinline__ uint32_t flag_wait(const unsigned* p, unsigned target) {
    unsigned v, n = 0;
    do {
        if (ACQ) asm volatile("ld.acquire.gpu.global.u32 %0, [%1];\n" : "=r"(v) : "l"(p) : "memory");
        else asm volatile("ld.relaxed.gpu.global.u32 %0, [%1];\n" : "=r"(v) : "l"(p) : "memory");
        n++;
    } while (v < target);
    return n == 1;
}
__device__ __forceinline__ void ldsm4t(uint32_t (&r)[4], uint32_t addr) {
    asm volatile("ldmatrix.sync.aligned.m8n8.x4.trans.shared.b16 {%0,%1,%2,%3}, [%4];\n"
                 : "=r"(r[0]), "=r"(r[1]), "=r"(r[2]), "=r"(r[3]) : "r"(addr) : "memory");
}
__device__ __forceinline__ void bulk_s2g(void* dst, uint32_t src, uint32_t bytes) {
    asm volatile("cp.async.bulk.global.shared::cta.bulk_group [%0], [%1], %2;\n" ::"l"(dst), "r"(src), "r"(bytes) : "memory");
}
__device__ __forceinline__ void cluster_sync_relaxed() {
    asm volatile("barrier.cluster.arrive.relaxed.aligned;\nbarrier.cluster.wait.aligned;\n" ::: "memory");
}
__device__ __forceinline__ void gdc_wait() { asm volatile("griddepcontrol.wait;\n" ::: "memory"); }
__device__ __forceinline__ void gdc_launch() { asm volatile("griddepcontrol.launch_dependents;\n" ::: "memory"); }
__device__ __forceinline__ uint32_t cluster_rank() {
    uint32_t r;
    asm volatile("mov.u32 %0, %%cluster_ctarank;\n" : "=r"(r));
    return r;
}
__device__ __forceinline__ bool elect_one() {
    uint32_t pred;
    asm volatile("{\n.reg .pred p;\nelect.sync _|p, 0xffffffff;\nselp.u32 %0, 1, 0, p;\n}\n" : "=r"(pred));
    return pred != 0;
}
__device__ __forceinline__ void wg_fence() { asm volatile("wgmma.fence.sync.aligned;\n" ::: "memory"); }
__device__ __forceinline__ void wg_commit() { asm volatile("wgmma.commit_group.sync.aligned;\n" ::: "memory"); }
template <int N> __device__ __forceinline__ void wg_wait() {
    asm volatile("wgmma.wait_group.sync.aligned %0;\n" ::"n"(N) : "memory");
}
template <int R> __device__ __forceinline__ void reg_inc() { asm volatile("setmaxnreg.inc.sync.aligned.u32 %0;\n" ::"n"(R)); }
template <int R> __device__ __forceinline__ void reg_dec() { asm volatile("setmaxnreg.dec.sync.aligned.u32 %0;\n" ::"n"(R)); }
__device__ __forceinline__ void bar_sync(int id, int n) { asm volatile("bar.sync %0, %1;\n" ::"r"(id), "r"(n) : "memory"); }
__device__ __forceinline__ void bar_arrive(int id, int n) { asm volatile("bar.arrive %0, %1;\n" ::"r"(id), "r"(n) : "memory"); }

__device__ __forceinline__ uint64_t make_desc(uint32_t saddr, uint32_t lbo, uint32_t sbo) {
    return (uint64_t)((saddr & 0x3FFFF) >> 4) | ((uint64_t)(lbo >> 4) << 16) | ((uint64_t)(sbo >> 4) << 32);
}

__device__ __forceinline__ void stg128_cs(void* p, uint32_t a, uint32_t b, uint32_t c, uint32_t d) {
    asm volatile("st.global.cs.v4.u32 [%0], {%1,%2,%3,%4};\n" ::"l"(p), "r"(a), "r"(b), "r"(c), "r"(d) : "memory");
}
__device__ __forceinline__ uint32_t pack_bf16(float lo, float hi) {
    uint32_t r;
    asm("cvt.rn.bf16x2.f32 %0, %1, %2;\n" : "=r"(r) : "f"(hi), "f"(lo));
    return r;
}
__device__ __forceinline__ float bf_lo(uint32_t v) { return __uint_as_float(v << 16); }
__device__ __forceinline__ float bf_hi(uint32_t v) { return __uint_as_float(v & 0xffff0000u); }
__device__ __forceinline__ uint32_t bf2_mul(uint32_t a, uint32_t b) {
    uint32_t r;
    asm("mul.rn.bf16x2 %0, %1, %2;\n" : "=r"(r) : "r"(a), "r"(b));
    return r;
}
__device__ __forceinline__ uint32_t bf2_fma(uint32_t a, uint32_t b, uint32_t c) {
    uint32_t r;
    asm("fma.rn.bf16x2 %0, %1, %2, %3;\n" : "=r"(r) : "r"(a), "r"(b), "r"(c));
    return r;
}
__device__ __forceinline__ uint32_t bf2_add(uint32_t a, uint32_t b) {
    uint32_t r;
    asm("add.rn.bf16x2 %0, %1, %2;\n" : "=r"(r) : "r"(a), "r"(b));
    return r;
}
constexpr float KAPPA = 0.3292034911525734f;
constexpr float GELU_C = 2.423681954311584f;
constexpr float HSCALE = 1.0f / (2.0f * KAPPA);
__device__ __forceinline__ uint32_t acc_exp(float z) { return max(__float_as_uint(z) >> 23, 10u); }
__device__ __forceinline__ void sched_break(int zero) {
    asm volatile("{\n.reg .pred p;\nsetp.ne.s32 p, %0, 0;\nSB_LOOP:\n@p nanosleep.u32 1;\n@p bra SB_LOOP;\n}\n" ::"r"(zero));
}

#define ACC8(d, o) "+f"(d[o + 0]), "+f"(d[o + 1]), "+f"(d[o + 2]), "+f"(d[o + 3]), "+f"(d[o + 4]), "+f"(d[o + 5]), "+f"(d[o + 6]), "+f"(d[o + 7])

#define ACCR8(d, o) "+r"(d[o + 0]), "+r"(d[o + 1]), "+r"(d[o + 2]), "+r"(d[o + 3]), "+r"(d[o + 4]), "+r"(d[o + 5]), "+r"(d[o + 6]), "+r"(d[o + 7])
__device__ __forceinline__ void mma_rs_n128(uint32_t (&d)[32], const uint32_t (&a)[4], uint64_t desc, int scale_d) {
    asm volatile(
        "{\n.reg .pred p;\nsetp.ne.b32 p, %37, 0;\n"
        "wgmma.mma_async.sync.aligned.m64n128k16.f16.f16.f16 "
        "{%0,%1,%2,%3,%4,%5,%6,%7,%8,%9,%10,%11,%12,%13,%14,%15,"
        "%16,%17,%18,%19,%20,%21,%22,%23,%24,%25,%26,%27,%28,%29,%30,%31},"
        "{%32,%33,%34,%35}, %36, p, 1, 1, 0;\n}\n"
        : ACCR8(d, 0), ACCR8(d, 8), ACCR8(d, 16), ACCR8(d, 24)
        : "r"(a[0]), "r"(a[1]), "r"(a[2]), "r"(a[3]), "l"(desc), "r"(scale_d));
}
__device__ __forceinline__ void mma_ss_n128(uint32_t (&d)[32], uint64_t da, uint64_t db) {
    asm volatile(
        "{\n.reg .pred p;\nsetp.ne.b32 p, %34, 0;\n"
        "wgmma.mma_async.sync.aligned.m64n128k16.f16.f16.f16 "
        "{%0,%1,%2,%3,%4,%5,%6,%7,%8,%9,%10,%11,%12,%13,%14,%15,"
        "%16,%17,%18,%19,%20,%21,%22,%23,%24,%25,%26,%27,%28,%29,%30,%31},"
        "%32, %33, p, 1, 1, 0, 0;\n}\n"
        : ACCR8(d, 0), ACCR8(d, 8), ACCR8(d, 16), ACCR8(d, 24)
        : "l"(da), "l"(db), "r"(1));
}
__device__ __forceinline__ uint32_t bf2_as_h2(uint32_t v) { return (v & 0x0fff0fffu) * 7u + v; }
__device__ __forceinline__ float h_lo(uint32_t v) {
    float r;
    asm("{\n.reg .b16 l, h;\nmov.b32 {l, h}, %1;\ncvt.f32.f16 %0, l;\n}\n" : "=f"(r) : "r"(v));
    return r;
}
__device__ __forceinline__ float h_hi(uint32_t v) {
    float r;
    asm("{\n.reg .b16 l, h;\nmov.b32 {l, h}, %1;\ncvt.f32.f16 %0, h;\n}\n" : "=f"(r) : "r"(v));
    return r;
}

__device__ __forceinline__ void mma_rs_n192(uint32_t (&d)[48], const uint4& a, uint64_t db, int scale_d) {
    asm volatile(
        "{\n.reg .pred p;\nsetp.ne.b32 p, %53, 0;\n"
        "wgmma.mma_async.sync.aligned.m64n192k16.f16.f16.f16 "
        "{%0,%1,%2,%3,%4,%5,%6,%7,%8,%9,%10,%11,%12,%13,%14,%15,"
        "%16,%17,%18,%19,%20,%21,%22,%23,%24,%25,%26,%27,%28,%29,%30,%31,"
        "%32,%33,%34,%35,%36,%37,%38,%39,%40,%41,%42,%43,%44,%45,%46,%47},"
        "{%48,%49,%50,%51}, %52, p, 1, 1, 0;\n}\n"
        : ACCR8(d, 0), ACCR8(d, 8), ACCR8(d, 16), ACCR8(d, 24), ACCR8(d, 32), ACCR8(d, 40)
        : "r"(a.x), "r"(a.y), "r"(a.z), "r"(a.w), "l"(db), "r"(scale_d));
}

__device__ __forceinline__ uint32_t pack_f16(float lo, float hi) {
    uint32_t r;
    asm("cvt.rn.f16x2.f32 %0, %1, %2;\n" : "=r"(r) : "f"(hi), "f"(lo));
    return r;
}

#define P1_IMG 900
constexpr int P1_SLOT = LN_TILE / 2, P1_NST = 4;
constexpr int P1_X = 16 * C_DIM * 2;
constexpr int P1_OFF_X = P1_SLOT * P1_NST;
constexpr int P1_OFF_A = P1_OFF_X + 2 * P1_X;
constexpr int P1_OFF_BAR = P1_OFF_A + 3 * 2048;
constexpr int P1_OFF_TILE = P1_OFF_BAR + (2 * P1_NST + 3 + 2 + 3 + 2) * 8;
constexpr int P1_OFF_DW = P1_OFF_TILE + 64;
constexpr int P1_SMEM = P1_OFF_DW + C_DIM * 2;

__device__ __forceinline__ float rsqrt_fast(float x) {
    float r;
    asm("rsqrt.approx.ftz.f32 %0, %1;\n" : "=f"(r) : "f"(x));
    return r;
}
__device__ __forceinline__ float sum8(const uint32_t (&c)[4]) {
    const uint32_t u = bf2_add(bf2_add(c[0], c[1]), bf2_add(c[2], c[3]));
    return bf_lo(u) + bf_hi(u);
}
__device__ __forceinline__ void lds128(uint32_t (&v)[4], uint32_t a) {
    asm volatile("ld.shared.v4.u32 {%0,%1,%2,%3}, [%4];\n" : "=r"(v[0]), "=r"(v[1]), "=r"(v[2]), "=r"(v[3]) : "r"(a) : "memory");
}
template <class F>
__device__ __forceinline__ void ln_row(uint32_t (&v)[6][4], uint32_t sdw, F after_loads) {
    uint32_t c[4], s[4], d[4], nm;
#pragma unroll
    for (int i = 0; i < 6; i++) {
        lds128(d, sdw + i * 128);
        if (i == 0) {
#pragma unroll
            for (int k = 0; k < 4; k++) c[k] = bf2_mul(v[0][k], d[k]);
            const float p = sum8(c) * -0.125f;
            nm = pack_bf16(p, p);
        }
#pragma unroll
        for (int k = 0; k < 4; k++) {
            v[i][k] = bf2_fma(v[i][k], d[k], nm);
            s[k] = i ? bf2_add(v[i][k], s[k]) : v[i][k];
            c[k] = i ? bf2_fma(v[i][k], v[i][k], c[k]) : bf2_mul(v[i][k], v[i][k]);
        }
    }
    after_loads(c[0]);
    float m = fmaf(sum8(s), 1.0f / 48, -bf_lo(nm));
    float q = fmaf(-bf_lo(nm), fmaf(2.f, m, bf_lo(nm)), sum8(c) * (1.0f / 48));
#pragma unroll
    for (int o = 1; o < 8; o <<= 1) {
        m += __shfl_xor_sync(0xffffffffu, m, o);
        q += __shfl_xor_sync(0xffffffffu, q, o);
    }
    m *= 0.125f;
    const float r = KAPPA * rsqrt_fast(fmaxf(fmaf(-m, m, q * 0.125f), 0.f) + 1e-5f);
    const float e = (-bf_lo(nm) - m) * r * 0x1p-112f;
    const bool two = __any_sync(0xffffffffu, r < 0x1p-14f);
    const float r1 = r * (two ? 0x1p-56f : 0x1p-112f);
    uint32_t mul = pack_bf16(r1, r1), add = two ? 0u : pack_bf16(e, e);
#pragma unroll 1
    for (int it = !two; it < 2; it++) {
#pragma unroll
        for (int i = 0; i < 6; i++)
#pragma unroll
            for (int k = 0; k < 4; k++) v[i][k] = bf2_fma(v[i][k], mul, add);
        mul = 0x23802380u;
        add = pack_bf16(e, e);
    }
#pragma unroll
    for (int i = 0; i < 6; i++)
#pragma unroll
        for (int k = 0; k < 4; k++) v[i][k] = bf2_as_h2(v[i][k]);
}

__device__ __forceinline__ float gelu_s(float y) {
    float u = y * fmaf(y, y, GELU_C);
    float t;
    asm volatile("tanh.approx.f32 %0, %1;\n" : "=f"(t) : "f"(u));
    return fmaf(y, t, y);
}
__device__ __forceinline__ void p1_pack(int c, uint32_t (&p)[4], uint32_t (&dd)[4]) {
#pragma unroll
    for (int u = 0; u < 4; u++) {
        if ((c & 3) == 0) dd[u] = p[u];
        else {
            uint32_t n = dd[u];
            if ((c & 3) == 1) n = __byte_perm(n, 0, 0x2301);
            if ((c & 3) == 2) {
                dd[u] = __byte_perm(n >> 3, n >> 1, 0x6341);
                n = __byte_perm(n >> 3, n >> 1, 0x7250);
            }
            asm("lop3.b32 %0, %0, %1, 0x40074007, 0xd8;\n" : "+r"(p[u]) : "r"(n));
        }
    }
}
__device__ __forceinline__ void p1_store(int c, const uint32_t (&p)[4], uint8_t* hptr) {
    if (c & 3) stg128_cs(hptr + (c >> 2) * H_HALF + ((c & 3) - 1) * 512, p[0], p[1], p[2], p[3]);
}

template <bool GEN>
__device__ __forceinline__ void p1_epilogue(uint32_t (&acc)[32], float (&ssq)[2], uint32_t sc2, uint8_t* hp, int zero) {
    uint32_t sq[2], dd[4];
#pragma unroll
    for (int c = 0; c < 8; c++) {
        if (GEN) sched_break(zero);
        uint32_t p[4];
#pragma unroll
        for (int u = 0; u < 4; u++) {
            const uint32_t y = acc[8 * (c >> 1) + 2 * u + (c & 1)];
            if (GEN) {
                const float sc = c & 1 ? bf_hi(sc2) : bf_lo(sc2), fs = __uint_as_float(0x78000000u - __float_as_uint(sc));
                const float g0 = gelu_s(h_lo(y) * fs), g1 = gelu_s(h_hi(y) * fs);
                ssq[c & 1] = fmaf(g1, g1, fmaf(g0, g0, ssq[c & 1]));
                p[u] = pack_f16(g0 * sc, g1 * sc);
            } else {
                uint32_t g;
                asm("{\n.reg .b32 w;\n"
                    "fma.rn.f16x2 w, %1, %1, %2;\n"
                    "mul.rn.f16x2 w, w, %1;\n"
                    "tanh.approx.f16x2 w, w;\n"
                    "fma.rn.f16x2 %0, %1, w, %1;\n}\n" : "=r"(g) : "r"(y), "r"(0x40d940d9u));
                acc[8 * (c >> 1) + 2 * u + (c & 1)] = g;
                if (c < 2 && u == 0) asm("mul.rn.f16x2 %0, %1, %1;\n" : "=r"(sq[c & 1]) : "r"(g));
                else asm("fma.rn.f16x2 %0, %1, %1, %0;\n" : "+r"(sq[c & 1]) : "r"(g));
                if (c & 1) asm("{\n.reg .b16 l, h;\n.reg .b32 f;\nmov.b32 {l, h}, %2;\nmov.b32 f, {h, h};\nmul.rn.f16x2 %0, %1, f;\n}\n" : "=r"(p[u]) : "r"(g), "r"(sc2));
                else asm("{\n.reg .b16 l, h;\n.reg .b32 f;\nmov.b32 {l, h}, %2;\nmov.b32 f, {l, l};\nmul.rn.f16x2 %0, %1, f;\n}\n" : "=r"(p[u]) : "r"(g), "r"(sc2));
            }
        }
        p1_pack(c, p, dd);
        if (c & 3) {
#pragma unroll
            for (int u = 0; u < 4; u++) acc[4 * (c - 1 - (c >> 2)) + u] = p[u];
        }
        p1_store(c, p, hp);
    }
    if (!GEN) {
#pragma unroll
        for (int r = 0; r < 2; r++) ssq[r] += h_lo(sq[r]) + h_hi(sq[r]);
    }
}
__device__ __forceinline__ void p1_consumer(const uint32_t (&a)[24][4], uint32_t sc2, bool gen, uint32_t sbase, int wg, int nwg, int cb,
                                            int w, int lane, int zero) {
    const uint32_t bar_full = sbase + P1_OFF_BAR, bar_empty = bar_full + P1_NST * 8;
    const uint32_t empty_remote = mapa(bar_empty, lane & 1);
    const int g = lane >> 2, q = lane & 3, turn = wg + 1 == nwg ? 1 : wg + 2;
    float ssq[2] = {0.f, 0.f};
    uint32_t acc[32] = {};
    TSTAMP(0, 1);
    STAMPT(128, 4);
    STAMPT(256, 5);

    uint8_t* hp = reinterpret_cast<uint8_t*>(g_h) + ((cb * 2 + (w >> 1)) * H_STEP + (w & 1) * 1536) + g * 64 + (q ^ (g >> 1)) * 16;
    const uint64_t desc_base = make_desc(sbase, 16, 1024) | (1ull << 62);
    const uint64_t da = make_desc(sbase + P1_OFF_A + wg * 2048, 128, 256);
#pragma unroll 1
    for (int i = 0;; i++) {
        const int s0 = (i & 1) * 16, par = (i >> 1) & 1;
        const uint64_t d0 = desc_base + (uint64_t)((i & 1) * (LN_TILE / 16));
        TRACE(wg, i, 0);
        mbar_wait(bar_full + s0, par);
        bar_sync(1 + wg, 256);
        TRACE(wg, i, 1);
        uint32_t step, more;
        wg_fence();
#pragma unroll
        for (int k = 0; k < 24; k++) {
            if (k == 12) mbar_wait(bar_full + s0 + 8, par);
            const uint64_t db = d0 + (uint64_t)((k >> 2) * 1024 + (k & 3) * 2);
            if (k < 23) mma_rs_n128(acc, a[k], db, k ? 1 : zero);
            else mma_ss_n128(acc, da, db);
            if (k == 23) bar_arrive(turn, 256);
            if (k % 12 == 11) wg_commit();
        }
        asm volatile("ld.shared.v2.u32 {%0, %1}, [%2];\n" : "=r"(step), "=r"(more) : "r"(sbase + P1_OFF_TILE + (i & 3) * 16) : "memory");
        TRACE(wg, i, 2);
        wg_wait<1>();
        if (lane < 2) mbar_arrive_cluster(empty_remote + s0);
        hp += step;
        TRACE(wg, i, 3);
        wg_wait<0>();
        TRACE(wg, i, 4);
        if (lane < 2) mbar_arrive_cluster(empty_remote + s0 + 8);
        if (gen) p1_epilogue<true>(acc, ssq, sc2, hp, zero);
        else p1_epilogue<false>(acc, ssq, sc2, hp, zero);
        if (!more) break;
    }
    TSTAMP(0, 21);
    if (wg == 0) bar_sync(1, 256);
    uint32_t par;
    asm volatile("ld.shared.u32 %0, [%1];\n" : "=r"(par) : "r"(sbase + P1_OFF_TILE - 4) : "memory");
    float* sums = g_sums[par];
#pragma unroll
    for (int r = 0; r < 2; r++) {
        ssq[r] += __shfl_xor_sync(0xffffffffu, ssq[r], 1);
        ssq[r] += __shfl_xor_sync(0xffffffffu, ssq[r], 2);
        if (q == 0) atomicAdd(sums + cb * 64 + w * 16 + r * 8 + g, ssq[r]);
    }
}

__device__ __forceinline__ void p1_w2(const __nv_bfloat16* __restrict__ w2, const __nv_bfloat16* __restrict__ grn_b, int w, int lane) {
    const int gw = (blockIdx.x - 8 * NGRP) * 4 + w;
    float* sums = g_sums[__ldcg(&g_epoch) & 1] + HID;
    flag_wait<true>(&g_flag[40][1][0], 12);
    {
        const int col = gw % 6 * 64 + lane * 2;
        float bsum[2] = {0.f, 0.f}, asum[2] = {0.f, 0.f};
#pragma unroll 4
        for (int kk = 0; kk < 192; kk++) {
            const int k = gw / 6 * 192 + kk;
            const uint32_t v = *reinterpret_cast<const uint32_t*>(w2 + k * C_DIM + col);
            const float b = __bfloat162float(grn_b[k]), f = __uint_as_float(__ldcg(&g_ex[k]) << 23);
            bsum[0] = fmaf(b, bf_lo(v), bsum[0]);
            bsum[1] = fmaf(b, bf_hi(v), bsum[1]);
            asum[0] = fmaf(f, fabsf(bf_lo(v)), asum[0]);
            asum[1] = fmaf(f, fabsf(bf_hi(v)), asum[1]);
        }
#pragma unroll
        for (int j = 0; j < 2; j++) {
            atomicAdd(sums + col + j, bsum[j]);
            atomicAdd(sums + C_DIM + col + j, asum[j]);
        }
        __threadfence();
        __syncwarp();
        if (lane == 0) asm volatile("red.relaxed.gpu.global.add.u32 [%0], 1;\n" ::"l"(&g_flag[LN_RING + 2][0][0]) : "memory");
    }
    while (*(volatile unsigned*)&g_flag[P1_IMG % LN_RING][1][0] < 12 * (P1_IMG / LN_RING + 1)) {
        __nanosleep(2000);
        SAFE_BREAK
    }
    flag_wait<true>(&g_flag[LN_RING + 2][0][0], 48);
    float z = 0.f;
#pragma unroll
    for (int j = 0; j < C_DIM / 32; j++) z = fmaxf(z, __ldcg(sums + C_DIM + j * 32 + lane));
    const float sc = __uint_as_float((263u - acc_exp(__uint_as_float(__reduce_max_sync(0xffffffffu, __float_as_uint(z))))) << 23);
    const int np = gw % 6 * 64 + lane * 2;
#pragma unroll 2
    for (int cc = 0; cc < 24; cc++) {
        const int c = gw / 6 * 24 + cc;
        uint32_t v[8], o[2][4];
#pragma unroll
        for (int e = 0; e < 8; e++) v[e] = *reinterpret_cast<const uint32_t*>(w2 + (c * 8 + e) * C_DIM + perm32(np));
#pragma unroll
        for (int e = 0; e < 4; e++) {
            const uint2 t = __ldcg(reinterpret_cast<const uint2*>(g_ex) + c * 4 + e);
            const float f0 = __uint_as_float(t.x << 23), f1 = __uint_as_float(t.y << 23);
            o[0][e] = pack_f16(bf_lo(v[2 * e]) * f0 * sc, bf_lo(v[2 * e + 1]) * f1 * sc);
            o[1][e] = pack_f16(bf_hi(v[2 * e]) * f0 * sc, bf_hi(v[2 * e + 1]) * f1 * sc);
        }
#pragma unroll
        for (int j = 0; j < 2; j++)
            g_w2img[0][(((c >> 1) * 48 + (np >> 3)) * 2 + (c & 1)) * 8 + (np & 7) + j] = make_uint4(o[j][0], o[j][1], o[j][2], o[j][3]);
    }
    asm volatile("fence.proxy.async.global;\n" ::: "memory");
    __threadfence();
    __syncwarp();
    if (lane == 0) asm volatile("red.relaxed.gpu.global.add.u32 [%0], 1;\n" ::"l"(&g_img[0]) : "memory");
}

__global__ void __cluster_dims__(2, 1, 1) __launch_bounds__(512, 1)
pass1_kernel(const __grid_constant__ CUtensorMap wmap, const __nv_bfloat16* __restrict__ x, const __nv_bfloat16* __restrict__ dw,
             const __nv_bfloat16* __restrict__ w1, const __nv_bfloat16* __restrict__ w2, const __nv_bfloat16* __restrict__ grn_b, int zero) {
    extern __shared__ __align__(1024) uint8_t smem[];
    const uint32_t sbase = smem_u32(smem);
    const uint32_t bar_full = sbase + P1_OFF_BAR, bar_empty = bar_full + P1_NST * 8, bar_w = bar_empty + P1_NST * 8;
    const uint32_t bar_xfull = bar_w + 24, bar_raw = bar_xfull + 16, bar_done = bar_raw + 16;
    const int tid = threadIdx.x;
    const int warp = __shfl_sync(0xffffffffu, tid >> 5, 0), lane = tid & 31;
    const uint32_t rank = cluster_rank();
    const int cl = blockIdx.x >> 1;
    const bool small = cl >= 4 * NGRP;
    const int nwg = small ? 2 : 3, cb0 = small ? (blockIdx.x - 8 * NGRP) * 2 : (blockIdx.x & 7) * 3;
    uint8_t* const ring = reinterpret_cast<uint8_t*>(g_ln);

    TSTAMP(0, 0);
    TRACEW(110 + warp, 0);

    if (warp >= 12) {
        reg_dec<56>();
        asm volatile("barrier.cluster.arrive.relaxed.aligned;\n" ::: "memory");
        asm volatile("barrier.cluster.wait.aligned;\n" ::: "memory");
        {
            auto ring_row = [&](int p) {
                const int n = (p & 8) * 8 + (lane >> 3) * 8 + (p & 3) * 2 + (p >> 2 & 1);
                return n * 128 + (((lane ^ n) & 7) << 4);
            };
            const uint8_t* xsrc = reinterpret_cast<const uint8_t*>(x) + (size_t)(LN_STEP * 8 + blockIdx.x * 2 + (warp & 1)) * P1_X;
            const uint32_t xbar = bar_xfull + (warp & 1) * 8, xdst = sbase + P1_OFF_X + (warp & 1) * P1_X;
            const uint32_t sdw = sbase + P1_OFF_DW + (lane & 7) * 16;
            uint32_t src = xdst - P1_OFF_X + (lane >> 3) * (C_DIM * 2) + (lane & 7) * 16;
            int row0 = ring_row((blockIdx.x & 7) * 2 + (warp & 1)) ^ 288, slot = blockIdx.x >> 3, used = 0;
            auto next = [&]() {
                xsrc += (size_t)LN_STEP * 8 * P1_X;
                if (elect_one()) {
                    mbar_expect_tx(xbar, P1_X);
                    bulk_g2s(xdst, xsrc, P1_X, xbar);
                }
                __syncwarp();
            };
#pragma unroll 1
            for (int i = -1; i * LN_STEP + (int)(blockIdx.x >> 2) < NT128 && blockIdx.x < 128; i++) {
                if (warp == 14) TRACEW(128 + i, 0);
                const int last = i > 0 ? 3 : i ? 2 + (warp >> 1 & 1) : blockIdx.x < 112 ? 1 : -1;
#pragma unroll 1
                for (int ps = i < 0 ? last - 4 : 0; ps <= last; ps += i < 0 ? 4 : 1) {
                    if (i < 0 && ps > 0) STAMPT(416, 6);
                    if (i < 0 && ps > 0) mbar_wait(bar_raw, 0);
                    if (i < 0 && ps > 0) STAMPT(416, 7);
                    if (ps == 0) {
                        if (used) flag_wait<false>(&g_flag[slot][1][0], used);
                        if (i) mbar_wait(xbar, ~i & 1);
                        else mbar_wait(bar_raw + 8, 0);
                        if (warp == 14) TRACEW(128 + i, 1);
                    }
                    uint32_t v[6][4];
#pragma unroll
                    for (int j = 0; j < 6; j++) lds128(v[j], src + (ps & 3) * (4 * C_DIM * 2) + j * 128);
                    ln_row(v, sdw, [&](uint32_t dep) {
                        if (i == 0 && ps == 1 && lane < 2) mbar_arrive_cluster(mapa(bar_empty, lane) + (dep & zero));
                        if (ps == 3 && i > 0 && (i + 1) * LN_STEP + (blockIdx.x >> 2) < NT128 && !__any_sync(0xffffffffu, dep & zero)) next();
                    });
                    uint8_t* dst = ring + (slot * LN_TILE + (ps & 1) * 4096 + (row0 ^ (ps & 2) * 144));
#pragma unroll
                    for (int j = 0; j < 6; j++)
                        asm volatile("{\n.reg .pred p;\nsetp.ge.s32 p, %5, 0;\n@p st.global.v4.u32 [%0], {%1,%2,%3,%4};\n}\n"
                                     ::"l"(dst + j * 16384), "r"(v[j][0]), "r"(v[j][1]), "r"(v[j][2]), "r"(v[j][3]), "r"(ps) : "memory");
                }
                if (warp == 14) TRACEW(128 + i, 2);
                asm volatile("fence.proxy.async.global;\nfence.acq_rel.cta;\n" ::: "memory");
                if (i < 0) {
                    bar_sync(4, 128);
                    if (warp < 14 || small) break;
                    if (blockIdx.x >= 112 && lane < 2) mbar_arrive_cluster(mapa(bar_empty, lane));
                    row0 ^= 288;
                    slot += 16;
                } else {
                    if (i) mbar_wait(bar_done, ~i & 1);
                    else {
                        src += P1_OFF_X;
                        slot = blockIdx.x >> 2;
                        row0 = ring_row((blockIdx.x & 3) * 4 + (warp & 1) * 2);
                    }
                    __syncwarp();
                    if (lane == 0) mbar_arrive(bar_done);
                    if ((slot += LN_STEP) >= LN_RING) { slot -= LN_RING; used += 12; }
                }
            }
            if ((warp < 14 || small) && lane < 2) mbar_arrive_cluster(mapa(bar_empty, lane));
        }
        if (warp == 12) {
            int prev = 0, t = p1_tile(small ? 0 : cl >> 2, small), next = p1_tile(small ? 1 : (cl >> 2) + NGRP, small);
            const uint32_t rbase = mapa(sbase, lane & 1);
            int i = 0;
#pragma unroll 1
            for (; t < NT128; i++) {
                const int s0 = (i & 1) * 2, par = (i >> 1) & 1;
                const int round = t / LN_RING, slot = t - round * LN_RING;
                const uint8_t* src = ring + slot * LN_TILE + rank * (P1_SLOT / 2);
                int draw = i + 2;
                if (rank == 0 && lane == 0 && !small) draw = 2 * NGRP + atomicAdd(&g_flag[LN_RING + ((cl >> 1) & 1)][cl & 1][0], 1u);
                flag_wait<true>(&g_flag[slot][0][0], 8 * round + 8);
                TRACEW(i, 2);
                if (i == 0) STAMPT(384, 10);
                if (i == 2) STAMPT(384, 13);
                if (i == 3) STAMPT(384, 14);
                asm volatile("fence.proxy.async.global;\n" ::: "memory");
                draw = p1_tile(__shfl_sync(0xffffffffu, draw, 0), small);
#pragma unroll
                for (int h = 0; h < 2; h++) {
                    mbar_wait(bar_empty + (s0 + h) * 8, par);
                    TRACEW(i, 4 + h);
                    if (i == 0 && h == 1) STAMPT(384, 11);
                    if (elect_one()) {
                        mbar_expect_tx(bar_full + (s0 + h) * 8, P1_SLOT + 16 - 16 * h);
                        bulk_g2s_mc(sbase + (s0 + h) * P1_SLOT + rank * (P1_SLOT / 2), src + h * P1_SLOT, P1_SLOT / 2, bar_full + (s0 + h) * 8, (uint16_t)3);
                    }
                    __syncwarp();
                    if (h == 0 && rank == 0 && lane < 2)
                        asm volatile("st.async.shared::cluster.mbarrier::complete_tx::bytes.v4.u32 [%0], {%1, %2, %3, %3}, [%4];\n"
                                     ::"r"(rbase + P1_OFF_TILE + (i & 3) * 16), "r"((t - prev) * (2 * H_TILE)), "r"((int)(next < NT128)), "r"(draw),
                                       "r"(rbase + P1_OFF_BAR + s0 * 8) : "memory");
                }
                prev = t;
                t = next;
                next = draw;
                if (rank != 0) {
                    mbar_wait(bar_full + s0 * 8, (i >> 1) & 1);
                    mbar_wait(bar_full + s0 * 8 + 8, (i >> 1) & 1);
                    if (lane == 0) asm volatile("red.relaxed.gpu.global.add.u32 [%0], %1;\n" ::"l"(&g_flag[slot][1][0]), "r"(nwg) : "memory");
                    asm volatile("ld.shared.u32 %0, [%1];\n" : "=r"(next) : "r"(sbase + P1_OFF_TILE + (i & 3) * 16 + 8) : "memory");
                    TRACEW(i, 3);
                }
            }
#pragma unroll 1
            for (int j = 2 * i; j < 2 * i + 4; j++) mbar_wait(bar_empty + (j & 3) * 8, (j >> 2) & 1);
        } else if (warp == 13) {
            STAMPT(416, 8);
            if (lane == 0 && blockIdx.x < 128) asm volatile("red.release.gpu.global.add.u32 [%0], 1;\n" ::"l"(&g_flag[blockIdx.x >> 3][0][0]) : "memory");
            __syncwarp();
            STAMPT(416, 9);
            const uint32_t ep = g_epoch & 1;
            asm volatile("st.shared.u32 [%0], %1;\n" ::"r"(sbase + P1_OFF_TILE - 4), "r"(ep) : "memory");
            if (blockIdx.x == 18) g_par = ep;
            if (blockIdx.x < 18) reinterpret_cast<float4*>(g_sums[ep ^ 1])[blockIdx.x * 32 + lane] = make_float4(0.f, 0.f, 0.f, 0.f);
#pragma unroll 1
            for (int i = 0; !small && i * LN_STEP + (blockIdx.x >> 2) < NT128; i++) {
                mbar_wait(bar_done, i & 1);
                asm volatile("fence.proxy.async.global;\n" ::: "memory");
                if (lane == 0) {
                    mbar_arrive(bar_done);
                    asm volatile("red.release.gpu.global.add.u32 [%0], %1;\n"
                                 ::"l"(&g_flag[i ? (blockIdx.x >> 2) + i % LN_DEPTH * LN_STEP : 16 + (blockIdx.x >> 3)][0][0]), "r"(i ? 2 : (int)(blockIdx.x < 112)) : "memory");
                }
                __syncwarp();
                TRACEW(128 + i, 3);
            }
            flag_wait<true>(&g_flag[LN_RING + 2][0][0], 48);
        }
    } else {
        if (tid == 0) {
            mbar_init(bar_raw, 1);
            mbar_init(bar_raw + 8, 1);
            mbar_init(bar_xfull, 1);
            mbar_init(bar_xfull + 8, 1);
            for (int i = 0; i < 3; i++) mbar_init(bar_w + i * 8, 1);
            asm volatile("fence.mbarrier_init.release.cluster;\n" ::: "memory");
            if (blockIdx.x < 128) {
                mbar_expect_tx(bar_raw, P1_X + C_DIM * 2);
                bulk_g2s(sbase + P1_OFF_DW, dw, C_DIM * 2, bar_raw);
                for (int i = 0; i < 2; i++) bulk_g2s(sbase + i * P1_X + P1_X / 2, x + (size_t)(blockIdx.x * 16 + i * 8) * C_DIM, P1_X / 2, bar_raw);
                asm volatile("cp.async.bulk.prefetch.L2.global [%0], 9216;\n" ::"l"(w1 + blockIdx.x * 4608) : "memory");
            }
            if (blockIdx.x < 112) {
                mbar_expect_tx(bar_raw + 8, P1_X);
                for (int i = 0; i < 2; i++) bulk_g2s(sbase + i * P1_X, x + (size_t)(16 * 128 + blockIdx.x * 16 + i * 8) * C_DIM, P1_X / 2, bar_raw + 8);
            }
            for (int i = 0; i < nwg; i++) {
                mbar_expect_tx(bar_w + i * 8, P1_SLOT);
                tma2(sbase + (1 + i) * P1_SLOT, &wmap, (cb0 + i) * 64, 0, bar_w + i * 8);
                tma2(sbase + (1 + i) * P1_SLOT + P1_SLOT / 2, &wmap, (cb0 + i) * 64, 192, bar_w + i * 8);
            }
            for (int i = 0; i < 2 && !small; i++) {
                mbar_expect_tx(bar_xfull + i * 8, P1_X);
                bulk_g2s(sbase + P1_OFF_X + i * P1_X, x + (size_t)(LN_STEP * 128 + blockIdx.x * 32 + i * 16) * C_DIM, P1_X, bar_xfull + i * 8);
            }
        }
        if (tid == 32) {
            mbar_init(bar_done, 3);
            mbar_arrive(bar_done);
            asm volatile("fence.mbarrier_init.release.cluster;\n" ::: "memory");
        }
        if (tid == 64) {
            for (int i = 0; i < P1_NST; i++) {
                mbar_init(bar_full + i * 8, 1);
                mbar_init(bar_empty + i * 8, 8 * nwg);
            }
            asm volatile("fence.mbarrier_init.release.cluster;\n" ::: "memory");
            if (blockIdx.x < 64) (&g_half[0][0])[blockIdx.x] = 0;
            else if (blockIdx.x == 64) g_prog = 0;
            else if (blockIdx.x < 67) g_img[blockIdx.x - 65] = 0;
        }
        __syncwarp();
        asm volatile("barrier.cluster.arrive.relaxed.aligned;\n" ::: "memory");
        reg_inc<152>();
        TRACEW(110 + warp, 1);
        const int wg = warp >> 2, w = warp & 3;
        gdc_launch();
        asm volatile("barrier.cluster.wait.aligned;\n" ::: "memory");
        if (wg == nwg) {
            p1_w2(w2, grn_b, w, lane);
            return;
        }
        const uint32_t slot_free = mapa(bar_empty, lane & 1) + (lane >> 1) * 8;
        if (lane < 8 && (lane >> 1) != 1 + wg && (wg || lane > 1)) mbar_arrive_cluster(slot_free);
        if (wg == 1) bar_arrive(1, 256);
        uint32_t a[24][4], ex[2], gen = 0;
        const uint32_t wsrc = sbase + (1 + wg) * P1_SLOT + ((lane >> 4) * 8 + (lane & 7)) * 128 + (((2 * w + ((lane >> 3) & 1)) ^ (lane & 7)) << 4);
#pragma unroll 1
        for (int it = 0; it < 2; it++) {
            if (it) mbar_wait(bar_w + wg * 8, 0);
            TRACEW(110 + warp, 5);
            if (it || wg == 0) {
#pragma unroll
            for (int k = 0; k < 24; k++) ldsm4t(a[k], wsrc + k * 2048);
#pragma unroll
            for (int r = 0; r < 2; r++) {
                float t = 0.f;
#pragma unroll
                for (int j = 0; j < 6; j++) {
                    uint32_t c = bf2_mul(a[4 * j][r], a[4 * j][r]);
#pragma unroll
                    for (int k = 1; k < 8; k++) c = bf2_fma(a[4 * j + k / 2][r + (k & 1) * 2], a[4 * j + k / 2][r + (k & 1) * 2], c);
                    t += bf_lo(c) + bf_hi(c);
                }
                t += __shfl_xor_sync(0xffffffffu, t, 1);
                t += __shfl_xor_sync(0xffffffffu, t, 2);
                asm("sqrt.approx.f32 %0, %0;\n" : "+f"(t));
                ex[r] = min(max(__float_as_uint(13.9f * t) >> 23, 72u), 198u);
            }
            asm volatile("{\n.reg .pred p;\nsetp.gt.u32 p, %1, 7;\nbar.red.or.pred p, %2, 128, p;\nselp.u32 %0, 1, 0, p;\n}\n"
                         : "=r"(gen) : "r"(max(ex[0] - 125u, ex[1] - 125u)), "r"(5 + wg) : "memory");
            gen = __shfl_sync(0xffffffffu, gen, 0) & it;
            if (it) {
                if ((lane & 3) < 2) g_ex[(cb0 + wg) * 64 + w * 16 + (lane & 1) * 8 + (lane >> 2)] = lane & 1 ? ex[1] : ex[0];
                if ((lane >> 1) == 1 + wg) mbar_arrive_cluster(slot_free);
                __syncwarp();
            }
            }
            if (gen) {
#pragma unroll
                for (int k = 0; k < 24; k++)
#pragma unroll
                    for (int j = 0; j < 4; j++) a[k][j] = bf2_mul(a[k][j], (268u - ex[j & 1]) * 0x00800080u);
            }
            if (it || wg == 1) {
#pragma unroll
                for (int k = 0; k < 24; k++)
#pragma unroll
                    for (int j = 0; j < 4; j++) {
                        a[k][j] = bf2_as_h2(bf2_mul(a[k][j], 0x07800780u));
                        asm volatile("" : "+r"(a[k][j]));
                    }
            }
            TRACEW(110 + warp, 6);
        }
#pragma unroll
        for (int j = 0; j < 4; j++)
            asm volatile("st.shared.u32 [%0], %1;\n" ::"r"(sbase + P1_OFF_A + warp * 512 + (j & 1) * 256 + (j >> 1) * 128 + lane * 4), "r"(a[23][j]) : "memory");
        asm volatile("fence.proxy.async.shared::cta;\n" ::: "memory");
        TRACEW(110 + warp, 7);
        const uint32_t ex2 = ex[0] | ex[1] << 16;
        p1_consumer(a, gen ? 0x7f007f00u - (ex2 << 7) : (0x008e008eu - ex2) << 10, gen, sbase, wg, nwg, cb0 + wg, w, lane, zero);
        TSTAMP(0, 30);
    }
}

#define P2_NB_ 5
#define P2_NA_ 5
#define P2_DELTA_ 7
#define P2_EXTRA 0
#define P2_HSLEEP 64
#define P2_PSLEEP 100
#define P2_T0 5
#define P2_TS 11
constexpr int P2_B = 24576, P2_NB = P2_NB_;
constexpr int P2_A = 3072, P2_NA = P2_NA_;
constexpr int P2_XROW = C_DIM * 2;
constexpr int P2_OFF_A = P2_B * P2_NB;
constexpr int P2_OFF_X = P2_OFF_A + 3 * P2_NA * P2_A;
constexpr int P2_XHALF = 32 * P2_XROW + 64;
constexpr int P2_OFF_BIAS = P2_OFF_X + 64 * P2_XROW + 64;
constexpr int P2_OFF_GRN = P2_OFF_BIAS + C_DIM * 4;
constexpr int P2_OFF_BAR = P2_OFF_GRN + HID * 2;
constexpr int P2_SMEM = P2_OFF_BAR + (2 * P2_NB + 6 * P2_NA + 3) * 8;
#define P2_LAG_ 17
constexpr int P2_LAG = P2_LAG_;
constexpr int P2_NCL = NUM_CTAS / 2, P2_ITEMS = NT128 / P2_NCL, P2_SHARED = NT128 - P2_ITEMS * P2_NCL;
constexpr int P2_POS = P2_LAG * (P2_ITEMS - 1) + 48;
__device__ __forceinline__ int p2_start(int n) { return n < 0 ? 0 : n == P2_ITEMS ? P2_POS - 24 : P2_LAG * n; }
constexpr int P2_FOLD = P2_LAG - 1 + (P2_LAG & 1);
constexpr int P2_XC = 8 * P2_XROW;
constexpr int P2_DELTA = P2_DELTA_;
__device__ __forceinline__ int p2_tile(int cl, int n) {
    return n == 0 ? NT128 - 1 - cl : n < 0 || n == P2_ITEMS ? NT128 - 1 - P2_NCL - (cl >> 1) : cl + P2_NCL * (n - 1);
}

constexpr int P2_EG = 2;
__device__ __forceinline__ void p2_epilogue(const uint32_t (&acc0)[48], const uint32_t (&acc1)[48], uint32_t sx, uint32_t sb, float up, int zero) {
    uint32_t v[2][P2_EG][4];
    float b[2][8];
    auto load = [&](int c, uint32_t a) {
#pragma unroll
        for (int j = 0; j < 2; j++)
            asm volatile("ld.shared.v4.f32 {%0,%1,%2,%3}, [%4];\n" : "=f"(b[c & 1][4 * j]), "=f"(b[c & 1][4 * j + 1]), "=f"(b[c & 1][4 * j + 2]), "=f"(b[c & 1][4 * j + 3])
                         : "r"(sb + c * 128 + j * 16) : "memory");
#pragma unroll
        for (int j = 0; j < P2_EG; j++) {
            const int u = c * P2_EG + j;
            asm volatile("ld.shared.v4.u32 {%0,%1,%2,%3}, [%4];\n" : "=r"(v[c & 1][j][0]), "=r"(v[c & 1][j][1]), "=r"(v[c & 1][j][2]), "=r"(v[c & 1][j][3])
                         : "r"(a + (u >> 1) * 64 + (u & 1) * 4 * P2_XROW) : "memory");
        }
    };
    load(0, sx);
#pragma unroll
    for (int c = 0; c < 24 / P2_EG; c++) {
        if (c + 1 < 24 / P2_EG) load(c + 1, sx + (v[c & 1][P2_EG - 1][0] & zero));
#pragma unroll
        for (int j = 0; j < P2_EG; j++) {
            const int u = c * P2_EG + j, i = 8 * ((u >> 1) % 6) + (u & 1);
            const uint32_t (&acc)[48] = u < 12 ? acc0 : acc1;
            uint32_t (&w)[4] = v[c & 1][j];
#pragma unroll
            for (int e = 0; e < 4; e++)
                w[e] = bf2_add(pack_bf16(fmaf(h_lo(acc[i + 2 * e]), up, b[c & 1][2 * e]), fmaf(h_hi(acc[i + 2 * e]), up, b[c & 1][2 * e + 1])), w[e]);
            asm volatile("st.shared.v4.u32 [%4], {%0,%1,%2,%3};\n" ::"r"(w[0]), "r"(w[1]), "r"(w[2]), "r"(w[3]),
                         "r"(sx + (u >> 1) * 64 + (u & 1) * 4 * P2_XROW) : "memory");
        }
    }
}

__device__ __forceinline__ void p2_unpack(uint4& u, uint32_t o1, uint32_t o2, uint32_t o3) {
    u.z = o1 & 0xbff8bff8u;
    u.y = o2 & 0xbff8bff8u;
    u.w = o3 & 0xbff8bff8u;
    u.x = (__byte_perm(o1, 0, 0x2301) & 0x07400740u) | ((__byte_perm(o2, o3, 0x6240) << 3) & 0x38383838u) | ((__byte_perm(o2, o3, 0x3715) << 1) & 0x80808080u);
}
__device__ __forceinline__ uint32_t h2_mul(uint32_t a, uint32_t b) {
    uint32_t r;
    asm("mul.rn.f16x2 %0, %1, %2;\n" : "=r"(r) : "r"(a), "r"(b));
    return r;
}
__device__ __forceinline__ void p2_epilogue_add(const uint32_t (&acc)[48], uint8_t* o, float f, int zero) {
#pragma unroll
    for (int t = 0; t < 12; t++) {
        uint32_t v[4];
#pragma unroll
        for (int e = 0; e < 4; e++) {
            v[e] = acc[8 * (t >> 1) + (t & 1) + 2 * e];
            asm volatile("" : "+r"(v[e]));
            v[e] = pack_bf16(h_lo(v[e]) * f, h_hi(v[e]) * f);
        }
        asm volatile("red.global.add.noftz.v4.bf16x2 [%0], {%1,%2,%3,%4};\n" ::"l"(o + (t >> 1) * 64 + (t & 1) * 4 * P2_XROW),
                     "r"(v[0]), "r"(v[1]), "r"(v[2]), "r"(v[3]) : "memory");
        if (t % 3 == 2) sched_break(zero);
    }
}

__global__ void __cluster_dims__(2, 1, 1) __launch_bounds__(512, 1)
pass2_kernel(const __nv_bfloat16* __restrict__ x, const __nv_bfloat16* __restrict__ grn_g, __nv_bfloat16* __restrict__ out, int zero) {
    extern __shared__ __align__(1024) uint8_t smem[];
    const uint32_t sbase = smem_u32(smem);
    const uint32_t bar_bfull = sbase + P2_OFF_BAR, bar_bempty = bar_bfull + P2_NB * 8;
    const uint32_t bar_afull = bar_bempty + P2_NB * 8, bar_aempty = bar_afull + 3 * P2_NA * 8;
    const uint32_t bar_xfull = bar_aempty + 3 * P2_NA * 8, bar_oready = bar_xfull + 8, s_pos = bar_xfull + 16;
    int tid;
    asm volatile("mov.u32 %0, %%tid.x;\n" : "=r"(tid));
    const int warp = __shfl_sync(0xffffffffu, tid >> 5, 0), lane = tid & 31;
    const uint32_t rank = cluster_rank();
    const int cl = blockIdx.x >> 1, pair = cl >> 1;
    const int k0 = (4 * pair + (cl & 1) * (48 - P2_POS % 48)) % 48;
    const int head = pair < P2_SHARED && !(cl & 1), tail = pair < P2_SHARED && (cl & 1);

    uint32_t par, gg[4];
    float pre[4];
    if (warp < 12) {
        asm volatile("ld.global.cg.u32 %0, [%1];\n" : "=r"(par) : "l"(&g_par) : "memory");
#pragma unroll
        for (int i = 0; i < 4; i++) {
            asm volatile("ld.global.cg.f32 %0, [%1];\n" : "=f"(pre[i]) : "l"(&g_sums[i & 1][HID + (i >> 1) * C_DIM + tid]) : "memory");
            asm volatile("ld.global.nc.u16 %0, [%1];\n" : "=r"(gg[i]) : "l"(grn_g + tid + 384 * i) : "memory");
        }
    }
    TSTAMP(1, 0);
    if (tid == 384) {
        for (int i = 0; i < P2_NB; i++) {
            mbar_init(bar_bfull + i * 8, 1);
            mbar_init(bar_bempty + i * 8, 24);
        }
        for (int i = 0; i < 3 * P2_NA; i++) {
            mbar_init(bar_afull + i * 8, 1);
            mbar_init(bar_aempty + i * 8, 4);
        }
        mbar_init(bar_xfull, 2);
        mbar_init(bar_oready, 4);
        asm volatile("st.shared.u32 [%0], 0;\n" ::"r"(s_pos) : "memory");
        asm volatile("fence.mbarrier_init.release.cluster;\n" ::: "memory");
    }
    __syncthreads();
    cluster_sync_relaxed();

    if (warp >= 12) {
        reg_dec<32>();
        if (warp == 12) {
            const uint8_t* wsrc = reinterpret_cast<const uint8_t*>(g_w2img) + rank * (P2_B / 2);
            int st = 0, ph = 1, kb = k0, m = 0, r = 0;
            const int busy = head ? 0 : tail ? P2_POS - 24 : P2_POS;
#pragma unroll 1
            for (int p = 0; p < P2_POS; p++) {
                if (p == 0 || p == P2_FOLD) {
                    flag_wait<true>(&g_img[p != 0], p ? 96 * 4 : 48);
                    asm volatile("fence.proxy.async.global;\n" ::: "memory");
                    if (p) wsrc += sizeof(g_w2img[0]);
                }
                mbar_wait(bar_bempty + st * 8, ph);
                TR2P(p, 0);
                if (elect_one()) {
                    mbar_expect_tx(bar_bfull + st * 8, P2_B);
                    bulk_g2s_mc(sbase + st * P2_B + rank * (P2_B / 2), wsrc + kb * P2_B, P2_B / 2, bar_bfull + st * 8, (uint16_t)3);
                    asm volatile("st.volatile.shared.u32 [%0], %1;\n" ::"r"(s_pos), "r"(p) : "memory");
                    const int idle = 2 - min(m, P2_ITEMS - 1) + max(m - 2 + (r >= 48 - 2 * P2_LAG), 0) - ((unsigned)(p - busy) < 24);
                    if (idle) asm volatile("mbarrier.arrive.shared::cta.b64 _, [%0], %1;\n" ::"r"(bar_bempty + st * 8), "r"(idle * 8) : "memory");
                    if (rank == 0) asm volatile("red.relaxed.gpu.global.add.u32 [%0], 1;\n" ::"l"(&g_prog) : "memory");
                }
                __syncwarp();
                if (++st == P2_NB) { st = 0; ph ^= 1; }
                if (++kb == 48) kb = 0;
                if (++r == P2_LAG) { r = 0; m++; }
            }
            mbar_wait(bar_bempty + st * 8, ph);
            if (lane == 0) mbar_arrive(bar_bfull + st * 8);
#pragma unroll 1
            for (int p = 1; p < P2_NB; p++) {
                if (++st == P2_NB) { st = 0; ph ^= 1; }
                mbar_wait(bar_bempty + st * 8, ph);
            }
        } else if (warp == 13) {
            const uint8_t* src[3];
            int n[3], left[3], wrap[3];
            uint32_t st[3];
            auto item = [&](int w) {
                const int u = (k0 + p2_start(n[w])) % 48;
                left[w] = n[w] < 0 || n[w] == P2_ITEMS ? 24 : 48;
                wrap[w] = left[w] - (48 - u);
                src[w] = reinterpret_cast<const uint8_t*>(g_h) + (size_t)p2_tile(cl, n[w]) * (2 * H_TILE) + rank * H_HALF + u * H_STEP;
            };
#pragma unroll
            for (int w = 0; w < 3; w++) {
                n[w] = w == 2 && head ? -1 : w;
                st[w] = 0x80000000u;
                item(w);
            }
            gdc_wait();
#pragma unroll 1
            for (int done = 0; done < 3;) {
                bool idle = true;
#pragma unroll
                for (int w = 0; w < 3; w++) {
                    const uint32_t o = (st[w] & 0xff) + w * P2_NA * 8;
                    if (left[w] >= 0 && mbar_test(bar_aempty + o, st[w] >> 31)) {
                        idle = false;
                        if (left[w] == 0) {
                            if (lane == 0) mbar_arrive(bar_afull + o);
                            left[w] = -1;
                            done++;
                        } else {
                            if (elect_one()) {
                                mbar_expect_tx(bar_afull + o, P2_A);
                                bulk_g2s(sbase + P2_OFF_A + o * (P2_A / 8), src[w], P2_A, bar_afull + o);
                            }
                            __syncwarp();
                            src[w] += H_STEP;
                            st[w] += 8;
                            if ((st[w] & 0xff) == P2_NA * 8) st[w] ^= 0x80000000u | (P2_NA * 8);
                            if (--left[w] == wrap[w]) src[w] -= 48 * H_STEP;
                            if (left[w] == 0 && (n[w] += 3) < P2_ITEMS + tail) item(w);
                        }
                    }
                }
                if (idle) __nanosleep(P2_HSLEEP);
                SAFE_BREAK
            }
        } else if (warp == 14) {
            const uint32_t sx = sbase + P2_OFF_X;
            size_t o = 0;
            auto pace = [&](int target) {
                int v;
                while (true) {
                    asm volatile("ld.volatile.shared.u32 %0, [%1];\n" : "=r"(v) : "r"(s_pos) : "memory");
                    if (v * 16 >= target) break;
                    __nanosleep(P2_PSLEEP);
                    SAFE_BREAK
                }
            };
#pragma unroll 1
            for (int n = -head; n <= P2_ITEMS; n++) {
                const size_t on = (size_t)(2 * p2_tile(cl, n) + rank) * (64 * C_DIM * 2);
                const bool st = n + head > 0, ld = n < P2_ITEMS;
                if (st) mbar_wait(bar_oready, (n - 1 + head) & 1);
                TR2P(n + 1, 1);
                if (lane == 0) {
                    if (n == 1 && head) {
                        asm volatile("cp.async.bulk.wait_group 0;\nfence.proxy.async.global;\n" ::: "memory");
                        asm volatile("st.release.gpu.global.u32 [%0], 1;\n" ::"l"(&g_half[pair][rank]) : "memory");
                    }
                    if (ld) mbar_expect_tx(bar_xfull, 64 * C_DIM * 2);
                    int t = st && n < P2_ITEMS - 1 ? (P2_LAG * (n - 1) + 48 + P2_T0 - 1) * 16 : -1024;
#pragma unroll 1
                    for (int c = 0; st && c < 64 * P2_XROW; c += P2_XC) {
                        pace(t += P2_TS);
                        bulk_s2g(reinterpret_cast<uint8_t*>(out) + o + c, sx + c + (c >= 32 * P2_XROW ? 64 : 0), P2_XC);
                    }
                    asm volatile("cp.async.bulk.commit_group;\ncp.async.bulk.wait_group.read 0;\n" ::: "memory");
#pragma unroll 1
                    for (int c = 0; ld && c < 64 * P2_XROW; c += P2_XC) {
                        pace(t += P2_TS);
                        bulk_g2s(sx + c + (c >= 32 * P2_XROW ? 64 : 0), reinterpret_cast<const uint8_t*>(x) + on + c, P2_XC, bar_xfull);
                    }
                    TR2P(n + 1, 2);
                    if (rank == 0 && n > 0 && n < P2_ITEMS - 2)
                        flag_wait<false>(&g_prog, P2_NCL * (P2_LAG * n + 48 + P2_EXTRA) + (tail ? P2_SHARED - P2_NCL : P2_SHARED) * P2_DELTA);
                    if (ld) mbar_arrive(bar_xfull);
                    TR2P(n + 1, 3);
                }
                __syncwarp();
                o = on;
            }
            asm volatile("cp.async.bulk.wait_group 0;\n" ::: "memory");
            TR2P(30, 1);
        }
    } else {
        reg_inc<160>();
        const int wg = warp >> 2, w = warp & 3, g = lane >> 2, q = lane & 3;
        const uint32_t sx = sbase + P2_OFF_X + (g & 1) * P2_XHALF + (w * 8 + (g >> 1)) * P2_XROW + q * 16;
        const uint32_t af = bar_afull + wg * P2_NA * 8, ae = bar_aempty + wg * P2_NA * 8;
        const uint32_t s_a = sbase + P2_OFF_A - bar_afull * (P2_A / 8) + (lane >> 3) * 512 + (lane & 7) * 64 +
                             ((w ^ ((lane & 7) >> 1)) << 4);
        uint32_t acc0[48], acc1[48];
        float up;
        uint4 a0[2], a1[2];
        int st = 0, ph = 0;

        {
            float4* s_red = reinterpret_cast<float4*>(smem + P2_OFF_BIAS);
            const float* sums = g_sums[par];
            float gx[4], part = 0.f, mx = 0.f;
            TSTAMP(1, 27);
            gdc_wait();
            TSTAMP(1, 1);
#pragma unroll
            for (int i = 0; i < 4; i++) gx[i] = __ldcg(sums + tid + 384 * i);
            if (blockIdx.x == 120 && tid < (LN_RING + 3) * 2) (&g_flag[0][0][0])[tid * 8] = 0;
            if (blockIdx.x == 121 && tid == 0) atomicAdd(&g_epoch, 1u);
            float z = __uint_as_float(__reduce_max_sync(0xffffffffu, __float_as_uint(pre[2] + pre[3])));
#pragma unroll
            for (int i = 0; i < 4; i++) {
                asm("sqrt.approx.f32 %0, %1;\n" : "=f"(gx[i]) : "f"(fmaf(gx[i], HSCALE * HSCALE, 1e-6f)));
                part += gx[i];
                gx[i] *= bf_lo(gg[i]);
                mx = fmaxf(mx, fabsf(gx[i]));
            }
#pragma unroll
            for (int o = 16; o > 0; o >>= 1) part += __shfl_xor_sync(0xffffffffu, part, o);
            mx = __uint_as_float(__reduce_max_sync(0xffffffffu, __float_as_uint(mx)));
            TSTAMP(1, 26);
            if (lane == 0) s_red[warp] = make_float4(part, mx, z, 0.f);
            bar_sync(1, 384);
            float tot = 0.f;
            {
                const float4 t = s_red[min(lane & 15, 11)];
                tot = (lane & 15) < 12 ? t.x : 0.f;
#pragma unroll
                for (int o = 8; o > 0; o >>= 1) tot += __shfl_xor_sync(0xffffffffu, tot, o);
                mx = __uint_as_float(__reduce_max_sync(0xffffffffu, __float_as_uint(t.y)));
                z = __uint_as_float(__reduce_max_sync(0xffffffffu, __float_as_uint(t.z)));
            }
            const float inv = __fdividef(1.0f, fmaf(tot, 1.0f / HID, 1e-6f));
            const uint32_t j = max(__float_as_uint(fmaf(mx, inv, 1.0f) * 1.01f) >> 23, 130u) - 130u;
            const float dn = __uint_as_float((127u - j) << 23);
#pragma unroll
            for (int i = 0; i < 4; i++)
                *reinterpret_cast<uint16_t*>(smem + P2_OFF_GRN + (tid + 384 * i) * 2) = pack_f16(fmaf(gx[i], inv, 1.0f) * dn, 0.f);
            up = (HSCALE * 1.00235f) * __uint_as_float(min(acc_exp(z) - 9u + j, 253u) << 23);
            TSTAMP(1, 25);
            bar_sync(1, 384);
            reinterpret_cast<float*>(smem + P2_OFF_BIAS)[tid] = pre[0] + pre[1];
            if (wg == 1 && blockIdx.x < 96) {
                const uint4* src = g_w2img[0] + blockIdx.x * 768 + tid - 128;
                const uint4 fk = *reinterpret_cast<const uint4*>(smem + P2_OFF_GRN + blockIdx.x * 32 + (tid & 8) * 2);
                uint4 v[6];
#pragma unroll
                for (int i = 0; i < 6; i++) v[i] = __ldcg(src + i * 128);
                auto fold = [&](uint32_t b, uint32_t f) { return (h2_mul(b, f) + 0x00040004u) & 0xfff8fff8u; };
#pragma unroll
                for (int i = 0; i < 6; i++)
                    g_w2img[1][blockIdx.x * 768 + tid - 128 + i * 128] = make_uint4(fold(v[i].x, fk.x), fold(v[i].y, fk.y), fold(v[i].z, fk.z), fold(v[i].w, fk.w));
                asm volatile("fence.proxy.async.global;\n" ::: "memory");
                __threadfence();
                __syncwarp();
                if (lane == 0) asm volatile("red.release.gpu.global.add.u32 [%0], 1;\n" ::"l"(&g_img[1]) : "memory");
            }
        }
        TSTAMP(1, 28);
        int kt = k0, pos;
        const int who = __shfl_sync(0xffffffffu, lane == 2 ? 0 : lane < 2 ? 1 : 2, lane);
        const uint32_t rel0 = who ? mapa(bar_bempty, lane & 1) : mapa(ae, rank), rel1 = rel0 + (who ? P2_NB : P2_NA) * 8;
        uint32_t rel = rel1 - 8;
        auto next_rel = [&](bool go) {
            if (go) rel += 8;
            if (rel == rel1) rel = rel0;
        };
        auto release_b = [&]() {
            next_rel(who == 1);
            if (who == 1) mbar_arrive_cluster(rel);
        };
        auto seek = [&](int p) {
            pos = p;
            st = p % P2_NB;
            ph = p / P2_NB & 1;
            if (who == 1) rel = (st ? rel0 + st * 8 : rel1) - 8;
            int v;
            while (true) {
                asm volatile("ld.volatile.shared.u32 %0, [%1];\n" : "=r"(v) : "r"(s_pos) : "memory");
                if (v >= p) break;
                __nanosleep(200);
                SAFE_BREAK
            }
        };
        auto publish = [&]() {
            asm volatile("fence.proxy.async.shared::cta;\n" ::: "memory");
            __syncwarp();
            if (who == 0) mbar_arrive(bar_oready);
        };
        bool ok_a;
        uint32_t abar = af, pa = 0;
        auto fetch = [&](uint4 (&a)[2], bool early) {
            const uint32_t src = s_a + abar * (P2_A / 8);
            abar += 8;
            if (abar == af + P2_NA * 8) { abar = af; pa ^= 0x80000000u; }
            const bool ok_b = mbar_test(bar_bfull + st * 8, ph);
            ok_a = mbar_test(abar, pa >> 31);
            uint32_t o[6];
            asm volatile("ldmatrix.sync.aligned.m8n8.x4.trans.shared.b16 {%0,%1,%2,%3}, [%4];\n"
                         : "=r"(o[0]), "=r"(o[1]), "=r"(o[2]), "=r"(o[3]) : "r"(src) : "memory");
            asm volatile("ldmatrix.sync.aligned.m8n8.x2.trans.shared.b16 {%0,%1}, [%2];\n"
                         : "=r"(o[4]), "=r"(o[5]) : "r"(src + 2048) : "memory");
            p2_unpack(a[0], o[0], o[1], o[2]);
            p2_unpack(a[1], o[3], o[4], o[5]);
            if (early) {
                const uint32_t* t = reinterpret_cast<const uint32_t*>(smem + P2_OFF_GRN) + kt * 16 + q;
#pragma unroll
                for (int i = 0; i < 2; i++)
                    a[i] = make_uint4(h2_mul(a[i].x, t[8 * i]), h2_mul(a[i].y, t[8 * i]), h2_mul(a[i].z, t[8 * i + 4]), h2_mul(a[i].w, t[8 * i + 4]));
                if (++kt == 48) kt = 0;
            }
            if (!ok_b) mbar_wait(bar_bfull + st * 8, ph);
        };
        auto step = [&](const uint4 (&a)[2], uint4 (&an)[2], int thr, bool early) {
            TR2(0);
            const uint64_t db = make_desc(sbase + st * P2_B, 128, 256);
            wg_fence();
            mma_rs_n192(acc0, a[0], db, thr - 1);
            mma_rs_n192(acc1, a[0], db + 384, thr - 1);
            mma_rs_n192(acc0, a[1], db + 768, 1);
            mma_rs_n192(acc1, a[1], db + 768 + 384, 1);
            wg_commit();
            next_rel(who < thr);
            if (++st == P2_NB) { st = 0; ph ^= 1; }
            wg_wait<1>();
            if (!ok_a) {
                if (who < thr) mbar_arrive_cluster(rel);
                thr = 0;
                mbar_wait(abar, pa >> 31);
            }
            if (who < thr) mbar_arrive_cluster(rel);
            fetch(an, early);
            pos++;
        };
        int n = wg == 2 && head ? -1 : wg;
        mbar_wait(af, 0);
        seek(p2_start(n));
        fetch(a0, n <= 0);
#pragma unroll 1
        for (;; n += 3) {
            TSTAMP(1, 2 + n);
            const int p0 = n < 0 || n == P2_ITEMS ? 12 : 0, pe = n <= 0 ? p0 + P2_FOLD / 2 : 0;
            const bool more = n + 3 < P2_ITEMS + tail;
#pragma unroll 1
            for (int p = p0; p < 24; p++) {
                step(a0, a1, p == p0 ? 1 : 2, p < pe);
                step(a1, a0, 2, p < pe);
            }
            if (n == P2_ITEMS) {
                flag_wait<true>(&g_half[pair][rank], 1);
                TR2(1);
                wg_wait<0>();
                TR2(2);
                release_b();
                uint8_t* o = reinterpret_cast<uint8_t*>(out) + (size_t)((2 * p2_tile(cl, -1) + rank) * 64 + (g & 1) * 32 + w * 8 + (g >> 1)) * P2_XROW + q * 16;
                p2_epilogue_add(acc0, o, up, zero);
                p2_epilogue_add(acc1, o + 384, up, zero);
                TR2(3);
                break;
            }
            mbar_wait(bar_xfull, (n + head) & 1);
            TR2(1);
            wg_wait<0>();
            TR2(2);
            release_b();
            __syncwarp();
            p2_epilogue(acc0, acc1, sx, sbase + P2_OFF_BIAS + q * 32, up, zero);
            TR2(3);
            publish();
            if (!more) break;
            seek(p2_start(n + 3));
            mbar_wait(bar_bfull + st * 8, ph);
        }
        TSTAMP(1, 30);
    }
}

}

extern "C" void kernel_launch(void* const* d_in, const int* in_sizes, int n_in, void* d_out, int out_size) {
    const __nv_bfloat16* x = (const __nv_bfloat16*)d_in[0];
    const __nv_bfloat16* dw = (const __nv_bfloat16*)d_in[1];
    const __nv_bfloat16* w1 = (const __nv_bfloat16*)d_in[2];
    const __nv_bfloat16* w2 = (const __nv_bfloat16*)d_in[3];
    const __nv_bfloat16* grn_g = (const __nv_bfloat16*)d_in[4];
    const __nv_bfloat16* grn_b = (const __nv_bfloat16*)d_in[5];
    __nv_bfloat16* out = (__nv_bfloat16*)d_out;

    cudaFuncSetAttribute(pass1_kernel, cudaFuncAttributeMaxDynamicSharedMemorySize, P1_SMEM);
    cudaFuncSetAttribute(pass2_kernel, cudaFuncAttributeMaxDynamicSharedMemorySize, P2_SMEM);

    typedef CUresult (*EncodeFn)(CUtensorMap*, CUtensorMapDataType, cuuint32_t, void*, const cuuint64_t*, const cuuint64_t*,
                                 const cuuint32_t*, const cuuint32_t*, CUtensorMapInterleave, CUtensorMapSwizzle,
                                 CUtensorMapL2promotion, CUtensorMapFloatOOBfill);
    static EncodeFn encode = nullptr;
    if (!encode) {
        cudaDriverEntryPointQueryResult qres;
        cudaGetDriverEntryPoint("cuTensorMapEncodeTiled", (void**)&encode, cudaEnableDefault, &qres);
    }
    CUtensorMap wmap;
    const cuuint64_t gdim[2] = {HID, C_DIM};
    const cuuint64_t gstr[1] = {HID * 2};
    const cuuint32_t box[2] = {64, 192}, estr[2] = {1, 1};
    CUresult er = encode(&wmap, CU_TENSOR_MAP_DATA_TYPE_BFLOAT16, 2, (void*)w1, gdim, gstr, box, estr, CU_TENSOR_MAP_INTERLEAVE_NONE,
           CU_TENSOR_MAP_SWIZZLE_128B, CU_TENSOR_MAP_L2_PROMOTION_L2_128B, CU_TENSOR_MAP_FLOAT_OOB_FILL_NONE);
    if (er != CUDA_SUCCESS) printf("tensor map encode failed %d\n", (int)er);

    pass1_kernel<<<NUM_CTAS, 512, P1_SMEM>>>(wmap, x, dw, w1, w2, grn_b, 0);

    cudaLaunchAttribute attr[1];
    attr[0].id = cudaLaunchAttributeProgrammaticStreamSerialization;
    attr[0].val.programmaticStreamSerializationAllowed = 1;
    cudaLaunchConfig_t cfg = {};
    cfg.gridDim = dim3(NUM_CTAS);
    cfg.stream = 0;
    cfg.attrs = attr;
    cfg.numAttrs = 1;
    cfg.blockDim = dim3(512);
    cfg.dynamicSmemBytes = P2_SMEM;
    cudaLaunchKernelEx(&cfg, pass2_kernel, x, grn_g, out, 0);
}
```

```cpp
#include <cuda.h>
#include <cuda_runtime.h>
#include <cuda_bf16.h>
#include <stdint.h>
#include <stdio.h>

namespace {

constexpr int M_TOTAL = 384 * 384;
constexpr int C_DIM   = 384;
constexpr int HID     = 1536;
constexpr int NT128   = M_TOTAL / 128;
constexpr int NUM_CTAS = 132;

constexpr int NGRP = 15;
#define LN_DEPTH 2
constexpr int LN_STEP = 2 * NGRP, LN_RING = LN_DEPTH * LN_STEP;
#define P1_M 101
#define P1_D 10
__device__ __forceinline__ int p1_tile(int t, bool small) {
    return t + (small ? ((t + 1) * P1_M + P1_D - 1) / P1_D : t * P1_D / P1_M);
}
constexpr int LN_TILE = 128 * C_DIM * 2;
constexpr int H_TILE = 64 * HID * 3 / 2;
constexpr int H_HALF = 3072, H_STEP = 6144;

__device__ __align__(1024) uint4 g_h[(size_t)M_TOTAL * HID * 3 / 32];
__device__ __align__(1024) uint4 g_ln[LN_RING * LN_TILE / 16];
__device__ __align__(1024) uint4 g_w2img[2][HID * C_DIM * 2 / 16];
__device__ __align__(16) float g_sums[2][HID + 2 * C_DIM];
__device__ __align__(16) unsigned g_ex[HID];
__device__ unsigned g_epoch, g_par;
__device__ __align__(128) unsigned g_img[2];
__device__ __align__(128) unsigned g_prog;
__device__ __align__(128) unsigned g_half[32][2];
__device__ unsigned g_flag[LN_RING + 3][2][8];
#define TSTAMP(k, i)
#define STAMPT(t, i)
#define TRACE(wg, pos, i)
#define TRACEW(pos, i)

#define TR2(i)
#define TR2P(pos, i)
__host__ __device__ __forceinline__ int perm32(int n) {
    return (n & ~31) | (((n >> 1) & 3) << 3) | (((n >> 3) & 3) << 1) | (n & 1);
}

__device__ __forceinline__ uint32_t smem_u32(const void* p) { return (uint32_t)__cvta_generic_to_shared(p); }

__device__ __forceinline__ void mbar_init(uint32_t bar, uint32_t count) {
    asm volatile("mbarrier.init.shared::cta.b64 [%0], %1;\n" ::"r"(bar), "r"(count) : "memory");
}
__device__ __forceinline__ void mbar_expect_tx(uint32_t bar, uint32_t bytes) {
    asm volatile("mbarrier.arrive.expect_tx.shared::cta.b64 _, [%0], %1;\n" ::"r"(bar), "r"(bytes) : "memory");
}
__device__ __forceinline__ void mbar_arrive(uint32_t bar) {
    asm volatile("mbarrier.arrive.shared::cta.b64 _, [%0];\n" ::"r"(bar) : "memory");
}
__device__ __forceinline__ void mbar_arrive_cluster(uint32_t bar_cluster_addr) {
    asm volatile("mbarrier.arrive.shared::cluster.b64 _, [%0];\n" ::"r"(bar_cluster_addr) : "memory");
}
#define SAFE_BREAK
__device__ __forceinline__ void mbar_wait(uint32_t bar, uint32_t parity) {
    asm volatile(
        "{\n"
        ".reg .pred p;\n"
        "LAB_WAIT:\n"
        "mbarrier.try_wait.parity.shared::cta.b64 p, [%0], %1;\n"
        "@!p bra LAB_WAIT;\n"
        "}\n" ::"r"(bar), "r"(parity) : "memory");
}
__device__ __forceinline__ bool mbar_test(uint32_t bar, uint32_t parity) {
    uint32_t ok;
    asm volatile("{\n.reg .pred p;\n"
                 "mbarrier.test_wait.parity.shared::cta.b64 p, [%1], %2;\n"
                 "selp.u32 %0, 1, 0, p;\n}\n" : "=r"(ok) : "r"(bar), "r"(parity) : "memory");
    return ok != 0;
}
__device__ __forceinline__ uint32_t mapa(uint32_t addr, uint32_t rank) {
    uint32_t r;
    asm volatile("mapa.shared::cluster.u32 %0, %1, %2;\n" : "=r"(r) : "r"(addr), "r"(rank));
    return r;
}
__device__ __forceinline__ void bulk_g2s(uint32_t dst, const void* src, uint32_t bytes, uint32_t bar) {
    asm volatile("cp.async.bulk.shared::cluster.global.mbarrier::complete_tx::bytes [%0], [%1], %2, [%3];\n"
                 ::"r"(dst), "l"(src), "r"(bytes), "r"(bar) : "memory");
}
__device__ __forceinline__ void bulk_g2s_mc(uint32_t dst, const void* src, uint32_t bytes, uint32_t bar, uint16_t mask) {
    asm volatile("cp.async.bulk.shared::cluster.global.mbarrier::complete_tx::bytes.multicast::cluster [%0], [%1], %2, [%3], %4;\n"
                 ::"r"(dst), "l"(src), "r"(bytes), "r"(bar), "h"(mask) : "memory");
}
__device__ __forceinline__ void tma2(uint32_t dst, const CUtensorMap* map, int c0, int c1, uint32_t bar) {
    asm volatile("cp.async.bulk.tensor.2d.shared::cluster.global.tile.mbarrier::complete_tx::bytes [%0], [%1, {%2, %3}], [%4];\n"
                 ::"r"(dst), "l"(map), "r"(c0), "r"(c1), "r"(bar) : "memory");
}
template <bool ACQ>
__device__ __forceinline__ uint32_t flag_wait(const unsigned* p, unsigned target) {
    unsigned v, n = 0;
    do {
        if (ACQ) asm volatile("ld.acquire.gpu.global.u32 %0, [%1];\n" : "=r"(v) : "l"(p) : "memory");
        else asm volatile("ld.relaxed.gpu.global.u32 %0, [%1];\n" : "=r"(v) : "l"(p) : "memory");
        n++;
    } while (v < target);
    return n == 1;
}
__device__ __forceinline__ void ldsm4t(uint32_t (&r)[4], uint32_t addr) {
    asm volatile("ldmatrix.sync.aligned.m8n8.x4.trans.shared.b16 {%0,%1,%2,%3}, [%4];\n"
                 : "=r"(r[0]), "=r"(r[1]), "=r"(r[2]), "=r"(r[3]) : "r"(addr) : "memory");
}
__device__ __forceinline__ void bulk_s2g(void* dst, uint32_t src, uint32_t bytes) {
    asm volatile("cp.async.bulk.global.shared::cta.bulk_group [%0], [%1], %2;\n" ::"l"(dst), "r"(src), "r"(bytes) : "memory");
}
__device__ __forceinline__ void cluster_sync_relaxed() {
    asm volatile("barrier.cluster.arrive.relaxed.aligned;\nbarrier.cluster.wait.aligned;\n" ::: "memory");
}
__device__ __forceinline__ void gdc_wait() { asm volatile("griddepcontrol.wait;\n" ::: "memory"); }
__device__ __forceinline__ void gdc_launch() { asm volatile("griddepcontrol.launch_dependents;\n" ::: "memory"); }
__device__ __forceinline__ uint32_t cluster_rank() {
    uint32_t r;
    asm volatile("mov.u32 %0, %%cluster_ctarank;\n" : "=r"(r));
    return r;
}
__device__ __forceinline__ bool elect_one() {
    uint32_t pred;
    asm volatile("{\n.reg .pred p;\nelect.sync _|p, 0xffffffff;\nselp.u32 %0, 1, 0, p;\n}\n" : "=r"(pred));
    return pred != 0;
}
__device__ __forceinline__ void wg_fence() { asm volatile("wgmma.fence.sync.aligned;\n" ::: "memory"); }
__device__ __forceinline__ void wg_commit() { asm volatile("wgmma.commit_group.sync.aligned;\n" ::: "memory"); }
template <int N> __device__ __forceinline__ void wg_wait() {
    asm volatile("wgmma.wait_group.sync.aligned %0;\n" ::"n"(N) : "memory");
}
template <int R> __device__ __forceinline__ void reg_inc() { asm volatile("setmaxnreg.inc.sync.aligned.u32 %0;\n" ::"n"(R)); }
template <int R> __device__ __forceinline__ void reg_dec() { asm volatile("setmaxnreg.dec.sync.aligned.u32 %0;\n" ::"n"(R)); }
__device__ __forceinline__ void bar_sync(int id, int n) { asm volatile("bar.sync %0, %1;\n" ::"r"(id), "r"(n) : "memory"); }
__device__ __forceinline__ void bar_arrive(int id, int n) { asm volatile("bar.arrive %0, %1;\n" ::"r"(id), "r"(n) : "memory"); }

__device__ __forceinline__ uint64_t make_desc(uint32_t saddr, uint32_t lbo, uint32_t sbo) {
    return (uint64_t)((saddr & 0x3FFFF) >> 4) | ((uint64_t)(lbo >> 4) << 16) | ((uint64_t)(sbo >> 4) << 32);
}

__device__ __forceinline__ void stg128_cs(void* p, uint32_t a, uint32_t b, uint32_t c, uint32_t d) {
    asm volatile("st.global.cs.v4.u32 [%0], {%1,%2,%3,%4};\n" ::"l"(p), "r"(a), "r"(b), "r"(c), "r"(d) : "memory");
}
__device__ __forceinline__ uint32_t pack_bf16(float lo, float hi) {
    uint32_t r;
    asm("cvt.rn.bf16x2.f32 %0, %1, %2;\n" : "=r"(r) : "f"(hi), "f"(lo));
    return r;
}
__device__ __forceinline__ float bf_lo(uint32_t v) { return __uint_as_float(v << 16); }
__device__ __forceinline__ float bf_hi(uint32_t v) { return __uint_as_float(v & 0xffff0000u); }
__device__ __forceinline__ uint32_t bf2_mul(uint32_t a, uint32_t b) {
    uint32_t r;
    asm("mul.rn.bf16x2 %0, %1, %2;\n" : "=r"(r) : "r"(a), "r"(b));
    return r;
}
__device__ __forceinline__ uint32_t bf2_fma(uint32_t a, uint32_t b, uint32_t c) {
    uint32_t r;
    asm("fma.rn.bf16x2 %0, %1, %2, %3;\n" : "=r"(r) : "r"(a), "r"(b), "r"(c));
    return r;
}
__device__ __forceinline__ uint32_t bf2_add(uint32_t a, uint32_t b) {
    uint32_t r;
    asm("add.rn.bf16x2 %0, %1, %2;\n" : "=r"(r) : "r"(a), "r"(b));
    return r;
}
constexpr float KAPPA = 0.3292034911525734f;
constexpr float GELU_C = 2.423681954311584f;
constexpr float HSCALE = 1.0f / (2.0f * KAPPA);
__device__ __forceinline__ uint32_t acc_exp(float z) { return max(__float_as_uint(z) >> 23, 10u); }
__device__ __forceinline__ void sched_break(int zero) {
    asm volatile("{\n.reg .pred p;\nsetp.ne.s32 p, %0, 0;\nSB_LOOP:\n@p nanosleep.u32 1;\n@p bra SB_LOOP;\n}\n" ::"r"(zero));
}

#define ACC8(d, o) "+f"(d[o + 0]), "+f"(d[o + 1]), "+f"(d[o + 2]), "+f"(d[o + 3]), "+f"(d[o + 4]), "+f"(d[o + 5]), "+f"(d[o + 6]), "+f"(d[o + 7])

#define ACCR8(d, o) "+r"(d[o + 0]), "+r"(d[o + 1]), "+r"(d[o + 2]), "+r"(d[o + 3]), "+r"(d[o + 4]), "+r"(d[o + 5]), "+r"(d[o + 6]), "+r"(d[o + 7])
__device__ __forceinline__ void mma_rs_n128(uint32_t (&d)[32], const uint32_t (&a)[4], uint64_t desc, int scale_d) {
    asm volatile(
        "{\n.reg .pred p;\nsetp.ne.b32 p, %37, 0;\n"
        "wgmma.mma_async.sync.aligned.m64n128k16.f16.f16.f16 "
        "{%0,%1,%2,%3,%4,%5,%6,%7,%8,%9,%10,%11,%12,%13,%14,%15,"
        "%16,%17,%18,%19,%20,%21,%22,%23,%24,%25,%26,%27,%28,%29,%30,%31},"
        "{%32,%33,%34,%35}, %36, p, 1, 1, 0;\n}\n"
        : ACCR8(d, 0), ACCR8(d, 8), ACCR8(d, 16), ACCR8(d, 24)
        : "r"(a[0]), "r"(a[1]), "r"(a[2]), "r"(a[3]), "l"(desc), "r"(scale_d));
}
__device__ __forceinline__ void mma_ss_n128(uint32_t (&d)[32], uint64_t da, uint64_t db) {
    asm volatile(
        "{\n.reg .pred p;\nsetp.ne.b32 p, %34, 0;\n"
        "wgmma.mma_async.sync.aligned.m64n128k16.f16.f16.f16 "
        "{%0,%1,%2,%3,%4,%5,%6,%7,%8,%9,%10,%11,%12,%13,%14,%15,"
        "%16,%17,%18,%19,%20,%21,%22,%23,%24,%25,%26,%27,%28,%29,%30,%31},"
        "%32, %33, p, 1, 1, 0, 0;\n}\n"
        : ACCR8(d, 0), ACCR8(d, 8), ACCR8(d, 16), ACCR8(d, 24)
        : "l"(da), "l"(db), "r"(1));
}
__device__ __forceinline__ uint32_t bf2_as_h2(uint32_t v) { return (v & 0x0fff0fffu) * 7u + v; }
__device__ __forceinline__ float h_lo(uint32_t v) {
    float r;
    asm("{\n.reg .b16 l, h;\nmov.b32 {l, h}, %1;\ncvt.f32.f16 %0, l;\n}\n" : "=f"(r) : "r"(v));
    return r;
}
__device__ __forceinline__ float h_hi(uint32_t v) {
    float r;
    asm("{\n.reg .b16 l, h;\nmov.b32 {l, h}, %1;\ncvt.f32.f16 %0, h;\n}\n" : "=f"(r) : "r"(v));
    return r;
}

__device__ __forceinline__ void mma_rs_n192(uint32_t (&d)[48], const uint4& a, uint64_t db, int scale_d) {
    asm volatile(
        "{\n.reg .pred p;\nsetp.ne.b32 p, %53, 0;\n"
        "wgmma.mma_async.sync.aligned.m64n192k16.f16.f16.f16 "
        "{%0,%1,%2,%3,%4,%5,%6,%7,%8,%9,%10,%11,%12,%13,%14,%15,"
        "%16,%17,%18,%19,%20,%21,%22,%23,%24,%25,%26,%27,%28,%29,%30,%31,"
        "%32,%33,%34,%35,%36,%37,%38,%39,%40,%41,%42,%43,%44,%45,%46,%47},"
        "{%48,%49,%50,%51}, %52, p, 1, 1, 0;\n}\n"
        : ACCR8(d, 0), ACCR8(d, 8), ACCR8(d, 16), ACCR8(d, 24), ACCR8(d, 32), ACCR8(d, 40)
        : "r"(a.x), "r"(a.y), "r"(a.z), "r"(a.w), "l"(db), "r"(scale_d));
}

__device__ __forceinline__ uint32_t pack_f16(float lo, float hi) {
    uint32_t r;
    asm("cvt.rn.f16x2.f32 %0, %1, %2;\n" : "=r"(r) : "f"(hi), "f"(lo));
    return r;
}

#define P1_IMG 900
constexpr int P1_SLOT = LN_TILE / 2, P1_NST = 4;
constexpr int P1_X = 16 * C_DIM * 2;
constexpr int P1_OFF_X = P1_SLOT * P1_NST;
constexpr int P1_OFF_A = P1_OFF_X + 2 * P1_X;
constexpr int P1_OFF_BAR = P1_OFF_A + 3 * 2048;
constexpr int P1_OFF_TILE = P1_OFF_BAR + (2 * P1_NST + 3 + 2 + 3 + 2) * 8;
constexpr int P1_OFF_DW = P1_OFF_TILE + 64;
constexpr int P1_SMEM = P1_OFF_DW + C_DIM * 2;

__device__ __forceinline__ float rsqrt_fast(float x) {
    float r;
    asm("rsqrt.approx.ftz.f32 %0, %1;\n" : "=f"(r) : "f"(x));
    return r;
}
__device__ __forceinline__ float sum8(const uint32_t (&c)[4]) {
    const uint32_t u = bf2_add(bf2_add(c[0], c[1]), bf2_add(c[2], c[3]));
    return bf_lo(u) + bf_hi(u);
}
__device__ __forceinline__ void lds128(uint32_t (&v)[4], uint32_t a) {
    asm volatile("ld.shared.v4.u32 {%0,%1,%2,%3}, [%4];\n" : "=r"(v[0]), "=r"(v[1]), "=r"(v[2]), "=r"(v[3]) : "r"(a) : "memory");
}
template <class F>
__device__ __forceinline__ void ln_row(uint32_t (&v)[6][4], uint32_t sdw, F after_loads) {
    uint32_t c[4], s[4], d[4], nm;
#pragma unroll
    for (int i = 0; i < 6; i++) {
        lds128(d, sdw + i * 128);
        if (i == 0) {
#pragma unroll
            for (int k = 0; k < 4; k++) c[k] = bf2_mul(v[0][k], d[k]);
            const float p = sum8(c) * -0.125f;
            nm = pack_bf16(p, p);
        }
#pragma unroll
        for (int k = 0; k < 4; k++) {
            v[i][k] = bf2_fma(v[i][k], d[k], nm);
            s[k] = i ? bf2_add(v[i][k], s[k]) : v[i][k];
            c[k] = i ? bf2_fma(v[i][k], v[i][k], c[k]) : bf2_mul(v[i][k], v[i][k]);
        }
    }
    after_loads(c[0]);
    float m = fmaf(sum8(s), 1.0f / 48, -bf_lo(nm));
    float q = fmaf(-bf_lo(nm), fmaf(2.f, m, bf_lo(nm)), sum8(c) * (1.0f / 48));
#pragma unroll
    for (int o = 1; o < 8; o <<= 1) {
        m += __shfl_xor_sync(0xffffffffu, m, o);
        q += __shfl_xor_sync(0xffffffffu, q, o);
    }
    m *= 0.125f;
    const float r = KAPPA * rsqrt_fast(fmaxf(fmaf(-m, m, q * 0.125f), 0.f) + 1e-5f);
    const float e = (-bf_lo(nm) - m) * r * 0x1p-112f;
    const bool two = __any_sync(0xffffffffu, r < 0x1p-14f);
    const float r1 = r * (two ? 0x1p-56f : 0x1p-112f);
    uint32_t mul = pack_bf16(r1, r1), add = two ? 0u : pack_bf16(e, e);
#pragma unroll 1
    for (int it = !two; it < 2; it++) {
#pragma unroll
        for (int i = 0; i < 6; i++)
#pragma unroll
            for (int k = 0; k < 4; k++) v[i][k] = bf2_fma(v[i][k], mul, add);
        mul = 0x23802380u;
        add = pack_bf16(e, e);
    }
#pragma unroll
    for (int i = 0; i < 6; i++)
#pragma unroll
        for (int k = 0; k < 4; k++) v[i][k] = bf2_as_h2(v[i][k]);
}

__device__ __forceinline__ float gelu_s(float y) {
    float u = y * fmaf(y, y, GELU_C);
    float t;
    asm volatile("tanh.approx.f32 %0, %1;\n" : "=f"(t) : "f"(u));
    return fmaf(y, t, y);
}
__device__ __forceinline__ void p1_pack(int c, uint32_t (&p)[4], uint32_t (&dd)[4]) {
#pragma unroll
    for (int u = 0; u < 4; u++) {
        if ((c & 3) == 0) dd[u] = p[u];
        else {
            uint32_t n = dd[u];
            if ((c & 3) == 1) n = __byte_perm(n, 0, 0x2301);
            if ((c & 3) == 2) {
                dd[u] = __byte_perm(n >> 3, n >> 1, 0x6341);
                n = __byte_perm(n >> 3, n >> 1, 0x7250);
            }
            asm("lop3.b32 %0, %0, %1, 0x40074007, 0xd8;\n" : "+r"(p[u]) : "r"(n));
        }
    }
}
__device__ __forceinline__ void p1_store(int c, const uint32_t (&p)[4], uint8_t* hptr) {
    if (c & 3) stg128_cs(hptr + (c >> 2) * H_HALF + ((c & 3) - 1) * 512, p[0], p[1], p[2], p[3]);
}

template <bool GEN>
__device__ __forceinline__ void p1_epilogue(uint32_t (&acc)[32], float (&ssq)[2], uint32_t sc2, uint8_t* hp, int zero) {
    uint32_t sq[2], dd[4];
#pragma unroll
    for (int c = 0; c < 8; c++) {
        if (GEN) sched_break(zero);
        uint32_t p[4];
#pragma unroll
        for (int u = 0; u < 4; u++) {
            const uint32_t y = acc[8 * (c >> 1) + 2 * u + (c & 1)];
            if (GEN) {
                const float sc = c & 1 ? bf_hi(sc2) : bf_lo(sc2), fs = __uint_as_float(0x78000000u - __float_as_uint(sc));
                const float g0 = gelu_s(h_lo(y) * fs), g1 = gelu_s(h_hi(y) * fs);
                ssq[c & 1] = fmaf(g1, g1, fmaf(g0, g0, ssq[c & 1]));
                p[u] = pack_f16(g0 * sc, g1 * sc);
            } else {
                uint32_t g;
                asm("{\n.reg .b32 w;\n"
                    "fma.rn.f16x2 w, %1, %1, %2;\n"
                    "mul.rn.f16x2 w, w, %1;\n"
                    "tanh.approx.f16x2 w, w;\n"
                    "fma.rn.f16x2 %0, %1, w, %1;\n}\n" : "=r"(g) : "r"(y), "r"(0x40d940d9u));
                acc[8 * (c >> 1) + 2 * u + (c & 1)] = g;
                if (c < 2 && u == 0) asm("mul.rn.f16x2 %0, %1, %1;\n" : "=r"(sq[c & 1]) : "r"(g));
                else asm("fma.rn.f16x2 %0, %1, %1, %0;\n" : "+r"(sq[c & 1]) : "r"(g));
                if (c & 1) asm("{\n.reg .b16 l, h;\n.reg .b32 f;\nmov.b32 {l, h}, %2;\nmov.b32 f, {h, h};\nmul.rn.f16x2 %0, %1, f;\n}\n" : "=r"(p[u]) : "r"(g), "r"(sc2));
                else asm("{\n.reg .b16 l, h;\n.reg .b32 f;\nmov.b32 {l, h}, %2;\nmov.b32 f, {l, l};\nmul.rn.f16x2 %0, %1, f;\n}\n" : "=r"(p[u]) : "r"(g), "r"(sc2));
            }
        }
        p1_pack(c, p, dd);
        if (c & 3) {
#pragma unroll
            for (int u = 0; u < 4; u++) acc[4 * (c - 1 - (c >> 2)) + u] = p[u];
        }
        p1_store(c, p, hp);
    }
    if (!GEN) {
#pragma unroll
        for (int r = 0; r < 2; r++) ssq[r] += h_lo(sq[r]) + h_hi(sq[r]);
    }
}
__device__ __forceinline__ void p1_consumer(const uint32_t (&a)[24][4], uint32_t sc2, bool gen, uint32_t sbase, int wg, int nwg, int cb,
                                            int w, int lane, int zero) {
    const uint32_t bar_full = sbase + P1_OFF_BAR, bar_empty = bar_full + P1_NST * 8;
    const uint32_t empty_remote = mapa(bar_empty, lane & 1);
    const int g = lane >> 2, q = lane & 3, turn = wg + 1 == nwg ? 1 : wg + 2;
    float ssq[2] = {0.f, 0.f};
    uint32_t acc[32] = {};
    TSTAMP(0, 1);
    STAMPT(128, 4);
    STAMPT(256, 5);

    uint8_t* hp = reinterpret_cast<uint8_t*>(g_h) + ((cb * 2 + (w >> 1)) * H_STEP + (w & 1) * 1536) + g * 64 + (q ^ (g >> 1)) * 16;
    const uint64_t desc_base = make_desc(sbase, 16, 1024) | (1ull << 62);
    const uint64_t da = make_desc(sbase + P1_OFF_A + wg * 2048, 128, 256);
#pragma unroll 1
    for (int i = 0;; i++) {
        const int s0 = (i & 1) * 16, par = (i >> 1) & 1;
        const uint64_t d0 = desc_base + (uint64_t)((i & 1) * (LN_TILE / 16));
        TRACE(wg, i, 0);
        mbar_wait(bar_full + s0, par);
        bar_sync(1 + wg, 256);
        TRACE(wg, i, 1);
        uint32_t step, more;
        wg_fence();
#pragma unroll
        for (int k = 0; k < 24; k++) {
            if (k == 12) mbar_wait(bar_full + s0 + 8, par);
            const uint64_t db = d0 + (uint64_t)((k >> 2) * 1024 + (k & 3) * 2);
            if (k < 23) mma_rs_n128(acc, a[k], db, k ? 1 : zero);
            else mma_ss_n128(acc, da, db);
            if (k == 23) bar_arrive(turn, 256);
            if (k % 12 == 11) wg_commit();
        }
        asm volatile("ld.shared.v2.u32 {%0, %1}, [%2];\n" : "=r"(step), "=r"(more) : "r"(sbase + P1_OFF_TILE + (i & 3) * 16) : "memory");
        TRACE(wg, i, 2);
        wg_wait<1>();
        if (lane < 2) mbar_arrive_cluster(empty_remote + s0);
        hp += step;
        TRACE(wg, i, 3);
        wg_wait<0>();
        TRACE(wg, i, 4);
        if (lane < 2) mbar_arrive_cluster(empty_remote + s0 + 8);
        if (gen) p1_epilogue<true>(acc, ssq, sc2, hp, zero);
        else p1_epilogue<false>(acc, ssq, sc2, hp, zero);
        if (!more) break;
    }
    TSTAMP(0, 21);
    if (wg == 0) bar_sync(1, 256);
    uint32_t par;
    asm volatile("ld.shared.u32 %0, [%1];\n" : "=r"(par) : "r"(sbase + P1_OFF_TILE - 4) : "memory");
    float* sums = g_sums[par];
#pragma unroll
    for (int r = 0; r < 2; r++) {
        ssq[r] += __shfl_xor_sync(0xffffffffu, ssq[r], 1);
        ssq[r] += __shfl_xor_sync(0xffffffffu, ssq[r], 2);
        if (q == 0) atomicAdd(sums + cb * 64 + w * 16 + r * 8 + g, ssq[r]);
    }
}

__device__ __forceinline__ void p1_w2(const __nv_bfloat16* __restrict__ w2, const __nv_bfloat16* __restrict__ grn_b, int w, int lane) {
    const int gw = (blockIdx.x - 8 * NGRP) * 4 + w;
    float* sums = g_sums[__ldcg(&g_epoch) & 1] + HID;
    flag_wait<true>(&g_flag[40][1][0], 12);
    {
        const int col = gw % 6 * 64 + lane * 2;
        float bsum[2] = {0.f, 0.f}, asum[2] = {0.f, 0.f};
#pragma unroll 4
        for (int kk = 0; kk < 192; kk++) {
            const int k = gw / 6 * 192 + kk;
            const uint32_t v = *reinterpret_cast<const uint32_t*>(w2 + k * C_DIM + col);
            const float b = __bfloat162float(grn_b[k]), f = __uint_as_float(__ldcg(&g_ex[k]) << 23);
            bsum[0] = fmaf(b, bf_lo(v), bsum[0]);
            bsum[1] = fmaf(b, bf_hi(v), bsum[1]);
            asum[0] = fmaf(f, fabsf(bf_lo(v)), asum[0]);
            asum[1] = fmaf(f, fabsf(bf_hi(v)), asum[1]);
        }
#pragma unroll
        for (int j = 0; j < 2; j++) {
            atomicAdd(sums + col + j, bsum[j]);
            atomicAdd(sums + C_DIM + col + j, asum[j]);
        }
        __threadfence();
        __syncwarp();
        if (lane == 0) asm volatile("red.relaxed.gpu.global.add.u32 [%0], 1;\n" ::"l"(&g_flag[LN_RING + 2][0][0]) : "memory");
    }
    while (*(volatile unsigned*)&g_flag[P1_IMG % LN_RING][1][0] < 12 * (P1_IMG / LN_RING + 1)) {
        __nanosleep(2000);
        SAFE_BREAK
    }
    flag_wait<true>(&g_flag[LN_RING + 2][0][0], 48);
    float z = 0.f;
#pragma unroll
    for (int j = 0; j < C_DIM / 32; j++) z = fmaxf(z, __ldcg(sums + C_DIM + j * 32 + lane));
    const float sc = __uint_as_float((263u - acc_exp(__uint_as_float(__reduce_max_sync(0xffffffffu, __float_as_uint(z))))) << 23);
    const int np = gw % 6 * 64 + lane * 2;
#pragma unroll 2
    for (int cc = 0; cc < 24; cc++) {
        const int c = gw / 6 * 24 + cc;
        uint32_t v[8], o[2][4];
#pragma unroll
        for (int e = 0; e < 8; e++) v[e] = *reinterpret_cast<const uint32_t*>(w2 + (c * 8 + e) * C_DIM + perm32(np));
#pragma unroll
        for (int e = 0; e < 4; e++) {
            const uint2 t = __ldcg(reinterpret_cast<const uint2*>(g_ex) + c * 4 + e);
            const float f0 = __uint_as_float(t.x << 23), f1 = __uint_as_float(t.y << 23);
            o[0][e] = pack_f16(bf_lo(v[2 * e]) * f0 * sc, bf_lo(v[2 * e + 1]) * f1 * sc);
            o[1][e] = pack_f16(bf_hi(v[2 * e]) * f0 * sc, bf_hi(v[2 * e + 1]) * f1 * sc);
        }
#pragma unroll
        for (int j = 0; j < 2; j++)
            g_w2img[0][(((c >> 1) * 48 + (np >> 3)) * 2 + (c & 1)) * 8 + (np & 7) + j] = make_uint4(o[j][0], o[j][1], o[j][2], o[j][3]);
    }
    asm volatile("fence.proxy.async.global;\n" ::: "memory");
    __threadfence();
    __syncwarp();
    if (lane == 0) asm volatile("red.relaxed.gpu.global.add.u32 [%0], 1;\n" ::"l"(&g_img[0]) : "memory");
}

__global__ void __cluster_dims__(2, 1, 1) __launch_bounds__(512, 1)
pass1_kernel(const __grid_constant__ CUtensorMap wmap, const __nv_bfloat16* __restrict__ x, const __nv_bfloat16* __restrict__ dw,
             const __nv_bfloat16* __restrict__ w1, const __nv_bfloat16* __restrict__ w2, const __nv_bfloat16* __restrict__ grn_b, int zero) {
    extern __shared__ __align__(1024) uint8_t smem[];
    const uint32_t sbase = smem_u32(smem);
    const uint32_t bar_full = sbase + P1_OFF_BAR, bar_empty = bar_full + P1_NST * 8, bar_w = bar_empty + P1_NST * 8;
    const uint32_t bar_xfull = bar_w + 24, bar_raw = bar_xfull + 16, bar_done = bar_raw + 16;
    const int tid = threadIdx.x;
    const int warp = __shfl_sync(0xffffffffu, tid >> 5, 0), lane = tid & 31;
    const uint32_t rank = cluster_rank();
    const int cl = blockIdx.x >> 1;
    const bool small = cl >= 4 * NGRP;
    const int nwg = small ? 2 : 3, cb0 = small ? (blockIdx.x - 8 * NGRP) * 2 : (blockIdx.x & 7) * 3;
    uint8_t* const ring = reinterpret_cast<uint8_t*>(g_ln);

    TSTAMP(0, 0);
    TRACEW(110 + warp, 0);

    if (warp >= 12) {
        reg_dec<56>();
        asm volatile("barrier.cluster.arrive.relaxed.aligned;\n" ::: "memory");
        asm volatile("barrier.cluster.wait.aligned;\n" ::: "memory");
        {
            auto ring_row = [&](int p) {
                const int n = (p & 8) * 8 + (lane >> 3) * 8 + (p & 3) * 2 + (p >> 2 & 1);
                return n * 128 + (((lane ^ n) & 7) << 4);
            };
            const uint8_t* xsrc = reinterpret_cast<const uint8_t*>(x) + (size_t)(LN_STEP * 8 + blockIdx.x * 2 + (warp & 1)) * P1_X;
            const uint32_t xbar = bar_xfull + (warp & 1) * 8, xdst = sbase + P1_OFF_X + (warp & 1) * P1_X;
            const uint32_t sdw = sbase + P1_OFF_DW + (lane & 7) * 16;
            uint32_t src = xdst - P1_OFF_X + (lane >> 3) * (C_DIM * 2) + (lane & 7) * 16;
            int row0 = ring_row((blockIdx.x & 7) * 2 + (warp & 1)) ^ 288, slot = blockIdx.x >> 3, used = 0;
            auto next = [&]() {
                xsrc += (size_t)LN_STEP * 8 * P1_X;
                if (elect_one()) {
                    mbar_expect_tx(xbar, P1_X);
                    bulk_g2s(xdst, xsrc, P1_X, xbar);
                }
                __syncwarp();
            };
#pragma unroll 1
            for (int i = -1; i * LN_STEP + (int)(blockIdx.x >> 2) < NT128 && blockIdx.x < 128; i++) {
                if (warp == 14) TRACEW(128 + i, 0);
                const int last = i > 0 ? 3 : i ? 2 + (warp >> 1 & 1) : blockIdx.x < 112 ? 1 : -1;
#pragma unroll 1
                for (int ps = i < 0 ? last - 4 : 0; ps <= last; ps += i < 0 ? 4 : 1) {
                    if (i < 0 && ps > 0) STAMPT(416, 6);
                    if (i < 0 && ps > 0) mbar_wait(bar_raw, 0);
                    if (i < 0 && ps > 0) STAMPT(416, 7);
                    if (ps == 0) {
                        if (used) flag_wait<false>(&g_flag[slot][1][0], used);
                        if (i) mbar_wait(xbar, ~i & 1);
                        else mbar_wait(bar_raw + 8, 0);
                        if (warp == 14) TRACEW(128 + i, 1);
                    }
                    uint32_t v[6][4];
#pragma unroll
                    for (int j = 0; j < 6; j++) lds128(v[j], src + (ps & 3) * (4 * C_DIM * 2) + j * 128);
                    ln_row(v, sdw, [&](uint32_t dep) {
                        if (i == 0 && ps == 1 && lane < 2) mbar_arrive_cluster(mapa(bar_empty, lane) + (dep & zero));
                        if (ps == 3 && i > 0 && (i + 1) * LN_STEP + (blockIdx.x >> 2) < NT128 && !__any_sync(0xffffffffu, dep & zero)) next();
                    });
                    uint8_t* dst = ring + (slot * LN_TILE + (ps & 1) * 4096 + (row0 ^ (ps & 2) * 144));
#pragma unroll
                    for (int j = 0; j < 6; j++)
                        asm volatile("{\n.reg .pred p;\nsetp.ge.s32 p, %5, 0;\n@p st.global.v4.u32 [%0], {%1,%2,%3,%4};\n}\n"
                                     ::"l"(dst + j * 16384), "r"(v[j][0]), "r"(v[j][1]), "r"(v[j][2]), "r"(v[j][3]), "r"(ps) : "memory");
                }
                if (warp == 14) TRACEW(128 + i, 2);
                asm volatile("fence.proxy.async.global;\nfence.acq_rel.cta;\n" ::: "memory");
                if (i < 0) {
                    bar_sync(4, 128);
                    if (warp < 14 || small) break;
                    if (blockIdx.x >= 112 && lane < 2) mbar_arrive_cluster(mapa(bar_empty, lane));
                    row0 ^= 288;
                    slot += 16;
                } else {
                    if (i) mbar_wait(bar_done, ~i & 1);
                    else {
                        src += P1_OFF_X;
                        slot = blockIdx.x >> 2;
                        row0 = ring_row((blockIdx.x & 3) * 4 + (warp & 1) * 2);
                    }
                    __syncwarp();
                    if (lane == 0) mbar_arrive(bar_done);
                    if ((slot += LN_STEP) >= LN_RING) { slot -= LN_RING; used += 12; }
                }
            }
            if ((warp < 14 || small) && lane < 2) mbar_arrive_cluster(mapa(bar_empty, lane));
        }
        if (warp == 12) {
            int prev = 0, t = p1_tile(small ? 0 : cl >> 2, small), next = p1_tile(small ? 1 : (cl >> 2) + NGRP, small);
            const uint32_t rbase = mapa(sbase, lane & 1);
            int i = 0;
#pragma unroll 1
            for (; t < NT128; i++) {
                const int s0 = (i & 1) * 2, par = (i >> 1) & 1;
                const int round = t / LN_RING, slot = t - round * LN_RING;
                const uint8_t* src = ring + slot * LN_TILE + rank * (P1_SLOT / 2);
                int draw = i + 2;
                if (rank == 0 && lane == 0 && !small) draw = 2 * NGRP + atomicAdd(&g_flag[LN_RING + ((cl >> 1) & 1)][cl & 1][0], 1u);
                flag_wait<true>(&g_flag[slot][0][0], 8 * round + 8);
                TRACEW(i, 2);
                if (i == 0) STAMPT(384, 10);
                if (i == 2) STAMPT(384, 13);
                if (i == 3) STAMPT(384, 14);
                asm volatile("fence.proxy.async.global;\n" ::: "memory");
                draw = p1_tile(__shfl_sync(0xffffffffu, draw, 0), small);
#pragma unroll
                for (int h = 0; h < 2; h++) {
                    mbar_wait(bar_empty + (s0 + h) * 8, par);
                    TRACEW(i, 4 + h);
                    if (i == 0 && h == 1) STAMPT(384, 11);
                    if (elect_one()) {
                        mbar_expect_tx(bar_full + (s0 + h) * 8, P1_SLOT + 16 - 16 * h);
                        bulk_g2s_mc(sbase + (s0 + h) * P1_SLOT + rank * (P1_SLOT / 2), src + h * P1_SLOT, P1_SLOT / 2, bar_full + (s0 + h) * 8, (uint16_t)3);
                    }
                    __syncwarp();
                    if (h == 0 && rank == 0 && lane < 2)
                        asm volatile("st.async.shared::cluster.mbarrier::complete_tx::bytes.v4.u32 [%0], {%1, %2, %3, %3}, [%4];\n"
                                     ::"r"(rbase + P1_OFF_TILE + (i & 3) * 16), "r"((t - prev) * (2 * H_TILE)), "r"((int)(next < NT128)), "r"(draw),
                                       "r"(rbase + P1_OFF_BAR + s0 * 8) : "memory");
                }
                prev = t;
                t = next;
                next = draw;
                if (rank != 0) {
                    mbar_wait(bar_full + s0 * 8, (i >> 1) & 1);
                    mbar_wait(bar_full + s0 * 8 + 8, (i >> 1) & 1);
                    if (lane == 0) asm volatile("red.relaxed.gpu.global.add.u32 [%0], %1;\n" ::"l"(&g_flag[slot][1][0]), "r"(nwg) : "memory");
                    asm volatile("ld.shared.u32 %0, [%1];\n" : "=r"(next) : "r"(sbase + P1_OFF_TILE + (i & 3) * 16 + 8) : "memory");
                    TRACEW(i, 3);
                }
            }
#pragma unroll 1
            for (int j = 2 * i; j < 2 * i + 4; j++) mbar_wait(bar_empty + (j & 3) * 8, (j >> 2) & 1);
        } else if (warp == 13) {
            STAMPT(416, 8);
            if (lane == 0 && blockIdx.x < 128) asm volatile("red.release.gpu.global.add.u32 [%0], 1;\n" ::"l"(&g_flag[blockIdx.x >> 3][0][0]) : "memory");
            __syncwarp();
            STAMPT(416, 9);
            const uint32_t ep = g_epoch & 1;
            asm volatile("st.shared.u32 [%0], %1;\n" ::"r"(sbase + P1_OFF_TILE - 4), "r"(ep) : "memory");
            if (blockIdx.x == 18) g_par = ep;
            if (blockIdx.x < 18) reinterpret_cast<float4*>(g_sums[ep ^ 1])[blockIdx.x * 32 + lane] = make_float4(0.f, 0.f, 0.f, 0.f);
#pragma unroll 1
            for (int i = 0; !small && i * LN_STEP + (blockIdx.x >> 2) < NT128; i++) {
                mbar_wait(bar_done, i & 1);
                asm volatile("fence.proxy.async.global;\n" ::: "memory");
                if (lane == 0) {
                    mbar_arrive(bar_done);
                    asm volatile("red.release.gpu.global.add.u32 [%0], %1;\n"
                                 ::"l"(&g_flag[i ? (blockIdx.x >> 2) + i % LN_DEPTH * LN_STEP : 16 + (blockIdx.x >> 3)][0][0]), "r"(i ? 2 : (int)(blockIdx.x < 112)) : "memory");
                }
                __syncwarp();
                TRACEW(128 + i, 3);
            }
            flag_wait<true>(&g_flag[LN_RING + 2][0][0], 48);
        }
    } else {
        if (tid == 0) {
            mbar_init(bar_raw, 1);
            mbar_init(bar_raw + 8, 1);
            mbar_init(bar_xfull, 1);
            mbar_init(bar_xfull + 8, 1);
            for (int i = 0; i < 3; i++) mbar_init(bar_w + i * 8, 1);
            asm volatile("fence.mbarrier_init.release.cluster;\n" ::: "memory");
            if (blockIdx.x < 128) {
                mbar_expect_tx(bar_raw, P1_X + C_DIM * 2);
                bulk_g2s(sbase + P1_OFF_DW, dw, C_DIM * 2, bar_raw);
                for (int i = 0; i < 2; i++) bulk_g2s(sbase + i * P1_X + P1_X / 2, x + (size_t)(blockIdx.x * 16 + i * 8) * C_DIM, P1_X / 2, bar_raw);
                asm volatile("cp.async.bulk.prefetch.L2.global [%0], 9216;\n" ::"l"(w1 + blockIdx.x * 4608) : "memory");
            }
            if (blockIdx.x < 112) {
                mbar_expect_tx(bar_raw + 8, P1_X);
                for (int i = 0; i < 2; i++) bulk_g2s(sbase + i * P1_X, x + (size_t)(16 * 128 + blockIdx.x * 16 + i * 8) * C_DIM, P1_X / 2, bar_raw + 8);
            }
            for (int i = 0; i < nwg; i++) {
                mbar_expect_tx(bar_w + i * 8, P1_SLOT);
                tma2(sbase + (1 + i) * P1_SLOT, &wmap, (cb0 + i) * 64, 0, bar_w + i * 8);
                tma2(sbase + (1 + i) * P1_SLOT + P1_SLOT / 2, &wmap, (cb0 + i) * 64, 192, bar_w + i * 8);
            }
            for (int i = 0; i < 2 && !small; i++) {
                mbar_expect_tx(bar_xfull + i * 8, P1_X);
                bulk_g2s(sbase + P1_OFF_X + i * P1_X, x + (size_t)(LN_STEP * 128 + blockIdx.x * 32 + i * 16) * C_DIM, P1_X, bar_xfull + i * 8);
            }
        }
        if (tid == 32) {
            mbar_init(bar_done, 3);
            mbar_arrive(bar_done);
            asm volatile("fence.mbarrier_init.release.cluster;\n" ::: "memory");
        }
        if (tid == 64) {
            for (int i = 0; i < P1_NST; i++) {
                mbar_init(bar_full + i * 8, 1);
                mbar_init(bar_empty + i * 8, 8 * nwg);
            }
            asm volatile("fence.mbarrier_init.release.cluster;\n" ::: "memory");
            if (blockIdx.x < 64) (&g_half[0][0])[blockIdx.x] = 0;
            else if (blockIdx.x == 64) g_prog = 0;
            else if (blockIdx.x < 67) g_img[blockIdx.x - 65] = 0;
        }
        __syncwarp();
        asm volatile("barrier.cluster.arrive.relaxed.aligned;\n" ::: "memory");
        reg_inc<152>();
        TRACEW(110 + warp, 1);
        const int wg = warp >> 2, w = warp & 3;
        gdc_launch();
        asm volatile("barrier.cluster.wait.aligned;\n" ::: "memory");
        if (wg == nwg) {
            p1_w2(w2, grn_b, w, lane);
            return;
        }
        const uint32_t slot_free = mapa(bar_empty, lane & 1) + (lane >> 1) * 8;
        if (lane < 8 && (lane >> 1) != 1 + wg && (wg || lane > 1)) mbar_arrive_cluster(slot_free);
        if (wg == 1) bar_arrive(1, 256);
        uint32_t a[24][4], ex[2], gen = 0;
        const uint32_t wsrc = sbase + (1 + wg) * P1_SLOT + ((lane >> 4) * 8 + (lane & 7)) * 128 + (((2 * w + ((lane >> 3) & 1)) ^ (lane & 7)) << 4);
#pragma unroll 1
        for (int it = 0; it < 2; it++) {
            if (it) mbar_wait(bar_w + wg * 8, 0);
            TRACEW(110 + warp, 5);
            if (it || wg == 0) {
#pragma unroll
            for (int k = 0; k < 24; k++) ldsm4t(a[k], wsrc + k * 2048);
#pragma unroll
            for (int r = 0; r < 2; r++) {
                float t = 0.f;
#pragma unroll
                for (int j = 0; j < 6; j++) {
                    uint32_t c = bf2_mul(a[4 * j][r], a[4 * j][r]);
#pragma unroll
                    for (int k = 1; k < 8; k++) c = bf2_fma(a[4 * j + k / 2][r + (k & 1) * 2], a[4 * j + k / 2][r + (k & 1) * 2], c);
                    t += bf_lo(c) + bf_hi(c);
                }
                t += __shfl_xor_sync(0xffffffffu, t, 1);
                t += __shfl_xor_sync(0xffffffffu, t, 2);
                asm("sqrt.approx.f32 %0, %0;\n" : "+f"(t));
                ex[r] = min(max(__float_as_uint(13.9f * t) >> 23, 72u), 198u);
            }
            asm volatile("{\n.reg .pred p;\nsetp.gt.u32 p, %1, 7;\nbar.red.or.pred p, %2, 128, p;\nselp.u32 %0, 1, 0, p;\n}\n"
                         : "=r"(gen) : "r"(max(ex[0] - 125u, ex[1] - 125u)), "r"(5 + wg) : "memory");
            gen = __shfl_sync(0xffffffffu, gen, 0) & it;
            if (it) {
                if ((lane & 3) < 2) g_ex[(cb0 + wg) * 64 + w * 16 + (lane & 1) * 8 + (lane >> 2)] = lane & 1 ? ex[1] : ex[0];
                if ((lane >> 1) == 1 + wg) mbar_arrive_cluster(slot_free);
                __syncwarp();
            }
            }
            if (gen) {
#pragma unroll
                for (int k = 0; k < 24; k++)
#pragma unroll
                    for (int j = 0; j < 4; j++) a[k][j] = bf2_mul(a[k][j], (268u - ex[j & 1]) * 0x00800080u);
            }
            if (it || wg == 1) {
#pragma unroll
                for (int k = 0; k < 24; k++)
#pragma unroll
                    for (int j = 0; j < 4; j++) {
                        a[k][j] = bf2_as_h2(bf2_mul(a[k][j], 0x07800780u));
                        asm volatile("" : "+r"(a[k][j]));
                    }
            }
            TRACEW(110 + warp, 6);
        }
#pragma unroll
        for (int j = 0; j < 4; j++)
            asm volatile("st.shared.u32 [%0], %1;\n" ::"r"(sbase + P1_OFF_A + warp * 512 + (j & 1) * 256 + (j >> 1) * 128 + lane * 4), "r"(a[23][j]) : "memory");
        asm volatile("fence.proxy.async.shared::cta;\n" ::: "memory");
        TRACEW(110 + warp, 7);
        const uint32_t ex2 = ex[0] | ex[1] << 16;
        p1_consumer(a, gen ? 0x7f007f00u - (ex2 << 7) : (0x008e008eu - ex2) << 10, gen, sbase, wg, nwg, cb0 + wg, w, lane, zero);
        TSTAMP(0, 30);
    }
}

#define P2_NB_ 5
#define P2_NA_ 5
#define P2_DELTA_ 7
#define P2_EXTRA 0
#define P2_HSLEEP 64
#define P2_PSLEEP 100
#define P2_T0 5
#define P2_TS 11
constexpr int P2_B = 24576, P2_NB = P2_NB_;
constexpr int P2_A = 3072, P2_NA = P2_NA_;
constexpr int P2_XROW = C_DIM * 2;
constexpr int P2_OFF_A = P2_B * P2_NB;
constexpr int P2_OFF_X = P2_OFF_A + 3 * P2_NA * P2_A;
constexpr int P2_XHALF = 32 * P2_XROW + 64;
constexpr int P2_OFF_BIAS = P2_OFF_X + 64 * P2_XROW + 64;
constexpr int P2_OFF_GRN = P2_OFF_BIAS + C_DIM * 4;
constexpr int P2_OFF_BAR = P2_OFF_GRN + HID * 2;
constexpr int P2_SMEM = P2_OFF_BAR + (2 * P2_NB + 6 * P2_NA + 3) * 8;
#define P2_LAG_ 17
constexpr int P2_LAG = P2_LAG_;
constexpr int P2_NCL = NUM_CTAS / 2, P2_ITEMS = NT128 / P2_NCL, P2_SHARED = NT128 - P2_ITEMS * P2_NCL;
constexpr int P2_POS = P2_LAG * (P2_ITEMS - 1) + 48;
__device__ __forceinline__ int p2_start(int n) { return n < 0 ? 0 : n == P2_ITEMS ? P2_POS - 24 : P2_LAG * n; }
constexpr int P2_FOLD = P2_LAG - 1 + (P2_LAG & 1);
constexpr int P2_XC = 8 * P2_XROW;
constexpr int P2_DELTA = P2_DELTA_;
__device__ __forceinline__ int p2_tile(int cl, int n) {
    return n == 0 ? NT128 - 1 - cl : n < 0 || n == P2_ITEMS ? NT128 - 1 - P2_NCL - (cl >> 1) : cl + P2_NCL * (n - 1);
}

constexpr int P2_EG = 2;
__device__ __forceinline__ void p2_epilogue(const uint32_t (&acc0)[48], const uint32_t (&acc1)[48], uint32_t sx, uint32_t sb, float up, int zero) {
    uint32_t v[2][P2_EG][4];
    float b[2][8];
    auto load = [&](int c, uint32_t a) {
#pragma unroll
        for (int j = 0; j < 2; j++)
            asm volatile("ld.shared.v4.f32 {%0,%1,%2,%3}, [%4];\n" : "=f"(b[c & 1][4 * j]), "=f"(b[c & 1][4 * j + 1]), "=f"(b[c & 1][4 * j + 2]), "=f"(b[c & 1][4 * j + 3])
                         : "r"(sb + c * 128 + j * 16) : "memory");
#pragma unroll
        for (int j = 0; j < P2_EG; j++) {
            const int u = c * P2_EG + j;
            asm volatile("ld.shared.v4.u32 {%0,%1,%2,%3}, [%4];\n" : "=r"(v[c & 1][j][0]), "=r"(v[c & 1][j][1]), "=r"(v[c & 1][j][2]), "=r"(v[c & 1][j][3])
                         : "r"(a + (u >> 1) * 64 + (u & 1) * 4 * P2_XROW) : "memory");
        }
    };
    load(0, sx);
#pragma unroll
    for (int c = 0; c < 24 / P2_EG; c++) {
        if (c + 1 < 24 / P2_EG) load(c + 1, sx + (v[c & 1][P2_EG - 1][0] & zero));
#pragma unroll
        for (int j = 0; j < P2_EG; j++) {
            const int u = c * P2_EG + j, i = 8 * ((u >> 1) % 6) + (u & 1);
            const uint32_t (&acc)[48] = u < 12 ? acc0 : acc1;
            uint32_t (&w)[4] = v[c & 1][j];
#pragma unroll
            for (int e = 0; e < 4; e++)
                w[e] = bf2_add(pack_bf16(fmaf(h_lo(acc[i + 2 * e]), up, b[c & 1][2 * e]), fmaf(h_hi(acc[i + 2 * e]), up, b[c & 1][2 * e + 1])), w[e]);
            asm volatile("st.shared.v4.u32 [%4], {%0,%1,%2,%3};\n" ::"r"(w[0]), "r"(w[1]), "r"(w[2]), "r"(w[3]),
                         "r"(sx + (u >> 1) * 64 + (u & 1) * 4 * P2_XROW) : "memory");
        }
    }
}

__device__ __forceinline__ void p2_unpack(uint4& u, uint32_t o1, uint32_t o2, uint32_t o3) {
    u.z = o1 & 0xbff8bff8u;
    u.y = o2 & 0xbff8bff8u;
    u.w = o3 & 0xbff8bff8u;
    u.x = (__byte_perm(o1, 0, 0x2301) & 0x07400740u) | ((__byte_perm(o2, o3, 0x6240) << 3) & 0x38383838u) | ((__byte_perm(o2, o3, 0x3715) << 1) & 0x80808080u);
}
__device__ __forceinline__ uint32_t h2_mul(uint32_t a, uint32_t b) {
    uint32_t r;
    asm("mul.rn.f16x2 %0, %1, %2;\n" : "=r"(r) : "r"(a), "r"(b));
    return r;
}
__device__ __forceinline__ void p2_epilogue_add(const uint32_t (&acc)[48], uint8_t* o, float f, int zero) {
#pragma unroll
    for (int t = 0; t < 12; t++) {
        uint32_t v[4];
#pragma unroll
        for (int e = 0; e < 4; e++) {
            v[e] = acc[8 * (t >> 1) + (t & 1) + 2 * e];
            asm volatile("" : "+r"(v[e]));
            v[e] = pack_bf16(h_lo(v[e]) * f, h_hi(v[e]) * f);
        }
        asm volatile("red.global.add.noftz.v4.bf16x2 [%0], {%1,%2,%3,%4};\n" ::"l"(o + (t >> 1) * 64 + (t & 1) * 4 * P2_XROW),
                     "r"(v[0]), "r"(v[1]), "r"(v[2]), "r"(v[3]) : "memory");
        if (t % 3 == 2) sched_break(zero);
    }
}

__global__ void __cluster_dims__(2, 1, 1) __launch_bounds__(512, 1)
pass2_kernel(const __nv_bfloat16* __restrict__ x, const __nv_bfloat16* __restrict__ grn_g, __nv_bfloat16* __restrict__ out, int zero) {
    extern __shared__ __align__(1024) uint8_t smem[];
    const uint32_t sbase = smem_u32(smem);
    const uint32_t bar_bfull = sbase + P2_OFF_BAR, bar_bempty = bar_bfull + P2_NB * 8;
    const uint32_t bar_afull = bar_bempty + P2_NB * 8, bar_aempty = bar_afull + 3 * P2_NA * 8;
    const uint32_t bar_xfull = bar_aempty + 3 * P2_NA * 8, bar_oready = bar_xfull + 8, s_pos = bar_xfull + 16;
    int tid;
    asm volatile("mov.u32 %0, %%tid.x;\n" : "=r"(tid));
    const int warp = __shfl_sync(0xffffffffu, tid >> 5, 0), lane = tid & 31;
    const uint32_t rank = cluster_rank();
    const int cl = blockIdx.x >> 1, pair = cl >> 1;
    const int k0 = (4 * pair + (cl & 1) * (48 - P2_POS % 48)) % 48;
    const int head = pair < P2_SHARED && !(cl & 1), tail = pair < P2_SHARED && (cl & 1);

    uint32_t par, gg[4];
    float pre[4];
    if (warp < 12) {
        asm volatile("ld.global.cg.u32 %0, [%1];\n" : "=r"(par) : "l"(&g_par) : "memory");
#pragma unroll
        for (int i = 0; i < 4; i++) {
            asm volatile("ld.global.cg.f32 %0, [%1];\n" : "=f"(pre[i]) : "l"(&g_sums[i & 1][HID + (i >> 1) * C_DIM + tid]) : "memory");
            asm volatile("ld.global.nc.u16 %0, [%1];\n" : "=r"(gg[i]) : "l"(grn_g + tid + 384 * i) : "memory");
        }
    }
    TSTAMP(1, 0);
    if (tid == 384) {
        for (int i = 0; i < P2_NB; i++) {
            mbar_init(bar_bfull + i * 8, 1);
            mbar_init(bar_bempty + i * 8, 24);
        }
        for (int i = 0; i < 3 * P2_NA; i++) {
            mbar_init(bar_afull + i * 8, 1);
            mbar_init(bar_aempty + i * 8, 4);
        }
        mbar_init(bar_xfull, 2);
        mbar_init(bar_oready, 4);
        asm volatile("st.shared.u32 [%0], 0;\n" ::"r"(s_pos) : "memory");
        asm volatile("fence.mbarrier_init.release.cluster;\n" ::: "memory");
    }
    __syncthreads();
    cluster_sync_relaxed();

    if (warp >= 12) {
        reg_dec<32>();
        if (warp == 12) {
            const uint8_t* wsrc = reinterpret_cast<const uint8_t*>(g_w2img) + rank * (P2_B / 2);
            int st = 0, ph = 1, kb = k0, m = 0, r = 0;
            const int busy = head ? 0 : tail ? P2_POS - 24 : P2_POS;
#pragma unroll 1
            for (int p = 0; p < P2_POS; p++) {
                if (p == 0 || p == P2_FOLD) {
                    flag_wait<true>(&g_img[p != 0], p ? 96 * 4 : 48);
                    asm volatile("fence.proxy.async.global;\n" ::: "memory");
                    if (p) wsrc += sizeof(g_w2img[0]);
                }
                mbar_wait(bar_bempty + st * 8, ph);
                TR2P(p, 0);
                if (elect_one()) {
                    mbar_expect_tx(bar_bfull + st * 8, P2_B);
                    bulk_g2s_mc(sbase + st * P2_B + rank * (P2_B / 2), wsrc + kb * P2_B, P2_B / 2, bar_bfull + st * 8, (uint16_t)3);
                    asm volatile("st.volatile.shared.u32 [%0], %1;\n" ::"r"(s_pos), "r"(p) : "memory");
                    const int idle = 2 - min(m, P2_ITEMS - 1) + max(m - 2 + (r >= 48 - 2 * P2_LAG), 0) - ((unsigned)(p - busy) < 24);
                    if (idle) asm volatile("mbarrier.arrive.shared::cta.b64 _, [%0], %1;\n" ::"r"(bar_bempty + st * 8), "r"(idle * 8) : "memory");
                    if (rank == 0) asm volatile("red.relaxed.gpu.global.add.u32 [%0], 1;\n" ::"l"(&g_prog) : "memory");
                }
                __syncwarp();
                if (++st == P2_NB) { st = 0; ph ^= 1; }
                if (++kb == 48) kb = 0;
                if (++r == P2_LAG) { r = 0; m++; }
            }
            mbar_wait(bar_bempty + st * 8, ph);
            if (lane == 0) mbar_arrive(bar_bfull + st * 8);
#pragma unroll 1
            for (int p = 1; p < P2_NB; p++) {
                if (++st == P2_NB) { st = 0; ph ^= 1; }
                mbar_wait(bar_bempty + st * 8, ph);
            }
        } else if (warp == 13) {
            const uint8_t* src[3];
            int n[3], left[3], wrap[3];
            uint32_t st[3];
            auto item = [&](int w) {
                const int u = (k0 + p2_start(n[w])) % 48;
                left[w] = n[w] < 0 || n[w] == P2_ITEMS ? 24 : 48;
                wrap[w] = left[w] - (48 - u);
                src[w] = reinterpret_cast<const uint8_t*>(g_h) + (size_t)p2_tile(cl, n[w]) * (2 * H_TILE) + rank * H_HALF + u * H_STEP;
            };
#pragma unroll
            for (int w = 0; w < 3; w++) {
                n[w] = w == 2 && head ? -1 : w;
                st[w] = 0x80000000u;
                item(w);
            }
            gdc_wait();
#pragma unroll 1
            for (int done = 0; done < 3;) {
                bool idle = true;
#pragma unroll
                for (int w = 0; w < 3; w++) {
                    const uint32_t o = (st[w] & 0xff) + w * P2_NA * 8;
                    if (left[w] >= 0 && mbar_test(bar_aempty + o, st[w] >> 31)) {
                        idle = false;
                        if (left[w] == 0) {
                            if (lane == 0) mbar_arrive(bar_afull + o);
                            left[w] = -1;
                            done++;
                        } else {
                            if (elect_one()) {
                                mbar_expect_tx(bar_afull + o, P2_A);
                                bulk_g2s(sbase + P2_OFF_A + o * (P2_A / 8), src[w], P2_A, bar_afull + o);
                            }
                            __syncwarp();
                            src[w] += H_STEP;
                            st[w] += 8;
                            if ((st[w] & 0xff) == P2_NA * 8) st[w] ^= 0x80000000u | (P2_NA * 8);
                            if (--left[w] == wrap[w]) src[w] -= 48 * H_STEP;
                            if (left[w] == 0 && (n[w] += 3) < P2_ITEMS + tail) item(w);
                        }
                    }
                }
                if (idle) __nanosleep(P2_HSLEEP);
                SAFE_BREAK
            }
        } else if (warp == 14) {
            const uint32_t sx = sbase + P2_OFF_X;
            size_t o = 0;
            auto pace = [&](int target) {
                int v;
                while (true) {
                    asm volatile("ld.volatile.shared.u32 %0, [%1];\n" : "=r"(v) : "r"(s_pos) : "memory");
                    if (v * 16 >= target) break;
                    __nanosleep(P2_PSLEEP);
                    SAFE_BREAK
                }
            };
#pragma unroll 1
            for (int n = -head; n <= P2_ITEMS; n++) {
                const size_t on = (size_t)(2 * p2_tile(cl, n) + rank) * (64 * C_DIM * 2);
                const bool st = n + head > 0, ld = n < P2_ITEMS;
                if (st) mbar_wait(bar_oready, (n - 1 + head) & 1);
                TR2P(n + 1, 1);
                if (lane == 0) {
                    if (n == 1 && head) {
                        asm volatile("cp.async.bulk.wait_group 0;\nfence.proxy.async.global;\n" ::: "memory");
                        asm volatile("st.release.gpu.global.u32 [%0], 1;\n" ::"l"(&g_half[pair][rank]) : "memory");
                    }
                    if (ld) mbar_expect_tx(bar_xfull, 64 * C_DIM * 2);
                    int t = st && n < P2_ITEMS - 1 ? (P2_LAG * (n - 1) + 48 + P2_T0 - 1) * 16 : -1024;
#pragma unroll 1
                    for (int c = 0; st && c < 64 * P2_XROW; c += P2_XC) {
                        pace(t += P2_TS);
                        bulk_s2g(reinterpret_cast<uint8_t*>(out) + o + c, sx + c + (c >= 32 * P2_XROW ? 64 : 0), P2_XC);
                    }
                    asm volatile("cp.async.bulk.commit_group;\ncp.async.bulk.wait_group.read 0;\n" ::: "memory");
#pragma unroll 1
                    for (int c = 0; ld && c < 64 * P2_XROW; c += P2_XC) {
                        pace(t += P2_TS);
                        bulk_g2s(sx + c + (c >= 32 * P2_XROW ? 64 : 0), reinterpret_cast<const uint8_t*>(x) + on + c, P2_XC, bar_xfull);
                    }
                    TR2P(n + 1, 2);
                    if (rank == 0 && n > 0 && n < P2_ITEMS - 2)
                        flag_wait<false>(&g_prog, P2_NCL * (P2_LAG * n + 48 + P2_EXTRA) + (tail ? P2_SHARED - P2_NCL : P2_SHARED) * P2_DELTA);
                    if (ld) mbar_arrive(bar_xfull);
                    TR2P(n + 1, 3);
                }
                __syncwarp();
                o = on;
            }
            asm volatile("cp.async.bulk.wait_group 0;\n" ::: "memory");
            TR2P(30, 1);
        }
    } else {
        reg_inc<160>();
        const int wg = warp >> 2, w = warp & 3, g = lane >> 2, q = lane & 3;
        const uint32_t sx = sbase + P2_OFF_X + (g & 1) * P2_XHALF + (w * 8 + (g >> 1)) * P2_XROW + q * 16;
        const uint32_t af = bar_afull + wg * P2_NA * 8;
        const uint32_t s_a = sbase + P2_OFF_A + wg * P2_NA * P2_A + (lane >> 3) * 512 + (lane & 7) * 64 +
                             ((w ^ ((lane & 7) >> 1)) << 4);
        uint32_t acc0[48], acc1[48];
        float up;
        uint4 a0[2], a1[2];
        uint32_t st = 0, ph = 0;

        {
            float4* s_red = reinterpret_cast<float4*>(smem + P2_OFF_BIAS);
            const float* sums = g_sums[par];
            float gx[4], part = 0.f, mx = 0.f;
            TSTAMP(1, 27);
            gdc_wait();
            TSTAMP(1, 1);
#pragma unroll
            for (int i = 0; i < 4; i++) gx[i] = __ldcg(sums + tid + 384 * i);
            if (blockIdx.x == 120 && tid < (LN_RING + 3) * 2) (&g_flag[0][0][0])[tid * 8] = 0;
            if (blockIdx.x == 121 && tid == 0) atomicAdd(&g_epoch, 1u);
            float z = __uint_as_float(__reduce_max_sync(0xffffffffu, __float_as_uint(pre[2] + pre[3])));
#pragma unroll
            for (int i = 0; i < 4; i++) {
                asm("sqrt.approx.f32 %0, %1;\n" : "=f"(gx[i]) : "f"(fmaf(gx[i], HSCALE * HSCALE, 1e-6f)));
                part += gx[i];
                gx[i] *= bf_lo(gg[i]);
                mx = fmaxf(mx, fabsf(gx[i]));
            }
#pragma unroll
            for (int o = 16; o > 0; o >>= 1) part += __shfl_xor_sync(0xffffffffu, part, o);
            mx = __uint_as_float(__reduce_max_sync(0xffffffffu, __float_as_uint(mx)));
            TSTAMP(1, 26);
            if (lane == 0) s_red[warp] = make_float4(part, mx, z, 0.f);
            bar_sync(1, 384);
            float tot = 0.f;
            {
                const float4 t = s_red[min(lane & 15, 11)];
                tot = (lane & 15) < 12 ? t.x : 0.f;
#pragma unroll
                for (int o = 8; o > 0; o >>= 1) tot += __shfl_xor_sync(0xffffffffu, tot, o);
                mx = __uint_as_float(__reduce_max_sync(0xffffffffu, __float_as_uint(t.y)));
                z = __uint_as_float(__reduce_max_sync(0xffffffffu, __float_as_uint(t.z)));
            }
            const float inv = __fdividef(1.0f, fmaf(tot, 1.0f / HID, 1e-6f));
            const uint32_t j = max(__float_as_uint(fmaf(mx, inv, 1.0f) * 1.01f) >> 23, 130u) - 130u;
            const float dn = __uint_as_float((127u - j) << 23);
#pragma unroll
            for (int i = 0; i < 4; i++)
                *reinterpret_cast<uint16_t*>(smem + P2_OFF_GRN + (tid + 384 * i) * 2) = pack_f16(fmaf(gx[i], inv, 1.0f) * dn, 0.f);
            up = (HSCALE * 1.00235f) * __uint_as_float(min(acc_exp(z) - 9u + j, 253u) << 23);
            TSTAMP(1, 25);
            bar_sync(1, 384);
            reinterpret_cast<float*>(smem + P2_OFF_BIAS)[tid] = pre[0] + pre[1];
            if (wg == 1 && blockIdx.x < 96) {
                const uint4* src = g_w2img[0] + blockIdx.x * 768 + tid - 128;
                const uint4 fk = *reinterpret_cast<const uint4*>(smem + P2_OFF_GRN + blockIdx.x * 32 + (tid & 8) * 2);
                uint4 v[6];
#pragma unroll
                for (int i = 0; i < 6; i++) v[i] = __ldcg(src + i * 128);
                auto fold = [&](uint32_t b, uint32_t f) { return (h2_mul(b, f) + 0x00040004u) & 0xfff8fff8u; };
#pragma unroll
                for (int i = 0; i < 6; i++)
                    g_w2img[1][blockIdx.x * 768 + tid - 128 + i * 128] = make_uint4(fold(v[i].x, fk.x), fold(v[i].y, fk.y), fold(v[i].z, fk.z), fold(v[i].w, fk.w));
                asm volatile("fence.proxy.async.global;\n" ::: "memory");
                __threadfence();
                __syncwarp();
                if (lane == 0) asm volatile("red.release.gpu.global.add.u32 [%0], 1;\n" ::"l"(&g_img[1]) : "memory");
            }
        }
        TSTAMP(1, 28);
        int kt = k0, pos;
        const uint32_t be = lane < 2 ? mapa(bar_bempty, lane) : 0, be0 = mapa(bar_bempty, 0);
        uint32_t prev = 0, sa = 0, pa = 0;
        auto release_b = [&](uint32_t p, bool on) {
            asm volatile("{\n.reg .pred p, q;\nsetp.ne.u32 q, %2, 0;\nsetp.ne.and.u32 p, %1, 0, q;\n@p mbarrier.arrive.shared::cluster.b64 _, [%0];\n}\n"
                         ::"r"(be + p), "r"(be), "r"((uint32_t)on) : "memory");
        };
        auto arrive1 = [&](uint32_t bar) {
            asm volatile("{\n.reg .pred p;\nsetp.eq.u32 p, %1, %2;\n@p mbarrier.arrive.shared::cta.b64 _, [%0];\n}\n" ::"r"(bar), "r"(be), "r"(be0) : "memory");
        };
        auto seek = [&](int p) {
            pos = p;
            st = p % P2_NB * 8;
            ph = p / P2_NB & 1;
            int v;
            while (true) {
                asm volatile("ld.volatile.shared.u32 %0, [%1];\n" : "=r"(v) : "r"(s_pos) : "memory");
                if (__all_sync(0xffffffffu, v >= p)) break;
                __nanosleep(200);
                SAFE_BREAK
            }
        };
        bool ok_a = false;
        auto fetch = [&](uint4 (&a)[2], uint32_t done, bool rel, bool early) {
            if (!ok_a) mbar_wait(af + sa, pa);
            uint32_t o[6];
            const uint32_t src = s_a + sa * (P2_A / 8);
            asm volatile("ldmatrix.sync.aligned.m8n8.x4.trans.shared.b16 {%0,%1,%2,%3}, [%4];\n"
                         : "=r"(o[0]), "=r"(o[1]), "=r"(o[2]), "=r"(o[3]) : "r"(src) : "memory");
            asm volatile("ldmatrix.sync.aligned.m8n8.x2.trans.shared.b16 {%0,%1}, [%2];\n"
                         : "=r"(o[4]), "=r"(o[5]) : "r"(src + 2048) : "memory");
            if ((sa += 8) == P2_NA * 8) { sa = 0; pa ^= 1; }
            wg_wait<1>();
            release_b(done, rel);
            ok_a = mbar_test(af + sa, pa);
            const bool ok_b = mbar_test(bar_bfull + st, ph);
            p2_unpack(a[0], o[0], o[1], o[2]);
            p2_unpack(a[1], o[3], o[4], o[5]);
            if (early) {
                const uint32_t* t = reinterpret_cast<const uint32_t*>(smem + P2_OFF_GRN) + kt * 16 + q;
#pragma unroll
                for (int i = 0; i < 2; i++)
                    a[i] = make_uint4(h2_mul(a[i].x, t[8 * i]), h2_mul(a[i].y, t[8 * i]), h2_mul(a[i].z, t[8 * i + 4]), h2_mul(a[i].w, t[8 * i + 4]));
                if (++kt == 48) kt = 0;
            }
            if (!ok_b) mbar_wait(bar_bfull + st, ph);
        };
        const uint64_t db0 = make_desc(sbase, 128, 256);
        auto step = [&](const uint4 (&a)[2], uint4 (&an)[2], bool cont, bool early) {
            TR2(0);
            const uint64_t db = db0 + st * (P2_B / 128);
            wg_fence();
            mma_rs_n192(acc0, a[0], db, cont);
            mma_rs_n192(acc1, a[0], db + 384, cont);
            mma_rs_n192(acc0, a[1], db + 768, 1);
            mma_rs_n192(acc1, a[1], db + 768 + 384, 1);
            wg_commit();
            arrive1(af + 3 * P2_NA * 8 - 8 + (sa ? sa : P2_NA * 8));
            const uint32_t done = prev;
            prev = st;
            if ((st += 8) == P2_NB * 8) { st = 0; ph ^= 1; }
            fetch(an, done, cont, early);
            pos++;
        };
        int n = wg == 2 && head ? -1 : wg;
        seek(p2_start(n));
        fetch(a0, 0, false, n <= 0);
#pragma unroll 1
        for (;; n += 3) {
            TSTAMP(1, 2 + n);
            const int p0 = n < 0 || n == P2_ITEMS ? 12 : 0, pe = n <= 0 ? p0 + P2_FOLD / 2 : 0;
            const bool more = n + 3 < P2_ITEMS + tail;
#pragma unroll 1
            for (int p = p0; p < 24; p++) {
                step(a0, a1, p != p0, p < pe);
                step(a1, a0, true, p < pe);
            }
            if (n == P2_ITEMS) {
                flag_wait<true>(&g_half[pair][rank], 1);
                TR2(1);
                wg_wait<0>();
                TR2(2);
                release_b(prev, true);
                uint8_t* o = reinterpret_cast<uint8_t*>(out) + (size_t)((2 * p2_tile(cl, -1) + rank) * 64 + (g & 1) * 32 + w * 8 + (g >> 1)) * P2_XROW + q * 16;
                p2_epilogue_add(acc0, o, up, zero);
                p2_epilogue_add(acc1, o + 384, up, zero);
                TR2(3);
                break;
            }
            mbar_wait(bar_xfull, (n + head) & 1);
            TR2(1);
            wg_wait<0>();
            TR2(2);
            release_b(prev, true);
            p2_epilogue(acc0, acc1, sx, sbase + P2_OFF_BIAS + q * 32, up, zero);
            TR2(3);
            asm volatile("fence.proxy.async.shared::cta;\n" ::: "memory");
            __syncwarp();
            arrive1(bar_oready);
            if (!more) break;
            ok_a = false;
            seek(p2_start(n + 3));
            mbar_wait(bar_bfull + st, ph);
        }
        TSTAMP(1, 30);
    }
}

}

extern "C" void kernel_launch(void* const* d_in, const int* in_sizes, int n_in, void* d_out, int out_size) {
    const __nv_bfloat16* x = (const __nv_bfloat16*)d_in[0];
    const __nv_bfloat16* dw = (const __nv_bfloat16*)d_in[1];
    const __nv_bfloat16* w1 = (const __nv_bfloat16*)d_in[2];
    const __nv_bfloat16* w2 = (const __nv_bfloat16*)d_in[3];
    const __nv_bfloat16* grn_g = (const __nv_bfloat16*)d_in[4];
    const __nv_bfloat16* grn_b = (const __nv_bfloat16*)d_in[5];
    __nv_bfloat16* out = (__nv_bfloat16*)d_out;

    cudaFuncSetAttribute(pass1_kernel, cudaFuncAttributeMaxDynamicSharedMemorySize, P1_SMEM);
    cudaFuncSetAttribute(pass2_kernel, cudaFuncAttributeMaxDynamicSharedMemorySize, P2_SMEM);

    typedef CUresult (*EncodeFn)(CUtensorMap*, CUtensorMapDataType, cuuint32_t, void*, const cuuint64_t*, const cuuint64_t*,
                                 const cuuint32_t*, const cuuint32_t*, CUtensorMapInterleave, CUtensorMapSwizzle,
                                 CUtensorMapL2promotion, CUtensorMapFloatOOBfill);
    static EncodeFn encode = nullptr;
    if (!encode) {
        cudaDriverEntryPointQueryResult qres;
        cudaGetDriverEntryPoint("cuTensorMapEncodeTiled", (void**)&encode, cudaEnableDefault, &qres);
    }
    CUtensorMap wmap;
    const cuuint64_t gdim[2] = {HID, C_DIM};
    const cuuint64_t gstr[1] = {HID * 2};
    const cuuint32_t box[2] = {64, 192}, estr[2] = {1, 1};
    CUresult er = encode(&wmap, CU_TENSOR_MAP_DATA_TYPE_BFLOAT16, 2, (void*)w1, gdim, gstr, box, estr, CU_TENSOR_MAP_INTERLEAVE_NONE,
           CU_TENSOR_MAP_SWIZZLE_128B, CU_TENSOR_MAP_L2_PROMOTION_L2_128B, CU_TENSOR_MAP_FLOAT_OOB_FILL_NONE);
    if (er != CUDA_SUCCESS) printf("tensor map encode failed %d\n", (int)er);

    pass1_kernel<<<NUM_CTAS, 512, P1_SMEM>>>(wmap, x, dw, w1, w2, grn_b, 0);

    cudaLaunchAttribute attr[1];
    attr[0].id = cudaLaunchAttributeProgrammaticStreamSerialization;
    attr[0].val.programmaticStreamSerializationAllowed = 1;
    cudaLaunchConfig_t cfg = {};
    cfg.gridDim = dim3(NUM_CTAS);
    cfg.stream = 0;
    cfg.attrs = attr;
    cfg.numAttrs = 1;
    cfg.blockDim = dim3(512);
    cfg.dynamicSmemBytes = P2_SMEM;
    cudaLaunchKernelEx(&cfg, pass2_kernel, x, grn_g, out, 0);
}
```

```cpp
#include <cuda.h>
#include <cuda_runtime.h>
#include <cuda_bf16.h>
#include <stdint.h>
#include <stdio.h>

namespace {

constexpr int M_TOTAL = 384 * 384;
constexpr int C_DIM   = 384;
constexpr int HID     = 1536;
constexpr int NT128   = M_TOTAL / 128;
constexpr int NUM_CTAS = 132;

constexpr int NGRP = 15;
constexpr int LN_STEP = 2 * NGRP, LN_RING = 2 * LN_STEP;
#define P1_M 101
#define P1_D 10
__device__ __forceinline__ int p1_tile(int t, bool small) {
    return t + (small ? ((t + 1) * P1_M + P1_D - 1) / P1_D : t * P1_D / P1_M);
}
constexpr int LN_TILE = 128 * C_DIM * 2;
constexpr int H_TILE = 64 * HID * 3 / 2;
constexpr int H_HALF = 3072, H_STEP = 6144;

__device__ __align__(1024) uint4 g_h[(size_t)M_TOTAL * HID * 3 / 32];
__device__ __align__(1024) uint4 g_ln[LN_RING * LN_TILE / 16];
__device__ __align__(1024) uint4 g_w2img[2][HID * C_DIM * 2 / 16];
__device__ __align__(16) float g_sums[2][HID + 2 * C_DIM];
__device__ __align__(16) unsigned g_ex[HID];
__device__ unsigned g_epoch, g_par;
__device__ __align__(128) unsigned g_img[2];
__device__ __align__(128) unsigned g_prog;
__device__ __align__(128) unsigned g_half[32][2];
__device__ unsigned g_flag[LN_RING + 3][2][8];
#define TSTAMP(k, i)
#define STAMPT(t, i)
#define TRACE(wg, pos, i)
#define TRACEW(pos, i)

#define TR2(i)
#define TR2P(pos, i)
__host__ __device__ __forceinline__ int perm32(int n) {
    return (n & ~31) | (((n >> 1) & 3) << 3) | (((n >> 3) & 3) << 1) | (n & 1);
}

__device__ __forceinline__ uint32_t smem_u32(const void* p) { return (uint32_t)__cvta_generic_to_shared(p); }

__device__ __forceinline__ void mbar_init(uint32_t bar, uint32_t count) {
    asm volatile("mbarrier.init.shared::cta.b64 [%0], %1;\n" ::"r"(bar), "r"(count) : "memory");
}
__device__ __forceinline__ void mbar_expect_tx(uint32_t bar, uint32_t bytes) {
    asm volatile("mbarrier.arrive.expect_tx.shared::cta.b64 _, [%0], %1;\n" ::"r"(bar), "r"(bytes) : "memory");
}
__device__ __forceinline__ void mbar_arrive(uint32_t bar) {
    asm volatile("mbarrier.arrive.shared::cta.b64 _, [%0];\n" ::"r"(bar) : "memory");
}
__device__ __forceinline__ void mbar_arrive_cluster(uint32_t bar_cluster_addr) {
    asm volatile("mbarrier.arrive.shared::cluster.b64 _, [%0];\n" ::"r"(bar_cluster_addr) : "memory");
}
#define SAFE_BREAK
__device__ __forceinline__ void mbar_wait(uint32_t bar, uint32_t parity) {
    asm volatile(
        "{\n"
        ".reg .pred p;\n"
        "LAB_WAIT:\n"
        "mbarrier.try_wait.parity.shared::cta.b64 p, [%0], %1;\n"
        "@!p bra LAB_WAIT;\n"
        "}\n" ::"r"(bar), "r"(parity) : "memory");
}
__device__ __forceinline__ bool mbar_test(uint32_t bar, uint32_t parity) {
    uint32_t ok;
    asm volatile("{\n.reg .pred p;\n"
                 "mbarrier.test_wait.parity.shared::cta.b64 p, [%1], %2;\n"
                 "selp.u32 %0, 1, 0, p;\n}\n" : "=r"(ok) : "r"(bar), "r"(parity) : "memory");
    return ok != 0;
}
__device__ __forceinline__ uint32_t mapa(uint32_t addr, uint32_t rank) {
    uint32_t r;
    asm volatile("mapa.shared::cluster.u32 %0, %1, %2;\n" : "=r"(r) : "r"(addr), "r"(rank));
    return r;
}
__device__ __forceinline__ void bulk_g2s(uint32_t dst, const void* src, uint32_t bytes, uint32_t bar) {
    asm volatile("cp.async.bulk.shared::cluster.global.mbarrier::complete_tx::bytes [%0], [%1], %2, [%3];\n"
                 ::"r"(dst), "l"(src), "r"(bytes), "r"(bar) : "memory");
}
__device__ __forceinline__ void bulk_g2s_mc(uint32_t dst, const void* src, uint32_t bytes, uint32_t bar, uint16_t mask) {
    asm volatile("cp.async.bulk.shared::cluster.global.mbarrier::complete_tx::bytes.multicast::cluster [%0], [%1], %2, [%3], %4;\n"
                 ::"r"(dst), "l"(src), "r"(bytes), "r"(bar), "h"(mask) : "memory");
}
__device__ __forceinline__ void tma2(uint32_t dst, const CUtensorMap* map, int c0, int c1, uint32_t bar) {
    asm volatile("cp.async.bulk.tensor.2d.shared::cluster.global.tile.mbarrier::complete_tx::bytes [%0], [%1, {%2, %3}], [%4];\n"
                 ::"r"(dst), "l"(map), "r"(c0), "r"(c1), "r"(bar) : "memory");
}
template <bool ACQ>
__device__ __forceinline__ uint32_t flag_wait(const unsigned* p, unsigned target) {
    unsigned v, n = 0;
    do {
        if (ACQ) asm volatile("ld.acquire.gpu.global.u32 %0, [%1];\n" : "=r"(v) : "l"(p) : "memory");
        else asm volatile("ld.relaxed.gpu.global.u32 %0, [%1];\n" : "=r"(v) : "l"(p) : "memory");
        n++;
    } while (v < target);
    return n == 1;
}
__device__ __forceinline__ void ldsm4t(uint32_t (&r)[4], uint32_t addr) {
    asm volatile("ldmatrix.sync.aligned.m8n8.x4.trans.shared.b16 {%0,%1,%2,%3}, [%4];\n"
                 : "=r"(r[0]), "=r"(r[1]), "=r"(r[2]), "=r"(r[3]) : "r"(addr) : "memory");
}
__device__ __forceinline__ void bulk_s2g(void* dst, uint32_t src, uint32_t bytes) {
    asm volatile("cp.async.bulk.global.shared::cta.bulk_group [%0], [%1], %2;\n" ::"l"(dst), "r"(src), "r"(bytes) : "memory");
}
__device__ __forceinline__ void cluster_sync_relaxed() {
    asm volatile("barrier.cluster.arrive.relaxed.aligned;\nbarrier.cluster.wait.aligned;\n" ::: "memory");
}
__device__ __forceinline__ void gdc_wait() { asm volatile("griddepcontrol.wait;\n" ::: "memory"); }
__device__ __forceinline__ void gdc_launch() { asm volatile("griddepcontrol.launch_dependents;\n" ::: "memory"); }
__device__ __forceinline__ uint32_t cluster_rank() {
    uint32_t r;
    asm volatile("mov.u32 %0, %%cluster_ctarank;\n" : "=r"(r));
    return r;
}
__device__ __forceinline__ bool elect_one() {
    uint32_t pred;
    asm volatile("{\n.reg .pred p;\nelect.sync _|p, 0xffffffff;\nselp.u32 %0, 1, 0, p;\n}\n" : "=r"(pred));
    return pred != 0;
}
__device__ __forceinline__ void wg_fence() { asm volatile("wgmma.fence.sync.aligned;\n" ::: "memory"); }
__device__ __forceinline__ void wg_commit() { asm volatile("wgmma.commit_group.sync.aligned;\n" ::: "memory"); }
template <int N> __device__ __forceinline__ void wg_wait() {
    asm volatile("wgmma.wait_group.sync.aligned %0;\n" ::"n"(N) : "memory");
}
template <int R> __device__ __forceinline__ void reg_inc() { asm volatile("setmaxnreg.inc.sync.aligned.u32 %0;\n" ::"n"(R)); }
template <int R> __device__ __forceinline__ void reg_dec() { asm volatile("setmaxnreg.dec.sync.aligned.u32 %0;\n" ::"n"(R)); }
__device__ __forceinline__ void bar_sync(int id, int n) { asm volatile("bar.sync %0, %1;\n" ::"r"(id), "r"(n) : "memory"); }
__device__ __forceinline__ void bar_arrive(int id, int n) { asm volatile("bar.arrive %0, %1;\n" ::"r"(id), "r"(n) : "memory"); }

__device__ __forceinline__ uint64_t make_desc(uint32_t saddr, uint32_t lbo, uint32_t sbo) {
    return (uint64_t)((saddr & 0x3FFFF) >> 4) | ((uint64_t)(lbo >> 4) << 16) | ((uint64_t)(sbo >> 4) << 32);
}

__device__ __forceinline__ void stg128_cs(void* p, uint32_t a, uint32_t b, uint32_t c, uint32_t d) {
    asm volatile("st.global.cs.v4.u32 [%0], {%1,%2,%3,%4};\n" ::"l"(p), "r"(a), "r"(b), "r"(c), "r"(d) : "memory");
}
__device__ __forceinline__ uint32_t pack_bf16(float lo, float hi) {
    uint32_t r;
    asm("cvt.rn.bf16x2.f32 %0, %1, %2;\n" : "=r"(r) : "f"(hi), "f"(lo));
    return r;
}
__device__ __forceinline__ float bf_lo(uint32_t v) { return __uint_as_float(v << 16); }
__device__ __forceinline__ float bf_hi(uint32_t v) { return __uint_as_float(v & 0xffff0000u); }
__device__ __forceinline__ uint32_t bf2_mul(uint32_t a, uint32_t b) {
    uint32_t r;
    asm("mul.rn.bf16x2 %0, %1, %2;\n" : "=r"(r) : "r"(a), "r"(b));
    return r;
}
__device__ __forceinline__ uint32_t bf2_fma(uint32_t a, uint32_t b, uint32_t c) {
    uint32_t r;
    asm("fma.rn.bf16x2 %0, %1, %2, %3;\n" : "=r"(r) : "r"(a), "r"(b), "r"(c));
    return r;
}
__device__ __forceinline__ uint32_t bf2_add(uint32_t a, uint32_t b) {
    uint32_t r;
    asm("add.rn.bf16x2 %0, %1, %2;\n" : "=r"(r) : "r"(a), "r"(b));
    return r;
}
constexpr float KAPPA = 0.3292034911525734f;
constexpr float GELU_C = 2.423681954311584f;
constexpr float HSCALE = 1.0f / (2.0f * KAPPA);
__device__ __forceinline__ uint32_t acc_exp(float z) { return max(__float_as_uint(z) >> 23, 10u); }
__device__ __forceinline__ void sched_break(int zero) {
    asm volatile("{\n.reg .pred p;\nsetp.ne.s32 p, %0, 0;\nSB_LOOP:\n@p nanosleep.u32 1;\n@p bra SB_LOOP;\n}\n" ::"r"(zero));
}

#define ACCR8(d, o) "+r"(d[o + 0]), "+r"(d[o + 1]), "+r"(d[o + 2]), "+r"(d[o + 3]), "+r"(d[o + 4]), "+r"(d[o + 5]), "+r"(d[o + 6]), "+r"(d[o + 7])
__device__ __forceinline__ void mma_rs_n128(uint32_t (&d)[32], const uint32_t (&a)[4], uint64_t desc, int scale_d) {
    asm volatile(
        "{\n.reg .pred p;\nsetp.ne.b32 p, %37, 0;\n"
        "wgmma.mma_async.sync.aligned.m64n128k16.f16.f16.f16 "
        "{%0,%1,%2,%3,%4,%5,%6,%7,%8,%9,%10,%11,%12,%13,%14,%15,"
        "%16,%17,%18,%19,%20,%21,%22,%23,%24,%25,%26,%27,%28,%29,%30,%31},"
        "{%32,%33,%34,%35}, %36, p, 1, 1, 0;\n}\n"
        : ACCR8(d, 0), ACCR8(d, 8), ACCR8(d, 16), ACCR8(d, 24)
        : "r"(a[0]), "r"(a[1]), "r"(a[2]), "r"(a[3]), "l"(desc), "r"(scale_d));
}
__device__ __forceinline__ void mma_ss_n128(uint32_t (&d)[32], uint64_t da, uint64_t db) {
    asm volatile(
        "{\n.reg .pred p;\nsetp.ne.b32 p, %34, 0;\n"
        "wgmma.mma_async.sync.aligned.m64n128k16.f16.f16.f16 "
        "{%0,%1,%2,%3,%4,%5,%6,%7,%8,%9,%10,%11,%12,%13,%14,%15,"
        "%16,%17,%18,%19,%20,%21,%22,%23,%24,%25,%26,%27,%28,%29,%30,%31},"
        "%32, %33, p, 1, 1, 0, 0;\n}\n"
        : ACCR8(d, 0), ACCR8(d, 8), ACCR8(d, 16), ACCR8(d, 24)
        : "l"(da), "l"(db), "r"(1));
}
__device__ __forceinline__ uint32_t bf2_as_h2(uint32_t v) { return (v & 0x0fff0fffu) * 7u + v; }
__device__ __forceinline__ float h_lo(uint32_t v) {
    float r;
    asm("{\n.reg .b16 l, h;\nmov.b32 {l, h}, %1;\ncvt.f32.f16 %0, l;\n}\n" : "=f"(r) : "r"(v));
    return r;
}
__device__ __forceinline__ float h_hi(uint32_t v) {
    float r;
    asm("{\n.reg .b16 l, h;\nmov.b32 {l, h}, %1;\ncvt.f32.f16 %0, h;\n}\n" : "=f"(r) : "r"(v));
    return r;
}

__device__ __forceinline__ void mma_rs_n192(uint32_t (&d)[48], const uint4& a, uint64_t db, int scale_d) {
    asm volatile(
        "{\n.reg .pred p;\nsetp.ne.b32 p, %53, 0;\n"
        "wgmma.mma_async.sync.aligned.m64n192k16.f16.f16.f16 "
        "{%0,%1,%2,%3,%4,%5,%6,%7,%8,%9,%10,%11,%12,%13,%14,%15,"
        "%16,%17,%18,%19,%20,%21,%22,%23,%24,%25,%26,%27,%28,%29,%30,%31,"
        "%32,%33,%34,%35,%36,%37,%38,%39,%40,%41,%42,%43,%44,%45,%46,%47},"
        "{%48,%49,%50,%51}, %52, p, 1, 1, 0;\n}\n"
        : ACCR8(d, 0), ACCR8(d, 8), ACCR8(d, 16), ACCR8(d, 24), ACCR8(d, 32), ACCR8(d, 40)
        : "r"(a.x), "r"(a.y), "r"(a.z), "r"(a.w), "l"(db), "r"(scale_d));
}

__device__ __forceinline__ uint32_t pack_f16(float lo, float hi) {
    uint32_t r;
    asm("cvt.rn.f16x2.f32 %0, %1, %2;\n" : "=r"(r) : "f"(hi), "f"(lo));
    return r;
}

constexpr int P1_IMG = 900;
constexpr int P1_SLOT = LN_TILE / 2, P1_NST = 4;
constexpr int P1_X = 16 * C_DIM * 2;
constexpr int P1_OFF_X = P1_SLOT * P1_NST;
constexpr int P1_OFF_A = P1_OFF_X + 2 * P1_X;
constexpr int P1_OFF_BAR = P1_OFF_A + 3 * 2048;
constexpr int P1_OFF_TILE = P1_OFF_BAR + (2 * P1_NST + 3 + 2 + 3 + 2) * 8;
constexpr int P1_OFF_DW = P1_OFF_TILE + 64;
constexpr int P1_SMEM = P1_OFF_DW + C_DIM * 2;

__device__ __forceinline__ float rsqrt_fast(float x) {
    float r;
    asm("rsqrt.approx.ftz.f32 %0, %1;\n" : "=f"(r) : "f"(x));
    return r;
}
__device__ __forceinline__ float sum8(const uint32_t (&c)[4]) {
    const uint32_t u = bf2_add(bf2_add(c[0], c[1]), bf2_add(c[2], c[3]));
    return bf_lo(u) + bf_hi(u);
}
__device__ __forceinline__ void lds128(uint32_t (&v)[4], uint32_t a) {
    asm volatile("ld.shared.v4.u32 {%0,%1,%2,%3}, [%4];\n" : "=r"(v[0]), "=r"(v[1]), "=r"(v[2]), "=r"(v[3]) : "r"(a) : "memory");
}
template <class F>
__device__ __forceinline__ void ln_row(uint32_t (&v)[6][4], uint32_t sdw, F after_loads) {
    uint32_t c[4], s[4], d[4], nm;
#pragma unroll
    for (int i = 0; i < 6; i++) {
        lds128(d, sdw + i * 128);
        if (i == 0) {
#pragma unroll
            for (int k = 0; k < 4; k++) c[k] = bf2_mul(v[0][k], d[k]);
            const float p = sum8(c) * -0.125f;
            nm = pack_bf16(p, p);
        }
#pragma unroll
        for (int k = 0; k < 4; k++) {
            v[i][k] = bf2_fma(v[i][k], d[k], nm);
            s[k] = i ? bf2_add(v[i][k], s[k]) : v[i][k];
            c[k] = i ? bf2_fma(v[i][k], v[i][k], c[k]) : bf2_mul(v[i][k], v[i][k]);
        }
    }
    after_loads(c[0]);
    float m = fmaf(sum8(s), 1.0f / 48, -bf_lo(nm));
    float q = fmaf(-bf_lo(nm), fmaf(2.f, m, bf_lo(nm)), sum8(c) * (1.0f / 48));
#pragma unroll
    for (int o = 1; o < 8; o <<= 1) {
        m += __shfl_xor_sync(0xffffffffu, m, o);
        q += __shfl_xor_sync(0xffffffffu, q, o);
    }
    m *= 0.125f;
    const float r = KAPPA * rsqrt_fast(fmaxf(fmaf(-m, m, q * 0.125f), 0.f) + 1e-5f);
    const float e = (-bf_lo(nm) - m) * r * 0x1p-112f;
    const bool two = __any_sync(0xffffffffu, r < 0x1p-14f);
    const float r1 = r * (two ? 0x1p-56f : 0x1p-112f);
    uint32_t mul = pack_bf16(r1, r1), add = two ? 0u : pack_bf16(e, e);
#pragma unroll 1
    for (int it = !two; it < 2; it++) {
#pragma unroll
        for (int i = 0; i < 6; i++)
#pragma unroll
            for (int k = 0; k < 4; k++) v[i][k] = bf2_fma(v[i][k], mul, add);
        mul = 0x23802380u;
        add = pack_bf16(e, e);
    }
#pragma unroll
    for (int i = 0; i < 6; i++)
#pragma unroll
        for (int k = 0; k < 4; k++) v[i][k] = bf2_as_h2(v[i][k]);
}

__device__ __forceinline__ float gelu_s(float y) {
    float u = y * fmaf(y, y, GELU_C);
    float t;
    asm volatile("tanh.approx.f32 %0, %1;\n" : "=f"(t) : "f"(u));
    return fmaf(y, t, y);
}
__device__ __forceinline__ void p1_pack(int c, uint32_t (&p)[4], uint32_t (&dd)[4]) {
#pragma unroll
    for (int u = 0; u < 4; u++) {
        if ((c & 3) == 0) dd[u] = p[u];
        else {
            uint32_t n = dd[u];
            if ((c & 3) == 1) n = __byte_perm(n, 0, 0x2301);
            if ((c & 3) == 2) {
                dd[u] = __byte_perm(n >> 3, n >> 1, 0x6341);
                n = __byte_perm(n >> 3, n >> 1, 0x7250);
            }
            asm("lop3.b32 %0, %0, %1, 0x40074007, 0xd8;\n" : "+r"(p[u]) : "r"(n));
        }
    }
}
__device__ __forceinline__ void p1_store(int c, const uint32_t (&p)[4], uint8_t* hptr) {
    if (c & 3) stg128_cs(hptr + (c >> 2) * H_HALF + ((c & 3) - 1) * 512, p[0], p[1], p[2], p[3]);
}

template <bool GEN>
__device__ __forceinline__ void p1_epilogue(uint32_t (&acc)[32], float (&ssq)[2], uint32_t sc2, uint8_t* hp, int zero) {
    uint32_t sq[2], dd[4];
#pragma unroll
    for (int c = 0; c < 8; c++) {
        if (GEN) sched_break(zero);
        uint32_t p[4];
#pragma unroll
        for (int u = 0; u < 4; u++) {
            const uint32_t y = acc[8 * (c >> 1) + 2 * u + (c & 1)];
            if (GEN) {
                const float sc = c & 1 ? bf_hi(sc2) : bf_lo(sc2), fs = __uint_as_float(0x78000000u - __float_as_uint(sc));
                const float g0 = gelu_s(h_lo(y) * fs), g1 = gelu_s(h_hi(y) * fs);
                ssq[c & 1] = fmaf(g1, g1, fmaf(g0, g0, ssq[c & 1]));
                p[u] = pack_f16(g0 * sc, g1 * sc);
            } else {
                uint32_t g;
                asm("{\n.reg .b32 w;\n"
                    "fma.rn.f16x2 w, %1, %1, %2;\n"
                    "mul.rn.f16x2 w, w, %1;\n"
                    "tanh.approx.f16x2 w, w;\n"
                    "fma.rn.f16x2 %0, %1, w, %1;\n}\n" : "=r"(g) : "r"(y), "r"(0x40d940d9u));
                acc[8 * (c >> 1) + 2 * u + (c & 1)] = g;
                if (c < 2 && u == 0) asm("mul.rn.f16x2 %0, %1, %1;\n" : "=r"(sq[c & 1]) : "r"(g));
                else asm("fma.rn.f16x2 %0, %1, %1, %0;\n" : "+r"(sq[c & 1]) : "r"(g));
                if (c & 1) asm("{\n.reg .b16 l, h;\n.reg .b32 f;\nmov.b32 {l, h}, %2;\nmov.b32 f, {h, h};\nmul.rn.f16x2 %0, %1, f;\n}\n" : "=r"(p[u]) : "r"(g), "r"(sc2));
                else asm("{\n.reg .b16 l, h;\n.reg .b32 f;\nmov.b32 {l, h}, %2;\nmov.b32 f, {l, l};\nmul.rn.f16x2 %0, %1, f;\n}\n" : "=r"(p[u]) : "r"(g), "r"(sc2));
            }
        }
        p1_pack(c, p, dd);
        if (c & 3) {
#pragma unroll
            for (int u = 0; u < 4; u++) acc[4 * (c - 1 - (c >> 2)) + u] = p[u];
        }
        p1_store(c, p, hp);
    }
    if (!GEN) {
#pragma unroll
        for (int r = 0; r < 2; r++) ssq[r] += h_lo(sq[r]) + h_hi(sq[r]);
    }
}
__device__ __forceinline__ void p1_consumer(const uint32_t (&a)[24][4], uint32_t sc2, bool gen, uint32_t sbase, int wg, int nwg, int cb,
                                            int w, int lane, int zero) {
    const uint32_t bar_full = sbase + P1_OFF_BAR, bar_empty = bar_full + P1_NST * 8;
    const uint32_t empty_remote = mapa(bar_empty, lane & 1);
    const int g = lane >> 2, q = lane & 3, turn = wg + 1 == nwg ? 1 : wg + 2;
    float ssq[2] = {0.f, 0.f};
    uint32_t acc[32] = {};
    TSTAMP(0, 1);
    STAMPT(128, 4);
    STAMPT(256, 5);

    uint8_t* hp = reinterpret_cast<uint8_t*>(g_h) + ((cb * 2 + (w >> 1)) * H_STEP + (w & 1) * 1536) + g * 64 + (q ^ (g >> 1)) * 16;
    const uint64_t desc_base = make_desc(sbase, 16, 1024) | (1ull << 62);
    const uint64_t da = make_desc(sbase + P1_OFF_A + wg * 2048, 128, 256);
#pragma unroll 1
    for (int i = 0;; i++) {
        const int s0 = (i & 1) * 16, par = (i >> 1) & 1;
        const uint64_t d0 = desc_base + (uint64_t)((i & 1) * (LN_TILE / 16));
        TRACE(wg, i, 0);
        mbar_wait(bar_full + s0, par);
        bar_sync(1 + wg, 256);
        TRACE(wg, i, 1);
        uint32_t step, more;
        wg_fence();
#pragma unroll
        for (int k = 0; k < 24; k++) {
            if (k == 12) mbar_wait(bar_full + s0 + 8, par);
            const uint64_t db = d0 + (uint64_t)((k >> 2) * 1024 + (k & 3) * 2);
            if (k < 23) mma_rs_n128(acc, a[k], db, k ? 1 : zero);
            else mma_ss_n128(acc, da, db);
            if (k == 23) bar_arrive(turn, 256);
            if (k % 12 == 11) wg_commit();
        }
        asm volatile("ld.shared.v2.u32 {%0, %1}, [%2];\n" : "=r"(step), "=r"(more) : "r"(sbase + P1_OFF_TILE + (i & 3) * 16) : "memory");
        TRACE(wg, i, 2);
        wg_wait<1>();
        if (lane < 2) mbar_arrive_cluster(empty_remote + s0);
        hp += step;
        TRACE(wg, i, 3);
        wg_wait<0>();
        TRACE(wg, i, 4);
        if (lane < 2) mbar_arrive_cluster(empty_remote + s0 + 8);
        if (gen) p1_epilogue<true>(acc, ssq, sc2, hp, zero);
        else p1_epilogue<false>(acc, ssq, sc2, hp, zero);
        if (!more) break;
    }
    TSTAMP(0, 21);
    if (wg == 0) bar_sync(1, 256);
    uint32_t par;
    asm volatile("ld.shared.u32 %0, [%1];\n" : "=r"(par) : "r"(sbase + P1_OFF_TILE - 4) : "memory");
    float* sums = g_sums[par];
#pragma unroll
    for (int r = 0; r < 2; r++) {
        ssq[r] += __shfl_xor_sync(0xffffffffu, ssq[r], 1);
        ssq[r] += __shfl_xor_sync(0xffffffffu, ssq[r], 2);
        if (q == 0) atomicAdd(sums + cb * 64 + w * 16 + r * 8 + g, ssq[r]);
    }
}

__device__ __forceinline__ void p1_w2(const __nv_bfloat16* __restrict__ w2, const __nv_bfloat16* __restrict__ grn_b, int w, int lane) {
    const int gw = (blockIdx.x - 8 * NGRP) * 4 + w;
    float* sums = g_sums[__ldcg(&g_epoch) & 1] + HID;
    flag_wait<true>(&g_flag[40][1][0], 12);
    {
        const int col = gw % 6 * 64 + lane * 2;
        float bsum[2] = {0.f, 0.f}, asum[2] = {0.f, 0.f};
#pragma unroll 4
        for (int kk = 0; kk < 192; kk++) {
            const int k = gw / 6 * 192 + kk;
            const uint32_t v = *reinterpret_cast<const uint32_t*>(w2 + k * C_DIM + col);
            const float b = __bfloat162float(grn_b[k]), f = __uint_as_float(__ldcg(&g_ex[k]) << 23);
            bsum[0] = fmaf(b, bf_lo(v), bsum[0]);
            bsum[1] = fmaf(b, bf_hi(v), bsum[1]);
            asum[0] = fmaf(f, fabsf(bf_lo(v)), asum[0]);
            asum[1] = fmaf(f, fabsf(bf_hi(v)), asum[1]);
        }
#pragma unroll
        for (int j = 0; j < 2; j++) {
            atomicAdd(sums + col + j, bsum[j]);
            atomicAdd(sums + C_DIM + col + j, asum[j]);
        }
        __threadfence();
        __syncwarp();
        if (lane == 0) asm volatile("red.relaxed.gpu.global.add.u32 [%0], 1;\n" ::"l"(&g_flag[LN_RING + 2][0][0]) : "memory");
    }
    while (*(volatile unsigned*)&g_flag[P1_IMG % LN_RING][1][0] < 12 * (P1_IMG / LN_RING + 1)) {
        __nanosleep(2000);
        SAFE_BREAK
    }
    flag_wait<true>(&g_flag[LN_RING + 2][0][0], 48);
    float z = 0.f;
#pragma unroll
    for (int j = 0; j < C_DIM / 32; j++) z = fmaxf(z, __ldcg(sums + C_DIM + j * 32 + lane));
    const float sc = __uint_as_float((263u - acc_exp(__uint_as_float(__reduce_max_sync(0xffffffffu, __float_as_uint(z))))) << 23);
    const int np = gw % 6 * 64 + lane * 2;
#pragma unroll 2
    for (int cc = 0; cc < 24; cc++) {
        const int c = gw / 6 * 24 + cc;
        uint32_t v[8], o[2][4];
#pragma unroll
        for (int e = 0; e < 8; e++) v[e] = *reinterpret_cast<const uint32_t*>(w2 + (c * 8 + e) * C_DIM + perm32(np));
#pragma unroll
        for (int e = 0; e < 4; e++) {
            const uint2 t = __ldcg(reinterpret_cast<const uint2*>(g_ex) + c * 4 + e);
            const float f0 = __uint_as_float(t.x << 23), f1 = __uint_as_float(t.y << 23);
            o[0][e] = pack_f16(bf_lo(v[2 * e]) * f0 * sc, bf_lo(v[2 * e + 1]) * f1 * sc);
            o[1][e] = pack_f16(bf_hi(v[2 * e]) * f0 * sc, bf_hi(v[2 * e + 1]) * f1 * sc);
        }
#pragma unroll
        for (int j = 0; j < 2; j++)
            g_w2img[0][(((c >> 1) * 48 + (np >> 3)) * 2 + (c & 1)) * 8 + (np & 7) + j] = make_uint4(o[j][0], o[j][1], o[j][2], o[j][3]);
    }
    asm volatile("fence.proxy.async.global;\n" ::: "memory");
    __threadfence();
    __syncwarp();
    if (lane == 0) asm volatile("red.relaxed.gpu.global.add.u32 [%0], 1;\n" ::"l"(&g_img[0]) : "memory");
}

__global__ void __cluster_dims__(2, 1, 1) __launch_bounds__(512, 1)
pass1_kernel(const __grid_constant__ CUtensorMap wmap, const __nv_bfloat16* __restrict__ x, const __nv_bfloat16* __restrict__ dw,
             const __nv_bfloat16* __restrict__ w1, const __nv_bfloat16* __restrict__ w2, const __nv_bfloat16* __restrict__ grn_b, int zero) {
    extern __shared__ __align__(1024) uint8_t smem[];
    const uint32_t sbase = smem_u32(smem);
    const uint32_t bar_full = sbase + P1_OFF_BAR, bar_empty = bar_full + P1_NST * 8, bar_w = bar_empty + P1_NST * 8;
    const uint32_t bar_xfull = bar_w + 24, bar_raw = bar_xfull + 16, bar_done = bar_raw + 16;
    const int tid = threadIdx.x;
    const int warp = __shfl_sync(0xffffffffu, tid >> 5, 0), lane = tid & 31;
    const uint32_t rank = cluster_rank();
    const int cl = blockIdx.x >> 1;
    const bool small = cl >= 4 * NGRP;
    const int nwg = small ? 2 : 3, cb0 = small ? (blockIdx.x - 8 * NGRP) * 2 : (blockIdx.x & 7) * 3;
    uint8_t* const ring = reinterpret_cast<uint8_t*>(g_ln);

    TSTAMP(0, 0);
    TRACEW(110 + warp, 0);

    if (warp >= 12) {
        reg_dec<56>();
        asm volatile("barrier.cluster.arrive.relaxed.aligned;\n" ::: "memory");
        asm volatile("barrier.cluster.wait.aligned;\n" ::: "memory");
        {
            auto ring_row = [&](int p) {
                const int n = (p & 8) * 8 + (lane >> 3) * 8 + (p & 3) * 2 + (p >> 2 & 1);
                return n * 128 + (((lane ^ n) & 7) << 4);
            };
            const uint8_t* xsrc = reinterpret_cast<const uint8_t*>(x) + (size_t)(LN_STEP * 8 + blockIdx.x * 2 + (warp & 1)) * P1_X;
            const uint32_t xbar = bar_xfull + (warp & 1) * 8, xdst = sbase + P1_OFF_X + (warp & 1) * P1_X;
            const uint32_t sdw = sbase + P1_OFF_DW + (lane & 7) * 16;
            uint32_t src = xdst - P1_OFF_X + (lane >> 3) * (C_DIM * 2) + (lane & 7) * 16;
            int row0 = ring_row((blockIdx.x & 7) * 2 + (warp & 1)) ^ 288, slot = blockIdx.x >> 3, used = 0;
            auto next = [&]() {
                xsrc += (size_t)LN_STEP * 8 * P1_X;
                if (elect_one()) {
                    mbar_expect_tx(xbar, P1_X);
                    bulk_g2s(xdst, xsrc, P1_X, xbar);
                }
                __syncwarp();
            };
#pragma unroll 1
            for (int i = -1; i * LN_STEP + (int)(blockIdx.x >> 2) < NT128 && blockIdx.x < 128; i++) {
                if (warp == 14) TRACEW(128 + i, 0);
                const int last = i > 0 ? 3 : i ? 2 + (warp >> 1 & 1) : blockIdx.x < 112 ? 1 : -1;
#pragma unroll 1
                for (int ps = i < 0 ? last - 4 : 0; ps <= last; ps += i < 0 ? 4 : 1) {
                    if (i < 0 && ps > 0) STAMPT(416, 6);
                    if (i < 0 && ps > 0) mbar_wait(bar_raw, 0);
                    if (i < 0 && ps > 0) STAMPT(416, 7);
                    if (ps == 0) {
                        if (used) flag_wait<false>(&g_flag[slot][1][0], used);
                        if (i) mbar_wait(xbar, ~i & 1);
                        else mbar_wait(bar_raw + 8, 0);
                        if (warp == 14) TRACEW(128 + i, 1);
                    }
                    uint32_t v[6][4];
#pragma unroll
                    for (int j = 0; j < 6; j++) lds128(v[j], src + (ps & 3) * (4 * C_DIM * 2) + j * 128);
                    ln_row(v, sdw, [&](uint32_t dep) {
                        if (i == 0 && ps == 1 && lane < 2) mbar_arrive_cluster(mapa(bar_empty, lane) + (dep & zero));
                        if (ps == 3 && i > 0 && (i + 1) * LN_STEP + (blockIdx.x >> 2) < NT128 && !__any_sync(0xffffffffu, dep & zero)) next();
                    });
                    uint8_t* dst = ring + (slot * LN_TILE + (ps & 1) * 4096 + (row0 ^ (ps & 2) * 144));
#pragma unroll
                    for (int j = 0; j < 6; j++)
                        asm volatile("{\n.reg .pred p;\nsetp.ge.s32 p, %5, 0;\n@p st.global.v4.u32 [%0], {%1,%2,%3,%4};\n}\n"
                                     ::"l"(dst + j * 16384), "r"(v[j][0]), "r"(v[j][1]), "r"(v[j][2]), "r"(v[j][3]), "r"(ps) : "memory");
                }
                if (warp == 14) TRACEW(128 + i, 2);
                asm volatile("fence.proxy.async.global;\nfence.acq_rel.cta;\n" ::: "memory");
                if (i < 0) {
                    bar_sync(4, 128);
                    if (warp < 14 || small) break;
                    if (blockIdx.x >= 112 && lane < 2) mbar_arrive_cluster(mapa(bar_empty, lane));
                    row0 ^= 288;
                    slot += 16;
                } else {
                    if (i) mbar_wait(bar_done, ~i & 1);
                    else {
                        src += P1_OFF_X;
                        slot = blockIdx.x >> 2;
                        row0 = ring_row((blockIdx.x & 3) * 4 + (warp & 1) * 2);
                    }
                    __syncwarp();
                    if (lane == 0) mbar_arrive(bar_done);
                    if ((slot += LN_STEP) >= LN_RING) { slot -= LN_RING; used += 12; }
                }
            }
            if ((warp < 14 || small) && lane < 2) mbar_arrive_cluster(mapa(bar_empty, lane));
        }
        if (warp == 12) {
            int prev = 0, t = p1_tile(small ? 0 : cl >> 2, small), next = p1_tile(small ? 1 : (cl >> 2) + NGRP, small);
            const uint32_t rbase = mapa(sbase, lane & 1);
            int i = 0;
#pragma unroll 1
            for (; t < NT128; i++) {
                const int s0 = (i & 1) * 2, par = (i >> 1) & 1;
                const int round = t / LN_RING, slot = t - round * LN_RING;
                const uint8_t* src = ring + slot * LN_TILE + rank * (P1_SLOT / 2);
                int draw = i + 2;
                if (rank == 0 && lane == 0 && !small) draw = 2 * NGRP + atomicAdd(&g_flag[LN_RING + ((cl >> 1) & 1)][cl & 1][0], 1u);
                flag_wait<true>(&g_flag[slot][0][0], 8 * round + 8);
                TRACEW(i, 2);
                if (i == 0) STAMPT(384, 10);
                if (i == 2) STAMPT(384, 13);
                if (i == 3) STAMPT(384, 14);
                asm volatile("fence.proxy.async.global;\n" ::: "memory");
                draw = p1_tile(__shfl_sync(0xffffffffu, draw, 0), small);
#pragma unroll
                for (int h = 0; h < 2; h++) {
                    mbar_wait(bar_empty + (s0 + h) * 8, par);
                    TRACEW(i, 4 + h);
                    if (i == 0 && h == 1) STAMPT(384, 11);
                    if (elect_one()) {
                        mbar_expect_tx(bar_full + (s0 + h) * 8, P1_SLOT + 16 - 16 * h);
                        bulk_g2s_mc(sbase + (s0 + h) * P1_SLOT + rank * (P1_SLOT / 2), src + h * P1_SLOT, P1_SLOT / 2, bar_full + (s0 + h) * 8, (uint16_t)3);
                    }
                    __syncwarp();
                    if (h == 0 && rank == 0 && lane < 2)
                        asm volatile("st.async.shared::cluster.mbarrier::complete_tx::bytes.v4.u32 [%0], {%1, %2, %3, %3}, [%4];\n"
                                     ::"r"(rbase + P1_OFF_TILE + (i & 3) * 16), "r"((t - prev) * (2 * H_TILE)), "r"((int)(next < NT128)), "r"(draw),
                                       "r"(rbase + P1_OFF_BAR + s0 * 8) : "memory");
                }
                prev = t;
                t = next;
                next = draw;
                if (rank != 0) {
                    mbar_wait(bar_full + s0 * 8, (i >> 1) & 1);
                    mbar_wait(bar_full + s0 * 8 + 8, (i >> 1) & 1);
                    if (lane == 0) asm volatile("red.relaxed.gpu.global.add.u32 [%0], %1;\n" ::"l"(&g_flag[slot][1][0]), "r"(nwg) : "memory");
                    asm volatile("ld.shared.u32 %0, [%1];\n" : "=r"(next) : "r"(sbase + P1_OFF_TILE + (i & 3) * 16 + 8) : "memory");
                    TRACEW(i, 3);
                }
            }
#pragma unroll 1
            for (int j = 2 * i; j < 2 * i + 4; j++) mbar_wait(bar_empty + (j & 3) * 8, (j >> 2) & 1);
        } else if (warp == 13) {
            STAMPT(416, 8);
            if (lane == 0 && blockIdx.x < 128) asm volatile("red.release.gpu.global.add.u32 [%0], 1;\n" ::"l"(&g_flag[blockIdx.x >> 3][0][0]) : "memory");
            __syncwarp();
            STAMPT(416, 9);
            const uint32_t ep = g_epoch & 1;
            asm volatile("st.shared.u32 [%0], %1;\n" ::"r"(sbase + P1_OFF_TILE - 4), "r"(ep) : "memory");
            if (blockIdx.x == 18) g_par = ep;
            if (blockIdx.x < 18) reinterpret_cast<float4*>(g_sums[ep ^ 1])[blockIdx.x * 32 + lane] = make_float4(0.f, 0.f, 0.f, 0.f);
#pragma unroll 1
            for (int i = 0; !small && i * LN_STEP + (blockIdx.x >> 2) < NT128; i++) {
                mbar_wait(bar_done, i & 1);
                asm volatile("fence.proxy.async.global;\n" ::: "memory");
                if (lane == 0) {
                    mbar_arrive(bar_done);
                    asm volatile("red.release.gpu.global.add.u32 [%0], %1;\n"
                                 ::"l"(&g_flag[i ? (blockIdx.x >> 2) + (i & 1) * LN_STEP : 16 + (blockIdx.x >> 3)][0][0]), "r"(i ? 2 : (int)(blockIdx.x < 112)) : "memory");
                }
                __syncwarp();
                TRACEW(128 + i, 3);
            }
            flag_wait<true>(&g_flag[LN_RING + 2][0][0], 48);
        }
    } else {
        if (tid == 0) {
            mbar_init(bar_raw, 1);
            mbar_init(bar_raw + 8, 1);
            mbar_init(bar_xfull, 1);
            mbar_init(bar_xfull + 8, 1);
            for (int i = 0; i < 3; i++) mbar_init(bar_w + i * 8, 1);
            asm volatile("fence.mbarrier_init.release.cluster;\n" ::: "memory");
            if (blockIdx.x < 128) {
                mbar_expect_tx(bar_raw, P1_X + C_DIM * 2);
                bulk_g2s(sbase + P1_OFF_DW, dw, C_DIM * 2, bar_raw);
                for (int i = 0; i < 2; i++) bulk_g2s(sbase + i * P1_X + P1_X / 2, x + (size_t)(blockIdx.x * 16 + i * 8) * C_DIM, P1_X / 2, bar_raw);
                asm volatile("cp.async.bulk.prefetch.L2.global [%0], 9216;\n" ::"l"(w1 + blockIdx.x * 4608) : "memory");
            }
            if (blockIdx.x < 112) {
                mbar_expect_tx(bar_raw + 8, P1_X);
                for (int i = 0; i < 2; i++) bulk_g2s(sbase + i * P1_X, x + (size_t)(16 * 128 + blockIdx.x * 16 + i * 8) * C_DIM, P1_X / 2, bar_raw + 8);
            }
            for (int i = 0; i < nwg; i++) {
                mbar_expect_tx(bar_w + i * 8, P1_SLOT);
                tma2(sbase + (1 + i) * P1_SLOT, &wmap, (cb0 + i) * 64, 0, bar_w + i * 8);
                tma2(sbase + (1 + i) * P1_SLOT + P1_SLOT / 2, &wmap, (cb0 + i) * 64, 192, bar_w + i * 8);
            }
            for (int i = 0; i < 2 && !small; i++) {
                mbar_expect_tx(bar_xfull + i * 8, P1_X);
                bulk_g2s(sbase + P1_OFF_X + i * P1_X, x + (size_t)(LN_STEP * 128 + blockIdx.x * 32 + i * 16) * C_DIM, P1_X, bar_xfull + i * 8);
            }
        }
        if (tid == 32) {
            mbar_init(bar_done, 3);
            mbar_arrive(bar_done);
            asm volatile("fence.mbarrier_init.release.cluster;\n" ::: "memory");
        }
        if (tid == 64) {
            for (int i = 0; i < P1_NST; i++) {
                mbar_init(bar_full + i * 8, 1);
                mbar_init(bar_empty + i * 8, 8 * nwg);
            }
            asm volatile("fence.mbarrier_init.release.cluster;\n" ::: "memory");
            if (blockIdx.x < 64) (&g_half[0][0])[blockIdx.x] = 0;
            else if (blockIdx.x == 64) g_prog = 0;
            else if (blockIdx.x < 67) g_img[blockIdx.x - 65] = 0;
        }
        __syncwarp();
        asm volatile("barrier.cluster.arrive.relaxed.aligned;\n" ::: "memory");
        reg_inc<152>();
        TRACEW(110 + warp, 1);
        const int wg = warp >> 2, w = warp & 3;
        gdc_launch();
        asm volatile("barrier.cluster.wait.aligned;\n" ::: "memory");
        if (wg == nwg) {
            p1_w2(w2, grn_b, w, lane);
            return;
        }
        const uint32_t slot_free = mapa(bar_empty, lane & 1) + (lane >> 1) * 8;
        if (lane < 8 && (lane >> 1) != 1 + wg && (wg || lane > 1)) mbar_arrive_cluster(slot_free);
        if (wg == 1) bar_arrive(1, 256);
        uint32_t a[24][4], ex[2], gen = 0;
        const uint32_t wsrc = sbase + (1 + wg) * P1_SLOT + ((lane >> 4) * 8 + (lane & 7)) * 128 + (((2 * w + ((lane >> 3) & 1)) ^ (lane & 7)) << 4);
#pragma unroll 1
        for (int it = 0; it < 2; it++) {
            if (it) mbar_wait(bar_w + wg * 8, 0);
            TRACEW(110 + warp, 5);
            if (it || wg == 0) {
#pragma unroll
            for (int k = 0; k < 24; k++) ldsm4t(a[k], wsrc + k * 2048);
#pragma unroll
            for (int r = 0; r < 2; r++) {
                float t = 0.f;
#pragma unroll
                for (int j = 0; j < 6; j++) {
                    uint32_t c = bf2_mul(a[4 * j][r], a[4 * j][r]);
#pragma unroll
                    for (int k = 1; k < 8; k++) c = bf2_fma(a[4 * j + k / 2][r + (k & 1) * 2], a[4 * j + k / 2][r + (k & 1) * 2], c);
                    t += bf_lo(c) + bf_hi(c);
                }
                t += __shfl_xor_sync(0xffffffffu, t, 1);
                t += __shfl_xor_sync(0xffffffffu, t, 2);
                asm("sqrt.approx.f32 %0, %0;\n" : "+f"(t));
                ex[r] = min(max(__float_as_uint(13.9f * t) >> 23, 72u), 198u);
            }
            asm volatile("{\n.reg .pred p;\nsetp.gt.u32 p, %1, 7;\nbar.red.or.pred p, %2, 128, p;\nselp.u32 %0, 1, 0, p;\n}\n"
                         : "=r"(gen) : "r"(max(ex[0] - 125u, ex[1] - 125u)), "r"(5 + wg) : "memory");
            gen = __shfl_sync(0xffffffffu, gen, 0) & it;
            if (it) {
                if ((lane & 3) < 2) g_ex[(cb0 + wg) * 64 + w * 16 + (lane & 1) * 8 + (lane >> 2)] = lane & 1 ? ex[1] : ex[0];
                if ((lane >> 1) == 1 + wg) mbar_arrive_cluster(slot_free);
                __syncwarp();
            }
            }
            if (gen) {
#pragma unroll
                for (int k = 0; k < 24; k++)
#pragma unroll
                    for (int j = 0; j < 4; j++) a[k][j] = bf2_mul(a[k][j], (268u - ex[j & 1]) * 0x00800080u);
            }
            if (it || wg == 1) {
#pragma unroll
                for (int k = 0; k < 24; k++)
#pragma unroll
                    for (int j = 0; j < 4; j++) {
                        a[k][j] = bf2_as_h2(bf2_mul(a[k][j], 0x07800780u));
                        asm volatile("" : "+r"(a[k][j]));
                    }
            }
            TRACEW(110 + warp, 6);
        }
#pragma unroll
        for (int j = 0; j < 4; j++)
            asm volatile("st.shared.u32 [%0], %1;\n" ::"r"(sbase + P1_OFF_A + warp * 512 + (j & 1) * 256 + (j >> 1) * 128 + lane * 4), "r"(a[23][j]) : "memory");
        asm volatile("fence.proxy.async.shared::cta;\n" ::: "memory");
        TRACEW(110 + warp, 7);
        const uint32_t ex2 = ex[0] | ex[1] << 16;
        p1_consumer(a, gen ? 0x7f007f00u - (ex2 << 7) : (0x008e008eu - ex2) << 10, gen, sbase, wg, nwg, cb0 + wg, w, lane, zero);
        TSTAMP(0, 30);
    }
}

constexpr int P2_B = 24576, P2_NB = 5;
constexpr int P2_A = 3072, P2_NA = 5;
constexpr int P2_XROW = C_DIM * 2;
constexpr int P2_OFF_A = P2_B * P2_NB;
constexpr int P2_OFF_X = P2_OFF_A + 3 * P2_NA * P2_A;
constexpr int P2_XHALF = 32 * P2_XROW + 64;
constexpr int P2_OFF_BIAS = P2_OFF_X + 64 * P2_XROW + 64;
constexpr int P2_OFF_GRN = P2_OFF_BIAS + C_DIM * 4;
constexpr int P2_OFF_BAR = P2_OFF_GRN + HID * 2;
constexpr int P2_SMEM = P2_OFF_BAR + (2 * P2_NB + 6 * P2_NA + 3) * 8;
constexpr int P2_LAG = 17;
constexpr int P2_NCL = NUM_CTAS / 2, P2_ITEMS = NT128 / P2_NCL, P2_SHARED = NT128 - P2_ITEMS * P2_NCL;
constexpr int P2_POS = P2_LAG * (P2_ITEMS - 1) + 48;
__device__ __forceinline__ int p2_start(int n) { return n < 0 ? 0 : n == P2_ITEMS ? P2_POS - 24 : P2_LAG * n; }
constexpr int P2_FOLD = 17;
constexpr int P2_XC = 8 * P2_XROW;
constexpr int P2_DELTA = 7;
__device__ __forceinline__ int p2_tile(int cl, int n) {
    return n == 0 ? NT128 - 1 - cl : n < 0 || n == P2_ITEMS ? NT128 - 1 - P2_NCL - (cl >> 1) : cl + P2_NCL * (n - 1);
}

constexpr int P2_EG = 2;
__device__ __forceinline__ void p2_epilogue(const uint32_t (&acc0)[48], const uint32_t (&acc1)[48], uint32_t sx, uint32_t sb, float up, int zero) {
    uint32_t v[2][P2_EG][4];
    float b[2][8];
    auto load = [&](int c, uint32_t a) {
#pragma unroll
        for (int j = 0; j < 2; j++)
            asm volatile("ld.shared.v4.f32 {%0,%1,%2,%3}, [%4];\n" : "=f"(b[c & 1][4 * j]), "=f"(b[c & 1][4 * j + 1]), "=f"(b[c & 1][4 * j + 2]), "=f"(b[c & 1][4 * j + 3])
                         : "r"(sb + c * 128 + j * 16) : "memory");
#pragma unroll
        for (int j = 0; j < P2_EG; j++) {
            const int u = c * P2_EG + j;
            asm volatile("ld.shared.v4.u32 {%0,%1,%2,%3}, [%4];\n" : "=r"(v[c & 1][j][0]), "=r"(v[c & 1][j][1]), "=r"(v[c & 1][j][2]), "=r"(v[c & 1][j][3])
                         : "r"(a + (u >> 1) * 64 + (u & 1) * 4 * P2_XROW) : "memory");
        }
    };
    load(0, sx);
#pragma unroll
    for (int c = 0; c < 24 / P2_EG; c++) {
        if (c + 1 < 24 / P2_EG) load(c + 1, sx + (v[c & 1][P2_EG - 1][0] & zero));
#pragma unroll
        for (int j = 0; j < P2_EG; j++) {
            const int u = c * P2_EG + j, i = 8 * ((u >> 1) % 6) + (u & 1);
            const uint32_t (&acc)[48] = u < 12 ? acc0 : acc1;
            uint32_t (&w)[4] = v[c & 1][j];
#pragma unroll
            for (int e = 0; e < 4; e++)
                w[e] = bf2_add(pack_bf16(fmaf(h_lo(acc[i + 2 * e]), up, b[c & 1][2 * e]), fmaf(h_hi(acc[i + 2 * e]), up, b[c & 1][2 * e + 1])), w[e]);
            asm volatile("st.shared.v4.u32 [%4], {%0,%1,%2,%3};\n" ::"r"(w[0]), "r"(w[1]), "r"(w[2]), "r"(w[3]),
                         "r"(sx + (u >> 1) * 64 + (u & 1) * 4 * P2_XROW) : "memory");
        }
    }
}

__device__ __forceinline__ void p2_unpack(uint4& u, uint32_t o1, uint32_t o2, uint32_t o3) {
    u.z = o1 & 0xbff8bff8u;
    u.y = o2 & 0xbff8bff8u;
    u.w = o3 & 0xbff8bff8u;
    u.x = (__byte_perm(o1, 0, 0x2301) & 0x07400740u) | ((__byte_perm(o2, o3, 0x6240) << 3) & 0x38383838u) | ((__byte_perm(o2, o3, 0x3715) << 1) & 0x80808080u);
}
__device__ __forceinline__ uint32_t h2_mul(uint32_t a, uint32_t b) {
    uint32_t r;
    asm("mul.rn.f16x2 %0, %1, %2;\n" : "=r"(r) : "r"(a), "r"(b));
    return r;
}
__device__ __forceinline__ void p2_epilogue_add(const uint32_t (&acc)[48], uint8_t* o, float f, int zero) {
#pragma unroll
    for (int t = 0; t < 12; t++) {
        uint32_t v[4];
#pragma unroll
        for (int e = 0; e < 4; e++) {
            v[e] = acc[8 * (t >> 1) + (t & 1) + 2 * e];
            asm volatile("" : "+r"(v[e]));
            v[e] = pack_bf16(h_lo(v[e]) * f, h_hi(v[e]) * f);
        }
        asm volatile("red.global.add.noftz.v4.bf16x2 [%0], {%1,%2,%3,%4};\n" ::"l"(o + (t >> 1) * 64 + (t & 1) * 4 * P2_XROW),
                     "r"(v[0]), "r"(v[1]), "r"(v[2]), "r"(v[3]) : "memory");
        if (t % 3 == 2) sched_break(zero);
    }
}

__global__ void __cluster_dims__(2, 1, 1) __launch_bounds__(512, 1)
pass2_kernel(const __nv_bfloat16* __restrict__ x, const __nv_bfloat16* __restrict__ grn_g, __nv_bfloat16* __restrict__ out, int zero) {
    extern __shared__ __align__(1024) uint8_t smem[];
    const uint32_t sbase = smem_u32(smem);
    const uint32_t bar_bfull = sbase + P2_OFF_BAR, bar_bempty = bar_bfull + P2_NB * 8;
    const uint32_t bar_afull = bar_bempty + P2_NB * 8, bar_aempty = bar_afull + 3 * P2_NA * 8;
    const uint32_t bar_xfull = bar_aempty + 3 * P2_NA * 8, bar_oready = bar_xfull + 8, s_pos = bar_xfull + 16;
    int tid;
    asm volatile("mov.u32 %0, %%tid.x;\n" : "=r"(tid));
    const int warp = __shfl_sync(0xffffffffu, tid >> 5, 0), lane = tid & 31;
    const uint32_t rank = cluster_rank();
    const int cl = blockIdx.x >> 1, pair = cl >> 1;
    const int k0 = (4 * pair + (cl & 1) * (48 - P2_POS % 48)) % 48;
    const int head = pair < P2_SHARED && !(cl & 1), tail = pair < P2_SHARED && (cl & 1);

    uint32_t par, gg[4];
    float pre[4];
    if (warp < 12) {
        asm volatile("ld.global.cg.u32 %0, [%1];\n" : "=r"(par) : "l"(&g_par) : "memory");
#pragma unroll
        for (int i = 0; i < 4; i++) {
            asm volatile("ld.global.cg.f32 %0, [%1];\n" : "=f"(pre[i]) : "l"(&g_sums[i & 1][HID + (i >> 1) * C_DIM + tid]) : "memory");
            asm volatile("ld.global.nc.u16 %0, [%1];\n" : "=r"(gg[i]) : "l"(grn_g + tid + 384 * i) : "memory");
        }
    }
    TSTAMP(1, 0);
    if (tid == 384) {
        for (int i = 0; i < P2_NB; i++) {
            mbar_init(bar_bfull + i * 8, 1);
            mbar_init(bar_bempty + i * 8, 24);
        }
        for (int i = 0; i < 3 * P2_NA; i++) {
            mbar_init(bar_afull + i * 8, 1);
            mbar_init(bar_aempty + i * 8, 4);
        }
        mbar_init(bar_xfull, 2);
        mbar_init(bar_oready, 4);
        asm volatile("st.shared.u32 [%0], 0;\n" ::"r"(s_pos) : "memory");
        asm volatile("fence.mbarrier_init.release.cluster;\n" ::: "memory");
    }
    __syncthreads();
    cluster_sync_relaxed();

    if (warp >= 12) {
        reg_dec<32>();
        if (warp == 12) {
            const uint8_t* wsrc = reinterpret_cast<const uint8_t*>(g_w2img) + rank * (P2_B / 2);
            int st = 0, ph = 1, kb = k0, m = 0, r = 0;
            const int busy = head ? 0 : tail ? P2_POS - 24 : P2_POS;
#pragma unroll 1
            for (int p = 0; p < P2_POS; p++) {
                if (p == 0 || p == P2_FOLD) {
                    flag_wait<true>(&g_img[p != 0], p ? 96 * 4 : 48);
                    asm volatile("fence.proxy.async.global;\n" ::: "memory");
                    if (p) wsrc += sizeof(g_w2img[0]);
                }
                mbar_wait(bar_bempty + st * 8, ph);
                TR2P(p, 0);
                if (elect_one()) {
                    mbar_expect_tx(bar_bfull + st * 8, P2_B);
                    bulk_g2s_mc(sbase + st * P2_B + rank * (P2_B / 2), wsrc + kb * P2_B, P2_B / 2, bar_bfull + st * 8, (uint16_t)3);
                    asm volatile("st.volatile.shared.u32 [%0], %1;\n" ::"r"(s_pos), "r"(p) : "memory");
                    const int idle = 2 - min(m, P2_ITEMS - 1) + max(m - 2 + (r >= 48 - 2 * P2_LAG), 0) - ((unsigned)(p - busy) < 24);
                    if (idle) asm volatile("mbarrier.arrive.shared::cta.b64 _, [%0], %1;\n" ::"r"(bar_bempty + st * 8), "r"(idle * 8) : "memory");
                    if (rank == 0) asm volatile("red.relaxed.gpu.global.add.u32 [%0], 1;\n" ::"l"(&g_prog) : "memory");
                }
                __syncwarp();
                if (++st == P2_NB) { st = 0; ph ^= 1; }
                if (++kb == 48) kb = 0;
                if (++r == P2_LAG) { r = 0; m++; }
            }
            mbar_wait(bar_bempty + st * 8, ph);
            if (lane == 0) mbar_arrive(bar_bfull + st * 8);
#pragma unroll 1
            for (int p = 1; p < P2_NB; p++) {
                if (++st == P2_NB) { st = 0; ph ^= 1; }
                mbar_wait(bar_bempty + st * 8, ph);
            }
        } else if (warp == 13) {
            const uint8_t* src[3];
            int n[3], left[3], wrap[3];
            uint32_t st[3];
            auto item = [&](int w) {
                const int u = (k0 + p2_start(n[w])) % 48;
                left[w] = n[w] < 0 || n[w] == P2_ITEMS ? 24 : 48;
                wrap[w] = left[w] - (48 - u);
                src[w] = reinterpret_cast<const uint8_t*>(g_h) + (size_t)p2_tile(cl, n[w]) * (2 * H_TILE) + rank * H_HALF + u * H_STEP;
            };
#pragma unroll
            for (int w = 0; w < 3; w++) {
                n[w] = w == 2 && head ? -1 : w;
                st[w] = 0x80000000u;
                item(w);
            }
            gdc_wait();
#pragma unroll 1
            for (int done = 0; done < 3;) {
                bool idle = true;
#pragma unroll
                for (int w = 0; w < 3; w++) {
                    const uint32_t o = (st[w] & 0xff) + w * P2_NA * 8;
                    if (left[w] >= 0 && mbar_test(bar_aempty + o, st[w] >> 31)) {
                        idle = false;
                        if (left[w] == 0) {
                            if (lane == 0) mbar_arrive(bar_afull + o);
                            left[w] = -1;
                            done++;
                        } else {
                            if (elect_one()) {
                                mbar_expect_tx(bar_afull + o, P2_A);
                                bulk_g2s(sbase + P2_OFF_A + o * (P2_A / 8), src[w], P2_A, bar_afull + o);
                            }
                            __syncwarp();
                            src[w] += H_STEP;
                            st[w] += 8;
                            if ((st[w] & 0xff) == P2_NA * 8) st[w] ^= 0x80000000u | (P2_NA * 8);
                            if (--left[w] == wrap[w]) src[w] -= 48 * H_STEP;
                            if (left[w] == 0 && (n[w] += 3) < P2_ITEMS + tail) item(w);
                        }
                    }
                }
                if (idle) __nanosleep(64);
                SAFE_BREAK
            }
        } else if (warp == 14) {
            const uint32_t sx = sbase + P2_OFF_X;
            size_t o = 0;
            auto pace = [&](int target) {
                int v;
                while (true) {
                    asm volatile("ld.volatile.shared.u32 %0, [%1];\n" : "=r"(v) : "r"(s_pos) : "memory");
                    if (v * 16 >= target) break;
                    __nanosleep(100);
                    SAFE_BREAK
                }
            };
#pragma unroll 1
            for (int n = -head; n <= P2_ITEMS; n++) {
                const size_t on = (size_t)(2 * p2_tile(cl, n) + rank) * (64 * C_DIM * 2);
                const bool st = n + head > 0, ld = n < P2_ITEMS;
                if (st) mbar_wait(bar_oready, (n - 1 + head) & 1);
                TR2P(n + 1, 1);
                if (lane == 0) {
                    if (n == 1 && head) {
                        asm volatile("cp.async.bulk.wait_group 0;\nfence.proxy.async.global;\n" ::: "memory");
                        asm volatile("st.release.gpu.global.u32 [%0], 1;\n" ::"l"(&g_half[pair][rank]) : "memory");
                    }
                    if (ld) mbar_expect_tx(bar_xfull, 64 * C_DIM * 2);
                    int t = st && n < P2_ITEMS - 1 ? (P2_LAG * (n - 1) + 52) * 16 : -1024;
#pragma unroll 1
                    for (int c = 0; st && c < 64 * P2_XROW; c += P2_XC) {
                        pace(t += 11);
                        bulk_s2g(reinterpret_cast<uint8_t*>(out) + o + c, sx + c + (c >= 32 * P2_XROW ? 64 : 0), P2_XC);
                    }
                    asm volatile("cp.async.bulk.commit_group;\ncp.async.bulk.wait_group.read 0;\n" ::: "memory");
#pragma unroll 1
                    for (int c = 0; ld && c < 64 * P2_XROW; c += P2_XC) {
                        pace(t += 11);
                        bulk_g2s(sx + c + (c >= 32 * P2_XROW ? 64 : 0), reinterpret_cast<const uint8_t*>(x) + on + c, P2_XC, bar_xfull);
                    }
                    TR2P(n + 1, 2);
                    if (rank == 0 && n > 0 && n < P2_ITEMS - 2)
                        flag_wait<false>(&g_prog, P2_NCL * (P2_LAG * n + 48) + (tail ? P2_SHARED - P2_NCL : P2_SHARED) * P2_DELTA);
                    if (ld) mbar_arrive(bar_xfull);
                    TR2P(n + 1, 3);
                }
                __syncwarp();
                o = on;
            }
            asm volatile("cp.async.bulk.wait_group 0;\n" ::: "memory");
            TR2P(30, 1);
        }
    } else {
        reg_inc<160>();
        const int wg = warp >> 2, w = warp & 3, g = lane >> 2, q = lane & 3;
        const uint32_t sx = sbase + P2_OFF_X + (g & 1) * P2_XHALF + (w * 8 + (g >> 1)) * P2_XROW + q * 16;
        const uint32_t af = bar_afull + wg * P2_NA * 8;
        const uint32_t s_a = sbase + P2_OFF_A + wg * P2_NA * P2_A + (lane >> 3) * 512 + (lane & 7) * 64 +
                             ((w ^ ((lane & 7) >> 1)) << 4);
        uint32_t acc0[48], acc1[48];
        float up;
        uint4 a0[2], a1[2];
        uint32_t st = 0, ph = 0;

        {
            float4* s_red = reinterpret_cast<float4*>(smem + P2_OFF_BIAS);
            const float* sums = g_sums[par];
            float gx[4], part = 0.f, mx = 0.f;
            TSTAMP(1, 27);
            gdc_wait();
            TSTAMP(1, 1);
#pragma unroll
            for (int i = 0; i < 4; i++) gx[i] = __ldcg(sums + tid + 384 * i);
            if (blockIdx.x == 120 && tid < (LN_RING + 3) * 2) (&g_flag[0][0][0])[tid * 8] = 0;
            if (blockIdx.x == 121 && tid == 0) atomicAdd(&g_epoch, 1u);
            float z = __uint_as_float(__reduce_max_sync(0xffffffffu, __float_as_uint(pre[2] + pre[3])));
#pragma unroll
            for (int i = 0; i < 4; i++) {
                asm("sqrt.approx.f32 %0, %1;\n" : "=f"(gx[i]) : "f"(fmaf(gx[i], HSCALE * HSCALE, 1e-6f)));
                part += gx[i];
                gx[i] *= bf_lo(gg[i]);
                mx = fmaxf(mx, fabsf(gx[i]));
            }
#pragma unroll
            for (int o = 16; o > 0; o >>= 1) part += __shfl_xor_sync(0xffffffffu, part, o);
            mx = __uint_as_float(__reduce_max_sync(0xffffffffu, __float_as_uint(mx)));
            TSTAMP(1, 26);
            if (lane == 0) s_red[warp] = make_float4(part, mx, z, 0.f);
            bar_sync(1, 384);
            float tot = 0.f;
            {
                const float4 t = s_red[min(lane & 15, 11)];
                tot = (lane & 15) < 12 ? t.x : 0.f;
#pragma unroll
                for (int o = 8; o > 0; o >>= 1) tot += __shfl_xor_sync(0xffffffffu, tot, o);
                mx = __uint_as_float(__reduce_max_sync(0xffffffffu, __float_as_uint(t.y)));
                z = __uint_as_float(__reduce_max_sync(0xffffffffu, __float_as_uint(t.z)));
            }
            const float inv = __fdividef(1.0f, fmaf(tot, 1.0f / HID, 1e-6f));
            const uint32_t j = max(__float_as_uint(fmaf(mx, inv, 1.0f) * 1.01f) >> 23, 130u) - 130u;
            const float dn = __uint_as_float((127u - j) << 23);
#pragma unroll
            for (int i = 0; i < 4; i++)
                *reinterpret_cast<uint16_t*>(smem + P2_OFF_GRN + (tid + 384 * i) * 2) = pack_f16(fmaf(gx[i], inv, 1.0f) * dn, 0.f);
            up = (HSCALE * 1.00235f) * __uint_as_float(min(acc_exp(z) - 9u + j, 253u) << 23);
            TSTAMP(1, 25);
            bar_sync(1, 384);
            reinterpret_cast<float*>(smem + P2_OFF_BIAS)[tid] = pre[0] + pre[1];
            if (wg == 1 && blockIdx.x < 96) {
                const uint4* src = g_w2img[0] + blockIdx.x * 768 + tid - 128;
                const uint4 fk = *reinterpret_cast<const uint4*>(smem + P2_OFF_GRN + blockIdx.x * 32 + (tid & 8) * 2);
                uint4 v[6];
#pragma unroll
                for (int i = 0; i < 6; i++) v[i] = __ldcg(src + i * 128);
                auto fold = [&](uint32_t b, uint32_t f) { return (h2_mul(b, f) + 0x00040004u) & 0xfff8fff8u; };
#pragma unroll
                for (int i = 0; i < 6; i++)
                    g_w2img[1][blockIdx.x * 768 + tid - 128 + i * 128] = make_uint4(fold(v[i].x, fk.x), fold(v[i].y, fk.y), fold(v[i].z, fk.z), fold(v[i].w, fk.w));
                asm volatile("fence.proxy.async.global;\n" ::: "memory");
                __threadfence();
                __syncwarp();
                if (lane == 0) asm volatile("red.release.gpu.global.add.u32 [%0], 1;\n" ::"l"(&g_img[1]) : "memory");
            }
        }
        TSTAMP(1, 28);
        int kt = k0, pos;
        const uint32_t be = lane < 2 ? mapa(bar_bempty, lane) : 0, be0 = mapa(bar_bempty, 0);
        uint32_t prev = 0, sa = 0, pa = 0;
        auto release_b = [&](uint32_t p, bool on) {
            asm volatile("{\n.reg .pred p, q;\nsetp.ne.u32 q, %2, 0;\nsetp.ne.and.u32 p, %1, 0, q;\n@p mbarrier.arrive.shared::cluster.b64 _, [%0];\n}\n"
                         ::"r"(be + p), "r"(be), "r"((uint32_t)on) : "memory");
        };
        auto arrive1 = [&](uint32_t bar) {
            asm volatile("{\n.reg .pred p;\nsetp.eq.u32 p, %1, %2;\n@p mbarrier.arrive.shared::cta.b64 _, [%0];\n}\n" ::"r"(bar), "r"(be), "r"(be0) : "memory");
        };
        auto seek = [&](int p) {
            pos = p;
            st = p % P2_NB * 8;
            ph = p / P2_NB & 1;
            int v;
            while (true) {
                asm volatile("ld.volatile.shared.u32 %0, [%1];\n" : "=r"(v) : "r"(s_pos) : "memory");
                if (__all_sync(0xffffffffu, v >= p)) break;
                __nanosleep(200);
                SAFE_BREAK
            }
        };
        bool ok_a = false;
        auto fetch = [&](uint4 (&a)[2], uint32_t done, bool rel, bool early) {
            if (!ok_a) mbar_wait(af + sa, pa);
            uint32_t o[6];
            const uint32_t src = s_a + sa * (P2_A / 8);
            asm volatile("ldmatrix.sync.aligned.m8n8.x4.trans.shared.b16 {%0,%1,%2,%3}, [%4];\n"
                         : "=r"(o[0]), "=r"(o[1]), "=r"(o[2]), "=r"(o[3]) : "r"(src) : "memory");
            asm volatile("ldmatrix.sync.aligned.m8n8.x2.trans.shared.b16 {%0,%1}, [%2];\n"
                         : "=r"(o[4]), "=r"(o[5]) : "r"(src + 2048) : "memory");
            if ((sa += 8) == P2_NA * 8) { sa = 0; pa ^= 1; }
            wg_wait<1>();
            release_b(done, rel);
            ok_a = mbar_test(af + sa, pa);
            const bool ok_b = mbar_test(bar_bfull + st, ph);
            p2_unpack(a[0], o[0], o[1], o[2]);
            p2_unpack(a[1], o[3], o[4], o[5]);
            if (early) {
                const uint32_t* t = reinterpret_cast<const uint32_t*>(smem + P2_OFF_GRN) + kt * 16 + q;
#pragma unroll
                for (int i = 0; i < 2; i++)
                    a[i] = make_uint4(h2_mul(a[i].x, t[8 * i]), h2_mul(a[i].y, t[8 * i]), h2_mul(a[i].z, t[8 * i + 4]), h2_mul(a[i].w, t[8 * i + 4]));
                if (++kt == 48) kt = 0;
            }
            if (!ok_b) mbar_wait(bar_bfull + st, ph);
        };
        const uint64_t db0 = make_desc(sbase, 128, 256);
        auto step = [&](const uint4 (&a)[2], uint4 (&an)[2], bool cont, bool early) {
            TR2(0);
            const uint64_t db = db0 + st * (P2_B / 128);
            wg_fence();
            mma_rs_n192(acc0, a[0], db, cont);
            mma_rs_n192(acc1, a[0], db + 384, cont);
            mma_rs_n192(acc0, a[1], db + 768, 1);
            mma_rs_n192(acc1, a[1], db + 768 + 384, 1);
            wg_commit();
            arrive1(af + 3 * P2_NA * 8 - 8 + (sa ? sa : P2_NA * 8));
            const uint32_t done = prev;
            prev = st;
            if ((st += 8) == P2_NB * 8) { st = 0; ph ^= 1; }
            fetch(an, done, cont, early);
            pos++;
        };
        int n = wg == 2 && head ? -1 : wg;
        seek(p2_start(n));
        fetch(a0, 0, false, n <= 0);
#pragma unroll 1
        for (;; n += 3) {
            TSTAMP(1, 2 + n);
            const int p0 = n < 0 || n == P2_ITEMS ? 12 : 0, pe = n <= 0 ? p0 + P2_FOLD / 2 : 0;
            const bool more = n + 3 < P2_ITEMS + tail;
#pragma unroll 1
            for (int p = p0; p < 24; p++) {
                step(a0, a1, p != p0, p < pe);
                step(a1, a0, true, p < pe);
            }
            if (n == P2_ITEMS) {
                flag_wait<true>(&g_half[pair][rank], 1);
                TR2(1);
                wg_wait<0>();
                TR2(2);
                release_b(prev, true);
                uint8_t* o = reinterpret_cast<uint8_t*>(out) + (size_t)((2 * p2_tile(cl, -1) + rank) * 64 + (g & 1) * 32 + w * 8 + (g >> 1)) * P2_XROW + q * 16;
                p2_epilogue_add(acc0, o, up, zero);
                p2_epilogue_add(acc1, o + 384, up, zero);
                TR2(3);
                break;
            }
            mbar_wait(bar_xfull, (n + head) & 1);
            TR2(1);
            wg_wait<0>();
            TR2(2);
            release_b(prev, true);
            p2_epilogue(acc0, acc1, sx, sbase + P2_OFF_BIAS + q * 32, up, zero);
            TR2(3);
            asm volatile("fence.proxy.async.shared::cta;\n" ::: "memory");
            __syncwarp();
            arrive1(bar_oready);
            if (!more) break;
            ok_a = false;
            seek(p2_start(n + 3));
            mbar_wait(bar_bfull + st, ph);
        }
        TSTAMP(1, 30);
    }
}

}

extern "C" void kernel_launch(void* const* d_in, const int* in_sizes, int n_in, void* d_out, int out_size) {
    const __nv_bfloat16* x = (const __nv_bfloat16*)d_in[0];
    const __nv_bfloat16* dw = (const __nv_bfloat16*)d_in[1];
    const __nv_bfloat16* w1 = (const __nv_bfloat16*)d_in[2];
    const __nv_bfloat16* w2 = (const __nv_bfloat16*)d_in[3];
    const __nv_bfloat16* grn_g = (const __nv_bfloat16*)d_in[4];
    const __nv_bfloat16* grn_b = (const __nv_bfloat16*)d_in[5];
    __nv_bfloat16* out = (__nv_bfloat16*)d_out;

    cudaFuncSetAttribute(pass1_kernel, cudaFuncAttributeMaxDynamicSharedMemorySize, P1_SMEM);
    cudaFuncSetAttribute(pass2_kernel, cudaFuncAttributeMaxDynamicSharedMemorySize, P2_SMEM);

    typedef CUresult (*EncodeFn)(CUtensorMap*, CUtensorMapDataType, cuuint32_t, void*, const cuuint64_t*, const cuuint64_t*,
                                 const cuuint32_t*, const cuuint32_t*, CUtensorMapInterleave, CUtensorMapSwizzle,
                                 CUtensorMapL2promotion, CUtensorMapFloatOOBfill);
    static EncodeFn encode = nullptr;
    if (!encode) {
        cudaDriverEntryPointQueryResult qres;
        cudaGetDriverEntryPoint("cuTensorMapEncodeTiled", (void**)&encode, cudaEnableDefault, &qres);
    }
    CUtensorMap wmap;
    const cuuint64_t gdim[2] = {HID, C_DIM};
    const cuuint64_t gstr[1] = {HID * 2};
    const cuuint32_t box[2] = {64, 192}, estr[2] = {1, 1};
    CUresult er = encode(&wmap, CU_TENSOR_MAP_DATA_TYPE_BFLOAT16, 2, (void*)w1, gdim, gstr, box, estr, CU_TENSOR_MAP_INTERLEAVE_NONE,
           CU_TENSOR_MAP_SWIZZLE_128B, CU_TENSOR_MAP_L2_PROMOTION_L2_128B, CU_TENSOR_MAP_FLOAT_OOB_FILL_NONE);
    if (er != CUDA_SUCCESS) printf("tensor map encode failed %d\n", (int)er);

    pass1_kernel<<<NUM_CTAS, 512, P1_SMEM>>>(wmap, x, dw, w1, w2, grn_b, 0);

    cudaLaunchAttribute attr[1];
    attr[0].id = cudaLaunchAttributeProgrammaticStreamSerialization;
    attr[0].val.programmaticStreamSerializationAllowed = 1;
    cudaLaunchConfig_t cfg = {};
    cfg.gridDim = dim3(NUM_CTAS);
    cfg.stream = 0;
    cfg.attrs = attr;
    cfg.numAttrs = 1;
    cfg.blockDim = dim3(512);
    cfg.dynamicSmemBytes = P2_SMEM;
    cudaLaunchKernelEx(&cfg, pass2_kernel, x, grn_g, out, 0);
}
```

```cpp
#include <cuda.h>
#include <cuda_runtime.h>
#include <cuda_bf16.h>
#include <stdint.h>
#include <stdio.h>

namespace {

constexpr int M_TOTAL = 384 * 384;
constexpr int C_DIM   = 384;
constexpr int HID     = 1536;
constexpr int NT128   = M_TOTAL / 128;
constexpr int NUM_CTAS = 132;

constexpr int NGRP = 15;
constexpr int LN_STEP = 2 * NGRP, LN_RING = 2 * LN_STEP;
#define P1_M 101
#define P1_D 10
__device__ __forceinline__ int p1_tile(int t, bool small) {
    return t + (small ? ((t + 1) * P1_M + P1_D - 1) / P1_D : t * P1_D / P1_M);
}
constexpr int LN_TILE = 128 * C_DIM * 2;
constexpr int H_TILE = 64 * HID * 3 / 2;
constexpr int H_HALF = 3072, H_STEP = 6144;

__device__ __align__(1024) uint4 g_h[(size_t)M_TOTAL * HID * 3 / 32];
__device__ __align__(1024) uint4 g_ln[LN_RING * LN_TILE / 16];
__device__ __align__(1024) uint4 g_w2img[2][HID * C_DIM * 2 / 16];
__device__ __align__(16) float g_sums[2][HID + 2 * C_DIM];
__device__ __align__(16) unsigned g_ex[HID];
__device__ unsigned g_epoch, g_par;
__device__ __align__(128) unsigned g_img[2];
__device__ __align__(128) unsigned g_prog;
__device__ __align__(128) unsigned g_half[32][2];
__device__ unsigned g_flag[LN_RING + 3][2][8];
#define TSTAMP(k, i)
#define STAMPT(t, i)
#define TRACE(wg, pos, i)
#define TRACEW(pos, i)

#define TR2(i)
#define TR2P(pos, i)
__host__ __device__ __forceinline__ int perm32(int n) {
    return (n & ~31) | (((n >> 1) & 3) << 3) | (((n >> 3) & 3) << 1) | (n & 1);
}

__device__ __forceinline__ uint32_t smem_u32(const void* p) { return (uint32_t)__cvta_generic_to_shared(p); }

__device__ __forceinline__ void mbar_init(uint32_t bar, uint32_t count) {
    asm volatile("mbarrier.init.shared::cta.b64 [%0], %1;\n" ::"r"(bar), "r"(count) : "memory");
}
__device__ __forceinline__ void mbar_expect_tx(uint32_t bar, uint32_t bytes) {
    asm volatile("mbarrier.arrive.expect_tx.shared::cta.b64 _, [%0], %1;\n" ::"r"(bar), "r"(bytes) : "memory");
}
__device__ __forceinline__ void mbar_arrive(uint32_t bar) {
    asm volatile("mbarrier.arrive.shared::cta.b64 _, [%0];\n" ::"r"(bar) : "memory");
}
__device__ __forceinline__ void mbar_arrive_cluster(uint32_t bar_cluster_addr) {
    asm volatile("mbarrier.arrive.shared::cluster.b64 _, [%0];\n" ::"r"(bar_cluster_addr) : "memory");
}
#define SAFE_BREAK
__device__ __forceinline__ void mbar_wait(uint32_t bar, uint32_t parity) {
    asm volatile(
        "{\n"
        ".reg .pred p;\n"
        "LAB_WAIT:\n"
        "mbarrier.try_wait.parity.shared::cta.b64 p, [%0], %1;\n"
        "@!p bra LAB_WAIT;\n"
        "}\n" ::"r"(bar), "r"(parity) : "memory");
}
__device__ __forceinline__ bool mbar_test(uint32_t bar, uint32_t parity) {
    uint32_t ok;
    asm volatile("{\n.reg .pred p;\n"
                 "mbarrier.test_wait.parity.shared::cta.b64 p, [%1], %2;\n"
                 "selp.u32 %0, 1, 0, p;\n}\n" : "=r"(ok) : "r"(bar), "r"(parity) : "memory");
    return ok != 0;
}
__device__ __forceinline__ uint32_t mapa(uint32_t addr, uint32_t rank) {
    uint32_t r;
    asm volatile("mapa.shared::cluster.u32 %0, %1, %2;\n" : "=r"(r) : "r"(addr), "r"(rank));
    return r;
}
__device__ __forceinline__ void bulk_g2s(uint32_t dst, const void* src, uint32_t bytes, uint32_t bar) {
    asm volatile("cp.async.bulk.shared::cluster.global.mbarrier::complete_tx::bytes [%0], [%1], %2, [%3];\n"
                 ::"r"(dst), "l"(src), "r"(bytes), "r"(bar) : "memory");
}
__device__ __forceinline__ void bulk_g2s_mc(uint32_t dst, const void* src, uint32_t bytes, uint32_t bar, uint16_t mask) {
    asm volatile("cp.async.bulk.shared::cluster.global.mbarrier::complete_tx::bytes.multicast::cluster [%0], [%1], %2, [%3], %4;\n"
                 ::"r"(dst), "l"(src), "r"(bytes), "r"(bar), "h"(mask) : "memory");
}
__device__ __forceinline__ void tma2(uint32_t dst, const CUtensorMap* map, int c0, int c1, uint32_t bar) {
    asm volatile("cp.async.bulk.tensor.2d.shared::cluster.global.tile.mbarrier::complete_tx::bytes [%0], [%1, {%2, %3}], [%4];\n"
                 ::"r"(dst), "l"(map), "r"(c0), "r"(c1), "r"(bar) : "memory");
}
template <bool ACQ>
__device__ __forceinline__ uint32_t flag_wait(const unsigned* p, unsigned target) {
    unsigned v, n = 0;
    do {
        if (ACQ) asm volatile("ld.acquire.gpu.global.u32 %0, [%1];\n" : "=r"(v) : "l"(p) : "memory");
        else asm volatile("ld.relaxed.gpu.global.u32 %0, [%1];\n" : "=r"(v) : "l"(p) : "memory");
        n++;
    } while (v < target);
    return n == 1;
}
__device__ __forceinline__ void ldsm4t(uint32_t (&r)[4], uint32_t addr) {
    asm volatile("ldmatrix.sync.aligned.m8n8.x4.trans.shared.b16 {%0,%1,%2,%3}, [%4];\n"
                 : "=r"(r[0]), "=r"(r[1]), "=r"(r[2]), "=r"(r[3]) : "r"(addr) : "memory");
}
__device__ __forceinline__ void bulk_s2g(void* dst, uint32_t src, uint32_t bytes) {
    asm volatile("cp.async.bulk.global.shared::cta.bulk_group [%0], [%1], %2;\n" ::"l"(dst), "r"(src), "r"(bytes) : "memory");
}
__device__ __forceinline__ void cluster_sync_relaxed() {
    asm volatile("barrier.cluster.arrive.relaxed.aligned;\nbarrier.cluster.wait.aligned;\n" ::: "memory");
}
__device__ __forceinline__ void gdc_wait() { asm volatile("griddepcontrol.wait;\n" ::: "memory"); }
__device__ __forceinline__ void gdc_launch() { asm volatile("griddepcontrol.launch_dependents;\n" ::: "memory"); }
__device__ __forceinline__ uint32_t cluster_rank() {
    uint32_t r;
    asm volatile("mov.u32 %0, %%cluster_ctarank;\n" : "=r"(r));
    return r;
}
__device__ __forceinline__ bool elect_one() {
    uint32_t pred;
    asm volatile("{\n.reg .pred p;\nelect.sync _|p, 0xffffffff;\nselp.u32 %0, 1, 0, p;\n}\n" : "=r"(pred));
    return pred != 0;
}
__device__ __forceinline__ void wg_fence() { asm volatile("wgmma.fence.sync.aligned;\n" ::: "memory"); }
__device__ __forceinline__ void wg_commit() { asm volatile("wgmma.commit_group.sync.aligned;\n" ::: "memory"); }
template <int N> __device__ __forceinline__ void wg_wait() {
    asm volatile("wgmma.wait_group.sync.aligned %0;\n" ::"n"(N) : "memory");
}
template <int R> __device__ __forceinline__ void reg_inc() { asm volatile("setmaxnreg.inc.sync.aligned.u32 %0;\n" ::"n"(R)); }
template <int R> __device__ __forceinline__ void reg_dec() { asm volatile("setmaxnreg.dec.sync.aligned.u32 %0;\n" ::"n"(R)); }
__device__ __forceinline__ void bar_sync(int id, int n) { asm volatile("bar.sync %0, %1;\n" ::"r"(id), "r"(n) : "memory"); }
__device__ __forceinline__ void bar_arrive(int id, int n) { asm volatile("bar.arrive %0, %1;\n" ::"r"(id), "r"(n) : "memory"); }

__device__ __forceinline__ uint64_t make_desc(uint32_t saddr, uint32_t lbo, uint32_t sbo) {
    return (uint64_t)((saddr & 0x3FFFF) >> 4) | ((uint64_t)(lbo >> 4) << 16) | ((uint64_t)(sbo >> 4) << 32);
}

__device__ __forceinline__ void stg128_cs(void* p, uint32_t a, uint32_t b, uint32_t c, uint32_t d) {
    asm volatile("st.global.cs.v4.u32 [%0], {%1,%2,%3,%4};\n" ::"l"(p), "r"(a), "r"(b), "r"(c), "r"(d) : "memory");
}
__device__ __forceinline__ uint32_t pack_bf16(float lo, float hi) {
    uint32_t r;
    asm("cvt.rn.bf16x2.f32 %0, %1, %2;\n" : "=r"(r) : "f"(hi), "f"(lo));
    return r;
}
__device__ __forceinline__ float bf_lo(uint32_t v) { return __uint_as_float(v << 16); }
__device__ __forceinline__ float bf_hi(uint32_t v) { return __uint_as_float(v & 0xffff0000u); }
__device__ __forceinline__ uint32_t bf2_mul(uint32_t a, uint32_t b) {
    uint32_t r;
    asm("mul.rn.bf16x2 %0, %1, %2;\n" : "=r"(r) : "r"(a), "r"(b));
    return r;
}
__device__ __forceinline__ uint32_t bf2_fma(uint32_t a, uint32_t b, uint32_t c) {
    uint32_t r;
    asm("fma.rn.bf16x2 %0, %1, %2, %3;\n" : "=r"(r) : "r"(a), "r"(b), "r"(c));
    return r;
}
__device__ __forceinline__ uint32_t bf2_add(uint32_t a, uint32_t b) {
    uint32_t r;
    asm("add.rn.bf16x2 %0, %1, %2;\n" : "=r"(r) : "r"(a), "r"(b));
    return r;
}
constexpr float KAPPA = 0.3292034911525734f;
constexpr float GELU_C = 2.423681954311584f;
constexpr float HSCALE = 1.0f / (2.0f * KAPPA);
__device__ __forceinline__ uint32_t acc_exp(float z) { return max(__float_as_uint(z) >> 23, 10u); }
__device__ __forceinline__ void sched_break(int zero) {
    asm volatile("{\n.reg .pred p;\nsetp.ne.s32 p, %0, 0;\nSB_LOOP:\n@p nanosleep.u32 1;\n@p bra SB_LOOP;\n}\n" ::"r"(zero));
}

#define ACCR8(d, o) "+r"(d[o + 0]), "+r"(d[o + 1]), "+r"(d[o + 2]), "+r"(d[o + 3]), "+r"(d[o + 4]), "+r"(d[o + 5]), "+r"(d[o + 6]), "+r"(d[o + 7])
__device__ __forceinline__ void mma_rs_n128(uint32_t (&d)[32], const uint32_t (&a)[4], uint64_t desc, int scale_d) {
    asm volatile(
        "{\n.reg .pred p;\nsetp.ne.b32 p, %37, 0;\n"
        "wgmma.mma_async.sync.aligned.m64n128k16.f16.f16.f16 "
        "{%0,%1,%2,%3,%4,%5,%6,%7,%8,%9,%10,%11,%12,%13,%14,%15,"
        "%16,%17,%18,%19,%20,%21,%22,%23,%24,%25,%26,%27,%28,%29,%30,%31},"
        "{%32,%33,%34,%35}, %36, p, 1, 1, 0;\n}\n"
        : ACCR8(d, 0), ACCR8(d, 8), ACCR8(d, 16), ACCR8(d, 24)
        : "r"(a[0]), "r"(a[1]), "r"(a[2]), "r"(a[3]), "l"(desc), "r"(scale_d));
}
__device__ __forceinline__ void mma_ss_n128(uint32_t (&d)[32], uint64_t da, uint64_t db) {
    asm volatile(
        "{\n.reg .pred p;\nsetp.ne.b32 p, %34, 0;\n"
        "wgmma.mma_async.sync.aligned.m64n128k16.f16.f16.f16 "
        "{%0,%1,%2,%3,%4,%5,%6,%7,%8,%9,%10,%11,%12,%13,%14,%15,"
        "%16,%17,%18,%19,%20,%21,%22,%23,%24,%25,%26,%27,%28,%29,%30,%31},"
        "%32, %33, p, 1, 1, 0, 0;\n}\n"
        : ACCR8(d, 0), ACCR8(d, 8), ACCR8(d, 16), ACCR8(d, 24)
        : "l"(da), "l"(db), "r"(1));
}
__device__ __forceinline__ uint32_t bf2_as_h2(uint32_t v) { return (v & 0x0fff0fffu) * 7u + v; }
__device__ __forceinline__ float h_lo(uint32_t v) {
    float r;
    asm("{\n.reg .b16 l, h;\nmov.b32 {l, h}, %1;\ncvt.f32.f16 %0, l;\n}\n" : "=f"(r) : "r"(v));
    return r;
}
__device__ __forceinline__ float h_hi(uint32_t v) {
    float r;
    asm("{\n.reg .b16 l, h;\nmov.b32 {l, h}, %1;\ncvt.f32.f16 %0, h;\n}\n" : "=f"(r) : "r"(v));
    return r;
}

__device__ __forceinline__ void mma_rs_n192(uint32_t (&d)[48], const uint4& a, uint64_t db, int scale_d) {
    asm volatile(
        "{\n.reg .pred p;\nsetp.ne.b32 p, %53, 0;\n"
        "wgmma.mma_async.sync.aligned.m64n192k16.f16.f16.f16 "
        "{%0,%1,%2,%3,%4,%5,%6,%7,%8,%9,%10,%11,%12,%13,%14,%15,"
        "%16,%17,%18,%19,%20,%21,%22,%23,%24,%25,%26,%27,%28,%29,%30,%31,"
        "%32,%33,%34,%35,%36,%37,%38,%39,%40,%41,%42,%43,%44,%45,%46,%47},"
        "{%48,%49,%50,%51}, %52, p, 1, 1, 0;\n}\n"
        : ACCR8(d, 0), ACCR8(d, 8), ACCR8(d, 16), ACCR8(d, 24), ACCR8(d, 32), ACCR8(d, 40)
        : "r"(a.x), "r"(a.y), "r"(a.z), "r"(a.w), "l"(db), "r"(scale_d));
}

__device__ __forceinline__ uint32_t pack_f16(float lo, float hi) {
    uint32_t r;
    asm("cvt.rn.f16x2.f32 %0, %1, %2;\n" : "=r"(r) : "f"(hi), "f"(lo));
    return r;
}

constexpr int P1_IMG = 900;
constexpr int P1_SLOT = LN_TILE / 2, P1_NST = 4;
constexpr int P1_X = 16 * C_DIM * 2;
constexpr int P1_OFF_X = P1_SLOT * P1_NST;
constexpr int P1_OFF_A = P1_OFF_X + 2 * P1_X;
constexpr int P1_OFF_BAR = P1_OFF_A + 3 * 2048;
constexpr int P1_OFF_TILE = P1_OFF_BAR + (2 * P1_NST + 3 + 2 + 3 + 2) * 8;
constexpr int P1_OFF_DW = P1_OFF_TILE + 64;
constexpr int P1_SMEM = P1_OFF_DW + C_DIM * 2;

__device__ __forceinline__ float rsqrt_fast(float x) {
    float r;
    asm("rsqrt.approx.ftz.f32 %0, %1;\n" : "=f"(r) : "f"(x));
    return r;
}
__device__ __forceinline__ float sum8(const uint32_t (&c)[4]) {
    const uint32_t u = bf2_add(bf2_add(c[0], c[1]), bf2_add(c[2], c[3]));
    return bf_lo(u) + bf_hi(u);
}
__device__ __forceinline__ void lds128(uint32_t (&v)[4], uint32_t a) {
    asm volatile("ld.shared.v4.u32 {%0,%1,%2,%3}, [%4];\n" : "=r"(v[0]), "=r"(v[1]), "=r"(v[2]), "=r"(v[3]) : "r"(a) : "memory");
}
template <class F>
__device__ __forceinline__ void ln_row(uint32_t (&v)[6][4], uint32_t sdw, F after_loads) {
    uint32_t c[4], s[4], d[4], nm;
#pragma unroll
    for (int i = 0; i < 6; i++) {
        lds128(d, sdw + i * 128);
        if (i == 0) {
#pragma unroll
            for (int k = 0; k < 4; k++) c[k] = bf2_mul(v[0][k], d[k]);
            const float p = sum8(c) * -0.125f;
            nm = pack_bf16(p, p);
        }
#pragma unroll
        for (int k = 0; k < 4; k++) {
            v[i][k] = bf2_fma(v[i][k], d[k], nm);
            s[k] = i ? bf2_add(v[i][k], s[k]) : v[i][k];
            c[k] = i ? bf2_fma(v[i][k], v[i][k], c[k]) : bf2_mul(v[i][k], v[i][k]);
        }
    }
    after_loads(c[0]);
    float m = fmaf(sum8(s), 1.0f / 48, -bf_lo(nm));
    float q = fmaf(-bf_lo(nm), fmaf(2.f, m, bf_lo(nm)), sum8(c) * (1.0f / 48));
#pragma unroll
    for (int o = 1; o < 8; o <<= 1) {
        m += __shfl_xor_sync(0xffffffffu, m, o);
        q += __shfl_xor_sync(0xffffffffu, q, o);
    }
    m *= 0.125f;
    const float r = KAPPA * rsqrt_fast(fmaxf(fmaf(-m, m, q * 0.125f), 0.f) + 1e-5f);
    const float e = (-bf_lo(nm) - m) * r * 0x1p-112f;
    const bool two = __any_sync(0xffffffffu, r < 0x1p-14f);
    const float r1 = r * (two ? 0x1p-56f : 0x1p-112f);
    uint32_t mul = pack_bf16(r1, r1), add = two ? 0u : pack_bf16(e, e);
#pragma unroll 1
    for (int it = !two; it < 2; it++) {
#pragma unroll
        for (int i = 0; i < 6; i++)
#pragma unroll
            for (int k = 0; k < 4; k++) v[i][k] = bf2_fma(v[i][k], mul, add);
        mul = 0x23802380u;
        add = pack_bf16(e, e);
    }
#pragma unroll
    for (int i = 0; i < 6; i++)
#pragma unroll
        for (int k = 0; k < 4; k++) v[i][k] = bf2_as_h2(v[i][k]);
}

__device__ __forceinline__ float gelu_s(float y) {
    float u = y * fmaf(y, y, GELU_C);
    float t;
    asm volatile("tanh.approx.f32 %0, %1;\n" : "=f"(t) : "f"(u));
    return fmaf(y, t, y);
}
__device__ __forceinline__ void p1_pack(int c, uint32_t (&p)[4], uint32_t (&dd)[4]) {
#pragma unroll
    for (int u = 0; u < 4; u++) {
        if ((c & 3) == 0) dd[u] = p[u];
        else {
            uint32_t n = dd[u];
            if ((c & 3) == 1) n = __byte_perm(n, 0, 0x2301);
            if ((c & 3) == 2) {
                dd[u] = __byte_perm(n >> 3, n >> 1, 0x6341);
                n = __byte_perm(n >> 3, n >> 1, 0x7250);
            }
            asm("lop3.b32 %0, %0, %1, 0x40074007, 0xd8;\n" : "+r"(p[u]) : "r"(n));
        }
    }
}
__device__ __forceinline__ void p1_store(int c, const uint32_t (&p)[4], uint8_t* hptr) {
    if (c & 3) stg128_cs(hptr + (c >> 2) * H_HALF + ((c & 3) - 1) * 512, p[0], p[1], p[2], p[3]);
}

template <bool GEN>
__device__ __forceinline__ void p1_epilogue(uint32_t (&acc)[32], float (&ssq)[2], uint32_t sc2, uint8_t* hp, int zero) {
    uint32_t sq[2], dd[4];
#pragma unroll
    for (int c = 0; c < 8; c++) {
        if (GEN) sched_break(zero);
        uint32_t p[4];
#pragma unroll
        for (int u = 0; u < 4; u++) {
            const uint32_t y = acc[8 * (c >> 1) + 2 * u + (c & 1)];
            if (GEN) {
                const float sc = c & 1 ? bf_hi(sc2) : bf_lo(sc2), fs = __uint_as_float(0x78000000u - __float_as_uint(sc));
                const float g0 = gelu_s(h_lo(y) * fs), g1 = gelu_s(h_hi(y) * fs);
                ssq[c & 1] = fmaf(g1, g1, fmaf(g0, g0, ssq[c & 1]));
                p[u] = pack_f16(g0 * sc, g1 * sc);
            } else {
                uint32_t g;
                asm("{\n.reg .b32 w;\n"
                    "fma.rn.f16x2 w, %1, %1, %2;\n"
                    "mul.rn.f16x2 w, w, %1;\n"
                    "tanh.approx.f16x2 w, w;\n"
                    "fma.rn.f16x2 %0, %1, w, %1;\n}\n" : "=r"(g) : "r"(y), "r"(0x40d940d9u));
                acc[8 * (c >> 1) + 2 * u + (c & 1)] = g;
                if (c < 2 && u == 0) asm("mul.rn.f16x2 %0, %1, %1;\n" : "=r"(sq[c & 1]) : "r"(g));
                else asm("fma.rn.f16x2 %0, %1, %1, %0;\n" : "+r"(sq[c & 1]) : "r"(g));
                if (c & 1) asm("{\n.reg .b16 l, h;\n.reg .b32 f;\nmov.b32 {l, h}, %2;\nmov.b32 f, {h, h};\nmul.rn.f16x2 %0, %1, f;\n}\n" : "=r"(p[u]) : "r"(g), "r"(sc2));
                else asm("{\n.reg .b16 l, h;\n.reg .b32 f;\nmov.b32 {l, h}, %2;\nmov.b32 f, {l, l};\nmul.rn.f16x2 %0, %1, f;\n}\n" : "=r"(p[u]) : "r"(g), "r"(sc2));
            }
        }
        p1_pack(c, p, dd);
        if (c & 3) {
#pragma unroll
            for (int u = 0; u < 4; u++) acc[4 * (c - 1 - (c >> 2)) + u] = p[u];
        }
        p1_store(c, p, hp);
    }
    if (!GEN) {
#pragma unroll
        for (int r = 0; r < 2; r++) ssq[r] += h_lo(sq[r]) + h_hi(sq[r]);
    }
}
__device__ __forceinline__ void p1_consumer(const uint32_t (&a)[24][4], uint32_t sc2, bool gen, uint32_t sbase, int wg, int nwg, int cb,
                                            int w, int lane, int zero) {
    const uint32_t bar_full = sbase + P1_OFF_BAR, bar_empty = bar_full + P1_NST * 8;
    const uint32_t empty_remote = mapa(bar_empty, lane & 1);
    const int g = lane >> 2, q = lane & 3, turn = wg + 1 == nwg ? 1 : wg + 2;
    float ssq[2] = {0.f, 0.f};
    uint32_t acc[32] = {};
    TSTAMP(0, 1);
    STAMPT(128, 4);
    STAMPT(256, 5);

    uint8_t* hp = reinterpret_cast<uint8_t*>(g_h) + ((cb * 2 + (w >> 1)) * H_STEP + (w & 1) * 1536) + g * 64 + (q ^ (g >> 1)) * 16;
    const uint64_t desc_base = make_desc(sbase, 16, 1024) | (1ull << 62);
    const uint64_t da = make_desc(sbase + P1_OFF_A + wg * 2048, 128, 256);
#pragma unroll 1
    for (int i = 0;; i++) {
        const int s0 = (i & 1) * 16, par = (i >> 1) & 1;
        const uint64_t d0 = desc_base + (uint64_t)((i & 1) * (LN_TILE / 16));
        TRACE(wg, i, 0);
        mbar_wait(bar_full + s0, par);
        bar_sync(1 + wg, 256);
        TRACE(wg, i, 1);
        uint32_t step, more;
        wg_fence();
#pragma unroll
        for (int k = 0; k < 24; k++) {
            if (k == 12) mbar_wait(bar_full + s0 + 8, par);
            const uint64_t db = d0 + (uint64_t)((k >> 2) * 1024 + (k & 3) * 2);
            if (k < 23) mma_rs_n128(acc, a[k], db, k ? 1 : zero);
            else mma_ss_n128(acc, da, db);
            if (k == 23) bar_arrive(turn, 256);
            if (k % 12 == 11) wg_commit();
        }
        asm volatile("ld.shared.v2.u32 {%0, %1}, [%2];\n" : "=r"(step), "=r"(more) : "r"(sbase + P1_OFF_TILE + (i & 3) * 16) : "memory");
        TRACE(wg, i, 2);
        wg_wait<1>();
        if (lane < 2) mbar_arrive_cluster(empty_remote + s0);
        hp += step;
        TRACE(wg, i, 3);
        wg_wait<0>();
        TRACE(wg, i, 4);
        if (lane < 2) mbar_arrive_cluster(empty_remote + s0 + 8);
        if (gen) p1_epilogue<true>(acc, ssq, sc2, hp, zero);
        else p1_epilogue<false>(acc, ssq, sc2, hp, zero);
        if (!more) break;
    }
    TSTAMP(0, 21);
    if (wg == 0) bar_sync(1, 256);
    uint32_t par;
    asm volatile("ld.shared.u32 %0, [%1];\n" : "=r"(par) : "r"(sbase + P1_OFF_TILE - 4) : "memory");
    float* sums = g_sums[par];
#pragma unroll
    for (int r = 0; r < 2; r++) {
        ssq[r] += __shfl_xor_sync(0xffffffffu, ssq[r], 1);
        ssq[r] += __shfl_xor_sync(0xffffffffu, ssq[r], 2);
        if (q == 0) atomicAdd(sums + cb * 64 + w * 16 + r * 8 + g, ssq[r]);
    }
}

__device__ __forceinline__ void p1_w2(const __nv_bfloat16* __restrict__ w2, const __nv_bfloat16* __restrict__ grn_b, int w, int lane) {
    const int gw = (blockIdx.x - 8 * NGRP) * 4 + w;
    float* sums = g_sums[__ldcg(&g_epoch) & 1] + HID;
    flag_wait<true>(&g_flag[40][1][0], 12);
    {
        const int col = gw % 6 * 64 + lane * 2;
        float bsum[2] = {0.f, 0.f}, asum[2] = {0.f, 0.f};
#pragma unroll 4
        for (int kk = 0; kk < 192; kk++) {
            const int k = gw / 6 * 192 + kk;
            const uint32_t v = *reinterpret_cast<const uint32_t*>(w2 + k * C_DIM + col);
            const float b = __bfloat162float(grn_b[k]), f = __uint_as_float(__ldcg(&g_ex[k]) << 23);
            bsum[0] = fmaf(b, bf_lo(v), bsum[0]);
            bsum[1] = fmaf(b, bf_hi(v), bsum[1]);
            asum[0] = fmaf(f, fabsf(bf_lo(v)), asum[0]);
            asum[1] = fmaf(f, fabsf(bf_hi(v)), asum[1]);
        }
#pragma unroll
        for (int j = 0; j < 2; j++) {
            atomicAdd(sums + col + j, bsum[j]);
            atomicAdd(sums + C_DIM + col + j, asum[j]);
        }
        __threadfence();
        __syncwarp();
        if (lane == 0) asm volatile("red.relaxed.gpu.global.add.u32 [%0], 1;\n" ::"l"(&g_flag[LN_RING + 2][0][0]) : "memory");
    }
    while (*(volatile unsigned*)&g_flag[P1_IMG % LN_RING][1][0] < 12 * (P1_IMG / LN_RING + 1)) {
        __nanosleep(2000);
        SAFE_BREAK
    }
    flag_wait<true>(&g_flag[LN_RING + 2][0][0], 48);
    float z = 0.f;
#pragma unroll
    for (int j = 0; j < C_DIM / 32; j++) z = fmaxf(z, __ldcg(sums + C_DIM + j * 32 + lane));
    const float sc = __uint_as_float((263u - acc_exp(__uint_as_float(__reduce_max_sync(0xffffffffu, __float_as_uint(z))))) << 23);
    const int np = gw % 6 * 64 + lane * 2;
#pragma unroll 2
    for (int cc = 0; cc < 24; cc++) {
        const int c = gw / 6 * 24 + cc;
        uint32_t v[8], o[2][4];
#pragma unroll
        for (int e = 0; e < 8; e++) v[e] = *reinterpret_cast<const uint32_t*>(w2 + (c * 8 + e) * C_DIM + perm32(np));
#pragma unroll
        for (int e = 0; e < 4; e++) {
            const uint2 t = __ldcg(reinterpret_cast<const uint2*>(g_ex) + c * 4 + e);
            const float f0 = __uint_as_float(t.x << 23), f1 = __uint_as_float(t.y << 23);
            o[0][e] = pack_f16(bf_lo(v[2 * e]) * f0 * sc, bf_lo(v[2 * e + 1]) * f1 * sc);
            o[1][e] = pack_f16(bf_hi(v[2 * e]) * f0 * sc, bf_hi(v[2 * e + 1]) * f1 * sc);
        }
#pragma unroll
        for (int j = 0; j < 2; j++)
            g_w2img[0][(((c >> 1) * 48 + (np >> 3)) * 2 + (c & 1)) * 8 + (np & 7) + j] = make_uint4(o[j][0], o[j][1], o[j][2], o[j][3]);
    }
    asm volatile("fence.proxy.async.global;\n" ::: "memory");
    __threadfence();
    __syncwarp();
    if (lane == 0) asm volatile("red.relaxed.gpu.global.add.u32 [%0], 1;\n" ::"l"(&g_img[0]) : "memory");
}

__global__ void __cluster_dims__(2, 1, 1) __launch_bounds__(512, 1)
pass1_kernel(const __grid_constant__ CUtensorMap wmap, const __nv_bfloat16* __restrict__ x, const __nv_bfloat16* __restrict__ dw,
             const __nv_bfloat16* __restrict__ w1, const __nv_bfloat16* __restrict__ w2, const __nv_bfloat16* __restrict__ grn_b, int zero) {
    extern __shared__ __align__(1024) uint8_t smem[];
    const uint32_t sbase = smem_u32(smem);
    const uint32_t bar_full = sbase + P1_OFF_BAR, bar_empty = bar_full + P1_NST * 8, bar_w = bar_empty + P1_NST * 8;
    const uint32_t bar_xfull = bar_w + 24, bar_raw = bar_xfull + 16, bar_done = bar_raw + 16;
    const int tid = threadIdx.x;
    const int warp = __shfl_sync(0xffffffffu, tid >> 5, 0), lane = tid & 31;
    const uint32_t rank = cluster_rank();
    const int cl = blockIdx.x >> 1;
    const bool small = cl >= 4 * NGRP;
    const int nwg = small ? 2 : 3, cb0 = small ? (blockIdx.x - 8 * NGRP) * 2 : (blockIdx.x & 7) * 3;
    uint8_t* const ring = reinterpret_cast<uint8_t*>(g_ln);
    const int ln0 = 2 + (blockIdx.x >> 2), items = blockIdx.x >= 128 ? -1 : small ? 1 : (NT128 - 1 - ln0) / LN_STEP + 1;

    TSTAMP(0, 0);
    TRACEW(110 + warp, 0);

    if (warp >= 12) {
        reg_dec<56>();
        asm volatile("barrier.cluster.arrive.relaxed.aligned;\n" ::: "memory");
        asm volatile("barrier.cluster.wait.aligned;\n" ::: "memory");
        {
            auto ring_row = [&](int p) {
                const int n = (p & 8) * 8 + (lane >> 3) * 8 + (p & 3) * 2 + (p >> 2 & 1);
                return n * 128 + (((lane ^ n) & 7) << 4);
            };
            const uint8_t* xsrc = reinterpret_cast<const uint8_t*>(x) + (size_t)(32 * 8 + blockIdx.x * 2 + (warp & 1)) * P1_X;
            const uint32_t xbar = bar_xfull + (warp & 1) * 8, xdst = sbase + P1_OFF_X + (warp & 1) * P1_X;
            const uint32_t sdw = sbase + P1_OFF_DW + (lane & 7) * 16;
            uint32_t src = xdst - P1_OFF_X + (lane >> 3) * (C_DIM * 2) + (lane & 7) * 16;
            int row0 = ring_row((blockIdx.x & 7) * 2 + (warp & 1)) ^ 288, slot = blockIdx.x >> 3, used = 0;
            auto next = [&]() {
                xsrc += (size_t)LN_STEP * 8 * P1_X;
                if (elect_one()) {
                    mbar_expect_tx(xbar, P1_X);
                    bulk_g2s(xdst, xsrc, P1_X, xbar);
                }
                __syncwarp();
            };
#pragma unroll 1
            for (int i = -1; i < items; i++) {
                if (warp == 14) TRACEW(128 + i, 0);
                const int last = i > 0 ? 3 : i ? 2 + (warp >> 1 & 1) : 1;
#pragma unroll 1
                for (int ps = i < 0 ? last - 4 : 0; ps <= last; ps += i < 0 ? 4 : 1) {
                    if (i < 0 && ps > 0) STAMPT(416, 6);
                    if (i < 0 && ps > 0) mbar_wait(bar_raw, 0);
                    if (i < 0 && ps > 0) STAMPT(416, 7);
                    if (ps == 0) {
                        if (used) flag_wait<false>(&g_flag[slot][1][0], used);
                        if (i && i + 1 < items && elect_one())
                            asm volatile("cp.async.bulk.prefetch.L2.global [%0], %1;\n" ::"l"(xsrc + (size_t)LN_STEP * 8 * P1_X), "r"(P1_X) : "memory");
                        if (i) mbar_wait(xbar, ~i & 1);
                        else mbar_wait(bar_raw + 8, 0);
                        if (warp == 14) TRACEW(128 + i, 1);
                    }
                    uint32_t v[6][4];
#pragma unroll
                    for (int j = 0; j < 6; j++) lds128(v[j], src + (ps & 3) * (4 * C_DIM * 2) + j * 128);
                    ln_row(v, sdw, [&](uint32_t dep) {
                        if (i == 0 && ps == 1 && lane < 2) mbar_arrive_cluster(mapa(bar_empty, lane) + (dep & zero));
                        if (ps == 3 && i > 0 && i + 1 < items && !__any_sync(0xffffffffu, dep & zero)) next();
                    });
                    uint8_t* dst = ring + (slot * LN_TILE + (ps & 1) * 4096 + (row0 ^ (ps & 2) * 144));
#pragma unroll
                    for (int j = 0; j < 6; j++)
                        asm volatile("{\n.reg .pred p;\nsetp.ge.s32 p, %5, 0;\n@p st.global.v4.u32 [%0], {%1,%2,%3,%4};\n}\n"
                                     ::"l"(dst + j * 16384), "r"(v[j][0]), "r"(v[j][1]), "r"(v[j][2]), "r"(v[j][3]), "r"(ps) : "memory");
                }
                if (warp == 14) TRACEW(128 + i, 2);
                asm volatile("fence.proxy.async.global;\nfence.acq_rel.cta;\n" ::: "memory");
                if (i < 0) {
                    bar_sync(4, 128);
                    if (warp < 14) break;
                    row0 ^= 288;
                    slot += 16;
                } else {
                    if (i) mbar_wait(bar_done, ~i & 1);
                    else {
                        src += P1_OFF_X;
                        slot = ln0;
                        row0 = ring_row((blockIdx.x & 3) * 4 + (warp & 1) * 2);
                    }
                    __syncwarp();
                    if (lane == 0) mbar_arrive(bar_done);
                    if ((slot += LN_STEP) >= LN_RING) { slot -= LN_RING; used += 12; }
                }
            }
            if ((warp < 14 || items < 0) && lane < 2) mbar_arrive_cluster(mapa(bar_empty, lane));
        }
        if (warp == 12) {
            int prev = 0, t = p1_tile(small ? 0 : cl >> 2, small), next = p1_tile(small ? 1 : (cl >> 2) + NGRP, small);
            const uint32_t rbase = mapa(sbase, lane & 1);
            int i = 0;
#pragma unroll 1
            for (; t < NT128; i++) {
                const int s0 = (i & 1) * 2, par = (i >> 1) & 1;
                const int round = t / LN_RING, slot = t - round * LN_RING;
                const uint8_t* src = ring + slot * LN_TILE + rank * (P1_SLOT / 2);
                int draw = i + 2;
                if (rank == 0 && lane == 0 && !small) draw = 2 * NGRP + atomicAdd(&g_flag[LN_RING + ((cl >> 1) & 1)][cl & 1][0], 1u);
                flag_wait<true>(&g_flag[slot][0][0], 8 * round + 8);
                TRACEW(i, 2);
                if (i == 0) STAMPT(384, 10);
                if (i == 2) STAMPT(384, 13);
                if (i == 3) STAMPT(384, 14);
                asm volatile("fence.proxy.async.global;\n" ::: "memory");
                draw = p1_tile(__shfl_sync(0xffffffffu, draw, 0), small);
#pragma unroll
                for (int h = 0; h < 2; h++) {
                    mbar_wait(bar_empty + (s0 + h) * 8, par);
                    TRACEW(i, 4 + h);
                    if (i == 0 && h == 1) STAMPT(384, 11);
                    if (elect_one()) {
                        mbar_expect_tx(bar_full + (s0 + h) * 8, P1_SLOT + 16 - 16 * h);
                        bulk_g2s_mc(sbase + (s0 + h) * P1_SLOT + rank * (P1_SLOT / 2), src + h * P1_SLOT, P1_SLOT / 2, bar_full + (s0 + h) * 8, (uint16_t)3);
                    }
                    __syncwarp();
                    if (h == 0 && rank == 0 && lane < 2)
                        asm volatile("st.async.shared::cluster.mbarrier::complete_tx::bytes.v4.u32 [%0], {%1, %2, %3, %3}, [%4];\n"
                                     ::"r"(rbase + P1_OFF_TILE + (i & 3) * 16), "r"((t - prev) * (2 * H_TILE)), "r"((int)(next < NT128)), "r"(draw),
                                       "r"(rbase + P1_OFF_BAR + s0 * 8) : "memory");
                }
                prev = t;
                t = next;
                next = draw;
                if (rank != 0) {
                    mbar_wait(bar_full + s0 * 8, (i >> 1) & 1);
                    mbar_wait(bar_full + s0 * 8 + 8, (i >> 1) & 1);
                    if (lane == 0) asm volatile("red.relaxed.gpu.global.add.u32 [%0], %1;\n" ::"l"(&g_flag[slot][1][0]), "r"(nwg) : "memory");
                    asm volatile("ld.shared.u32 %0, [%1];\n" : "=r"(next) : "r"(sbase + P1_OFF_TILE + (i & 3) * 16 + 8) : "memory");
                    TRACEW(i, 3);
                }
            }
#pragma unroll 1
            for (int j = 2 * i; j < 2 * i + 4; j++) mbar_wait(bar_empty + (j & 3) * 8, (j >> 2) & 1);
        } else if (warp == 13) {
            STAMPT(416, 8);
            if (lane == 0 && blockIdx.x < 128) asm volatile("red.release.gpu.global.add.u32 [%0], 1;\n" ::"l"(&g_flag[blockIdx.x >> 3][0][0]) : "memory");
            __syncwarp();
            STAMPT(416, 9);
            const uint32_t ep = g_epoch & 1;
            asm volatile("st.shared.u32 [%0], %1;\n" ::"r"(sbase + P1_OFF_TILE - 4), "r"(ep) : "memory");
            if (blockIdx.x == 18) g_par = ep;
            if (blockIdx.x < 18) reinterpret_cast<float4*>(g_sums[ep ^ 1])[blockIdx.x * 32 + lane] = make_float4(0.f, 0.f, 0.f, 0.f);
#pragma unroll 1
            for (int i = 0; i < items; i++) {
                mbar_wait(bar_done, i & 1);
                asm volatile("fence.proxy.async.global;\n" ::: "memory");
                if (lane == 0) {
                    mbar_arrive(bar_done);
                    asm volatile("red.release.gpu.global.add.u32 [%0], %1;\n"
                                 ::"l"(&g_flag[i ? (ln0 + (i & 1) * LN_STEP) % LN_RING : 16 + (blockIdx.x >> 3)][0][0]), "r"(i ? 2 : 1) : "memory");
                }
                __syncwarp();
                TRACEW(128 + i, 3);
            }
            flag_wait<true>(&g_flag[LN_RING + 2][0][0], 48);
        }
    } else {
        if (tid == 0) {
            mbar_init(bar_raw, 1);
            mbar_init(bar_raw + 8, 1);
            mbar_init(bar_xfull, 1);
            mbar_init(bar_xfull + 8, 1);
            for (int i = 0; i < 3; i++) mbar_init(bar_w + i * 8, 1);
            asm volatile("fence.mbarrier_init.release.cluster;\n" ::: "memory");
            if (blockIdx.x < 128) {
                mbar_expect_tx(bar_raw, P1_X + C_DIM * 2);
                bulk_g2s(sbase + P1_OFF_DW, dw, C_DIM * 2, bar_raw);
                for (int i = 0; i < 2; i++) bulk_g2s(sbase + i * P1_X + P1_X / 2, x + (size_t)(blockIdx.x * 16 + i * 8) * C_DIM, P1_X / 2, bar_raw);
                asm volatile("cp.async.bulk.prefetch.L2.global [%0], 9216;\n" ::"l"(w1 + blockIdx.x * 4608) : "memory");
                mbar_expect_tx(bar_raw + 8, P1_X);
                for (int i = 0; i < 2; i++) bulk_g2s(sbase + i * P1_X, x + (size_t)(16 * 128 + blockIdx.x * 16 + i * 8) * C_DIM, P1_X / 2, bar_raw + 8);
            }
            for (int i = 0; i < nwg; i++) {
                mbar_expect_tx(bar_w + i * 8, P1_SLOT);
                tma2(sbase + (1 + i) * P1_SLOT, &wmap, (cb0 + i) * 64, 0, bar_w + i * 8);
                tma2(sbase + (1 + i) * P1_SLOT + P1_SLOT / 2, &wmap, (cb0 + i) * 64, 192, bar_w + i * 8);
            }
            for (int i = 0; i < 2 && !small; i++) {
                mbar_expect_tx(bar_xfull + i * 8, P1_X);
                bulk_g2s(sbase + P1_OFF_X + i * P1_X, x + (size_t)(32 * 128 + blockIdx.x * 32 + i * 16) * C_DIM, P1_X, bar_xfull + i * 8);
            }
        }
        if (tid == 32) {
            mbar_init(bar_done, 3);
            mbar_arrive(bar_done);
            asm volatile("fence.mbarrier_init.release.cluster;\n" ::: "memory");
        }
        if (tid == 64) {
            for (int i = 0; i < P1_NST; i++) {
                mbar_init(bar_full + i * 8, 1);
                mbar_init(bar_empty + i * 8, 8 * nwg);
            }
            asm volatile("fence.mbarrier_init.release.cluster;\n" ::: "memory");
            if (blockIdx.x < 64) (&g_half[0][0])[blockIdx.x] = 0;
            else if (blockIdx.x == 64) g_prog = 0;
            else if (blockIdx.x < 67) g_img[blockIdx.x - 65] = 0;
        }
        __syncwarp();
        asm volatile("barrier.cluster.arrive.relaxed.aligned;\n" ::: "memory");
        reg_inc<152>();
        TRACEW(110 + warp, 1);
        const int wg = warp >> 2, w = warp & 3;
        gdc_launch();
        asm volatile("barrier.cluster.wait.aligned;\n" ::: "memory");
        if (wg == nwg) {
            p1_w2(w2, grn_b, w, lane);
            return;
        }
        const uint32_t slot_free = mapa(bar_empty, lane & 1) + (lane >> 1) * 8;
        if (lane < 8 && (lane >> 1) != 1 + wg && (wg || lane > 1)) mbar_arrive_cluster(slot_free);
        if (wg == 1) bar_arrive(1, 256);
        uint32_t a[24][4], ex[2], gen = 0;
        const uint32_t wsrc = sbase + (1 + wg) * P1_SLOT + ((lane >> 4) * 8 + (lane & 7)) * 128 + (((2 * w + ((lane >> 3) & 1)) ^ (lane & 7)) << 4);
#pragma unroll 1
        for (int it = 0; it < 2; it++) {
            if (it) mbar_wait(bar_w + wg * 8, 0);
            TRACEW(110 + warp, 5);
            if (it || wg == 0) {
#pragma unroll
            for (int k = 0; k < 24; k++) ldsm4t(a[k], wsrc + k * 2048);
#pragma unroll
            for (int r = 0; r < 2; r++) {
                float t = 0.f;
#pragma unroll
                for (int j = 0; j < 6; j++) {
                    uint32_t c = bf2_mul(a[4 * j][r], a[4 * j][r]);
#pragma unroll
                    for (int k = 1; k < 8; k++) c = bf2_fma(a[4 * j + k / 2][r + (k & 1) * 2], a[4 * j + k / 2][r + (k & 1) * 2], c);
                    t += bf_lo(c) + bf_hi(c);
                }
                t += __shfl_xor_sync(0xffffffffu, t, 1);
                t += __shfl_xor_sync(0xffffffffu, t, 2);
                asm("sqrt.approx.f32 %0, %0;\n" : "+f"(t));
                ex[r] = min(max(__float_as_uint(13.9f * t) >> 23, 72u), 198u);
            }
            asm volatile("{\n.reg .pred p;\nsetp.gt.u32 p, %1, 7;\nbar.red.or.pred p, %2, 128, p;\nselp.u32 %0, 1, 0, p;\n}\n"
                         : "=r"(gen) : "r"(max(ex[0] - 125u, ex[1] - 125u)), "r"(5 + wg) : "memory");
            gen = __shfl_sync(0xffffffffu, gen, 0) & it;
            if (it) {
                if ((lane & 3) < 2) g_ex[(cb0 + wg) * 64 + w * 16 + (lane & 1) * 8 + (lane >> 2)] = lane & 1 ? ex[1] : ex[0];
                if ((lane >> 1) == 1 + wg) mbar_arrive_cluster(slot_free);
                __syncwarp();
            }
            }
            if (gen) {
#pragma unroll
                for (int k = 0; k < 24; k++)
#pragma unroll
                    for (int j = 0; j < 4; j++) a[k][j] = bf2_mul(a[k][j], (268u - ex[j & 1]) * 0x00800080u);
            }
            if (it || wg == 1) {
#pragma unroll
                for (int k = 0; k < 24; k++)
#pragma unroll
                    for (int j = 0; j < 4; j++) {
                        a[k][j] = bf2_as_h2(bf2_mul(a[k][j], 0x07800780u));
                        asm volatile("" : "+r"(a[k][j]));
                    }
            }
            TRACEW(110 + warp, 6);
        }
#pragma unroll
        for (int j = 0; j < 4; j++)
            asm volatile("st.shared.u32 [%0], %1;\n" ::"r"(sbase + P1_OFF_A + warp * 512 + (j & 1) * 256 + (j >> 1) * 128 + lane * 4), "r"(a[23][j]) : "memory");
        asm volatile("fence.proxy.async.shared::cta;\n" ::: "memory");
        TRACEW(110 + warp, 7);
        const uint32_t ex2 = ex[0] | ex[1] << 16;
        p1_consumer(a, gen ? 0x7f007f00u - (ex2 << 7) : (0x008e008eu - ex2) << 10, gen, sbase, wg, nwg, cb0 + wg, w, lane, zero);
        TSTAMP(0, 30);
    }
}

constexpr int P2_B = 24576, P2_NB = 5;
constexpr int P2_A = 3072, P2_NA = 5;
constexpr int P2_XROW = C_DIM * 2;
constexpr int P2_OFF_A = P2_B * P2_NB;
constexpr int P2_OFF_X = P2_OFF_A + 3 * P2_NA * P2_A;
constexpr int P2_XHALF = 32 * P2_XROW + 64;
constexpr int P2_OFF_BIAS = P2_OFF_X + 64 * P2_XROW + 64;
constexpr int P2_OFF_GRN = P2_OFF_BIAS + C_DIM * 4;
constexpr int P2_OFF_BAR = P2_OFF_GRN + HID * 2;
constexpr int P2_SMEM = P2_OFF_BAR + (2 * P2_NB + 6 * P2_NA + 3) * 8;
constexpr int P2_LAG = 17;
constexpr int P2_NCL = NUM_CTAS / 2, P2_ITEMS = NT128 / P2_NCL, P2_SHARED = NT128 - P2_ITEMS * P2_NCL;
constexpr int P2_POS = P2_LAG * (P2_ITEMS - 1) + 48;
__device__ __forceinline__ int p2_start(int n) { return n < 0 ? 0 : n == P2_ITEMS ? P2_POS - 24 : P2_LAG * n; }
constexpr int P2_FOLD = 17;
constexpr int P2_XC = 8 * P2_XROW;
constexpr int P2_DELTA = 7;
__device__ __forceinline__ int p2_tile(int cl, int n) {
    return n == 0 ? NT128 - 1 - cl : n < 0 || n == P2_ITEMS ? NT128 - 1 - P2_NCL - (cl >> 1) : cl + P2_NCL * (n - 1);
}

constexpr int P2_EG = 2;
__device__ __forceinline__ void p2_epilogue(const uint32_t (&acc0)[48], const uint32_t (&acc1)[48], uint32_t sx, uint32_t sb, float up, int zero) {
    uint32_t v[2][P2_EG][4];
    float b[2][8];
    auto load = [&](int c, uint32_t a) {
#pragma unroll
        for (int j = 0; j < 2; j++)
            asm volatile("ld.shared.v4.f32 {%0,%1,%2,%3}, [%4];\n" : "=f"(b[c & 1][4 * j]), "=f"(b[c & 1][4 * j + 1]), "=f"(b[c & 1][4 * j + 2]), "=f"(b[c & 1][4 * j + 3])
                         : "r"(sb + c * 128 + j * 16) : "memory");
#pragma unroll
        for (int j = 0; j < P2_EG; j++) {
            const int u = c * P2_EG + j;
            asm volatile("ld.shared.v4.u32 {%0,%1,%2,%3}, [%4];\n" : "=r"(v[c & 1][j][0]), "=r"(v[c & 1][j][1]), "=r"(v[c & 1][j][2]), "=r"(v[c & 1][j][3])
                         : "r"(a + (u >> 1) * 64 + (u & 1) * 4 * P2_XROW) : "memory");
        }
    };
    load(0, sx);
#pragma unroll
    for (int c = 0; c < 24 / P2_EG; c++) {
        if (c + 1 < 24 / P2_EG) load(c + 1, sx + (v[c & 1][P2_EG - 1][0] & zero));
#pragma unroll
        for (int j = 0; j < P2_EG; j++) {
            const int u = c * P2_EG + j, i = 8 * ((u >> 1) % 6) + (u & 1);
            const uint32_t (&acc)[48] = u < 12 ? acc0 : acc1;
            uint32_t (&w)[4] = v[c & 1][j];
#pragma unroll
            for (int e = 0; e < 4; e++)
                w[e] = bf2_add(pack_bf16(fmaf(h_lo(acc[i + 2 * e]), up, b[c & 1][2 * e]), fmaf(h_hi(acc[i + 2 * e]), up, b[c & 1][2 * e + 1])), w[e]);
            asm volatile("st.shared.v4.u32 [%4], {%0,%1,%2,%3};\n" ::"r"(w[0]), "r"(w[1]), "r"(w[2]), "r"(w[3]),
                         "r"(sx + (u >> 1) * 64 + (u & 1) * 4 * P2_XROW) : "memory");
        }
    }
}

__device__ __forceinline__ void p2_unpack(uint4& u, uint32_t o1, uint32_t o2, uint32_t o3) {
    u.z = o1 & 0xbff8bff8u;
    u.y = o2 & 0xbff8bff8u;
    u.w = o3 & 0xbff8bff8u;
    u.x = (__byte_perm(o1, 0, 0x2301) & 0x07400740u) | ((__byte_perm(o2, o3, 0x6240) << 3) & 0x38383838u) | ((__byte_perm(o2, o3, 0x3715) << 1) & 0x80808080u);
}
__device__ __forceinline__ uint32_t h2_mul(uint32_t a, uint32_t b) {
    uint32_t r;
    asm("mul.rn.f16x2 %0, %1, %2;\n" : "=r"(r) : "r"(a), "r"(b));
    return r;
}
__device__ __forceinline__ void p2_epilogue_add(const uint32_t (&acc)[48], uint8_t* o, float f, int zero) {
#pragma unroll
    for (int t = 0; t < 12; t++) {
        uint32_t v[4];
#pragma unroll
        for (int e = 0; e < 4; e++) {
            v[e] = acc[8 * (t >> 1) + (t & 1) + 2 * e];
            asm volatile("" : "+r"(v[e]));
            v[e] = pack_bf16(h_lo(v[e]) * f, h_hi(v[e]) * f);
        }
        asm volatile("red.global.add.noftz.v4.bf16x2 [%0], {%1,%2,%3,%4};\n" ::"l"(o + (t >> 1) * 64 + (t & 1) * 4 * P2_XROW),
                     "r"(v[0]), "r"(v[1]), "r"(v[2]), "r"(v[3]) : "memory");
        if (t % 3 == 2) sched_break(zero);
    }
}

__global__ void __cluster_dims__(2, 1, 1) __launch_bounds__(512, 1)
pass2_kernel(const __nv_bfloat16* __restrict__ x, const __nv_bfloat16* __restrict__ grn_g, __nv_bfloat16* __restrict__ out, int zero) {
    extern __shared__ __align__(1024) uint8_t smem[];
    const uint32_t sbase = smem_u32(smem);
    const uint32_t bar_bfull = sbase + P2_OFF_BAR, bar_bempty = bar_bfull + P2_NB * 8;
    const uint32_t bar_afull = bar_bempty + P2_NB * 8, bar_aempty = bar_afull + 3 * P2_NA * 8;
    const uint32_t bar_xfull = bar_aempty + 3 * P2_NA * 8, bar_oready = bar_xfull + 8, s_pos = bar_xfull + 16;
    int tid;
    asm volatile("mov.u32 %0, %%tid.x;\n" : "=r"(tid));
    const int warp = __shfl_sync(0xffffffffu, tid >> 5, 0), lane = tid & 31;
    const uint32_t rank = cluster_rank();
    const int cl = blockIdx.x >> 1, pair = cl >> 1;
    const int k0 = (4 * pair + (cl & 1) * (48 - P2_POS % 48)) % 48;
    const int head = pair < P2_SHARED && !(cl & 1), tail = pair < P2_SHARED && (cl & 1);

    uint32_t par, gg[4];
    float pre[4];
    if (warp < 12) {
        asm volatile("ld.global.cg.u32 %0, [%1];\n" : "=r"(par) : "l"(&g_par) : "memory");
#pragma unroll
        for (int i = 0; i < 4; i++) {
            asm volatile("ld.global.cg.f32 %0, [%1];\n" : "=f"(pre[i]) : "l"(&g_sums[i & 1][HID + (i >> 1) * C_DIM + tid]) : "memory");
            asm volatile("ld.global.nc.u16 %0, [%1];\n" : "=r"(gg[i]) : "l"(grn_g + tid + 384 * i) : "memory");
        }
    }
    TSTAMP(1, 0);
    if (tid == 384) {
        for (int i = 0; i < P2_NB; i++) {
            mbar_init(bar_bfull + i * 8, 1);
            mbar_init(bar_bempty + i * 8, 24);
        }
        for (int i = 0; i < 3 * P2_NA; i++) {
            mbar_init(bar_afull + i * 8, 1);
            mbar_init(bar_aempty + i * 8, 4);
        }
        mbar_init(bar_xfull, 2);
        mbar_init(bar_oready, 4);
        asm volatile("st.shared.u32 [%0], 0;\n" ::"r"(s_pos) : "memory");
        asm volatile("fence.mbarrier_init.release.cluster;\n" ::: "memory");
    }
    __syncthreads();
    cluster_sync_relaxed();

    if (warp >= 12) {
        reg_dec<32>();
        if (warp == 12) {
            const uint8_t* wsrc = reinterpret_cast<const uint8_t*>(g_w2img) + rank * (P2_B / 2);
            int st = 0, ph = 1, kb = k0, m = 0, r = 0;
            const int busy = head ? 0 : tail ? P2_POS - 24 : P2_POS;
#pragma unroll 1
            for (int p = 0; p < P2_POS; p++) {
                if (p == 0 || p == P2_FOLD) {
                    flag_wait<true>(&g_img[p != 0], p ? 96 * 4 : 48);
                    asm volatile("fence.proxy.async.global;\n" ::: "memory");
                    if (p) wsrc += sizeof(g_w2img[0]);
                }
                mbar_wait(bar_bempty + st * 8, ph);
                TR2P(p, 0);
                if (elect_one()) {
                    mbar_expect_tx(bar_bfull + st * 8, P2_B);
                    bulk_g2s_mc(sbase + st * P2_B + rank * (P2_B / 2), wsrc + kb * P2_B, P2_B / 2, bar_bfull + st * 8, (uint16_t)3);
                    asm volatile("st.volatile.shared.u32 [%0], %1;\n" ::"r"(s_pos), "r"(p) : "memory");
                    const int idle = 2 - min(m, P2_ITEMS - 1) + max(m - 2 + (r >= 48 - 2 * P2_LAG), 0) - ((unsigned)(p - busy) < 24);
                    if (idle) asm volatile("mbarrier.arrive.shared::cta.b64 _, [%0], %1;\n" ::"r"(bar_bempty + st * 8), "r"(idle * 8) : "memory");
                    if (rank == 0) asm volatile("red.relaxed.gpu.global.add.u32 [%0], 1;\n" ::"l"(&g_prog) : "memory");
                }
                __syncwarp();
                if (++st == P2_NB) { st = 0; ph ^= 1; }
                if (++kb == 48) kb = 0;
                if (++r == P2_LAG) { r = 0; m++; }
            }
            mbar_wait(bar_bempty + st * 8, ph);
            if (lane == 0) mbar_arrive(bar_bfull + st * 8);
#pragma unroll 1
            for (int p = 1; p < P2_NB; p++) {
                if (++st == P2_NB) { st = 0; ph ^= 1; }
                mbar_wait(bar_bempty + st * 8, ph);
            }
        } else if (warp == 13) {
            const uint8_t* src[3];
            int n[3], left[3], wrap[3];
            uint32_t st[3];
            auto item = [&](int w) {
                const int u = (k0 + p2_start(n[w])) % 48;
                left[w] = n[w] < 0 || n[w] == P2_ITEMS ? 24 : 48;
                wrap[w] = left[w] - (48 - u);
                src[w] = reinterpret_cast<const uint8_t*>(g_h) + (size_t)p2_tile(cl, n[w]) * (2 * H_TILE) + rank * H_HALF + u * H_STEP;
            };
#pragma unroll
            for (int w = 0; w < 3; w++) {
                n[w] = w == 2 && head ? -1 : w;
                st[w] = 0x80000000u;
                item(w);
            }
            gdc_wait();
#pragma unroll 1
            for (int done = 0; done < 3;) {
                bool idle = true;
#pragma unroll
                for (int w = 0; w < 3; w++) {
                    const uint32_t o = (st[w] & 0xff) + w * P2_NA * 8;
                    if (left[w] >= 0 && mbar_test(bar_aempty + o, st[w] >> 31)) {
                        idle = false;
                        if (left[w] == 0) {
                            if (lane == 0) mbar_arrive(bar_afull + o);
                            left[w] = -1;
                            done++;
                        } else {
                            if (elect_one()) {
                                mbar_expect_tx(bar_afull + o, P2_A);
                                bulk_g2s(sbase + P2_OFF_A + o * (P2_A / 8), src[w], P2_A, bar_afull + o);
                            }
                            __syncwarp();
                            src[w] += H_STEP;
                            st[w] += 8;
                            if ((st[w] & 0xff) == P2_NA * 8) st[w] ^= 0x80000000u | (P2_NA * 8);
                            if (--left[w] == wrap[w]) src[w] -= 48 * H_STEP;
                            if (left[w] == 0 && (n[w] += 3) < P2_ITEMS + tail) item(w);
                        }
                    }
                }
                if (idle) __nanosleep(64);
                SAFE_BREAK
            }
        } else if (warp == 14) {
            const uint32_t sx = sbase + P2_OFF_X;
            size_t o = 0;
            auto pace = [&](int target) {
                int v;
                while (true) {
                    asm volatile("ld.volatile.shared.u32 %0, [%1];\n" : "=r"(v) : "r"(s_pos) : "memory");
                    if (v * 16 >= target) break;
                    __nanosleep(100);
                    SAFE_BREAK
                }
            };
#pragma unroll 1
            for (int n = -head; n <= P2_ITEMS; n++) {
                const size_t on = (size_t)(2 * p2_tile(cl, n) + rank) * (64 * C_DIM * 2);
                const bool st = n + head > 0, ld = n < P2_ITEMS;
                if (st) mbar_wait(bar_oready, (n - 1 + head) & 1);
                TR2P(n + 1, 1);
                if (lane == 0) {
                    if (n == 1 && head) {
                        asm volatile("cp.async.bulk.wait_group 0;\nfence.proxy.async.global;\n" ::: "memory");
                        asm volatile("st.release.gpu.global.u32 [%0], 1;\n" ::"l"(&g_half[pair][rank]) : "memory");
                    }
                    if (ld) mbar_expect_tx(bar_xfull, 64 * C_DIM * 2);
                    int t = st && n < P2_ITEMS - 1 ? (P2_LAG * (n - 1) + 52) * 16 : -1024;
#pragma unroll 1
                    for (int c = 0; st && c < 64 * P2_XROW; c += P2_XC) {
                        pace(t += 11);
                        bulk_s2g(reinterpret_cast<uint8_t*>(out) + o + c, sx + c + (c >= 32 * P2_XROW ? 64 : 0), P2_XC);
                    }
                    asm volatile("cp.async.bulk.commit_group;\ncp.async.bulk.wait_group.read 0;\n" ::: "memory");
#pragma unroll 1
                    for (int c = 0; ld && c < 64 * P2_XROW; c += P2_XC) {
                        pace(t += 11);
                        bulk_g2s(sx + c + (c >= 32 * P2_XROW ? 64 : 0), reinterpret_cast<const uint8_t*>(x) + on + c, P2_XC, bar_xfull);
                    }
                    TR2P(n + 1, 2);
                    if (rank == 0 && n > 0 && n < P2_ITEMS - 2)
                        flag_wait<false>(&g_prog, P2_NCL * (P2_LAG * n + 48) + (tail ? P2_SHARED - P2_NCL : P2_SHARED) * P2_DELTA);
                    if (ld) mbar_arrive(bar_xfull);
                    TR2P(n + 1, 3);
                }
                __syncwarp();
                o = on;
            }
            asm volatile("cp.async.bulk.wait_group 0;\n" ::: "memory");
            TR2P(30, 1);
        }
    } else {
        reg_inc<160>();
        const int wg = warp >> 2, w = warp & 3, g = lane >> 2, q = lane & 3;
        const uint32_t sx = sbase + P2_OFF_X + (g & 1) * P2_XHALF + (w * 8 + (g >> 1)) * P2_XROW + q * 16;
        const uint32_t af = bar_afull + wg * P2_NA * 8;
        const uint32_t s_a = sbase + P2_OFF_A + wg * P2_NA * P2_A + (lane >> 3) * 512 + (lane & 7) * 64 +
                             ((w ^ ((lane & 7) >> 1)) << 4);
        uint32_t acc0[48], acc1[48];
        float up;
        uint4 a0[2], a1[2];
        uint32_t st = 0, ph = 0;

        {
            float4* s_red = reinterpret_cast<float4*>(smem + P2_OFF_BIAS);
            const float* sums = g_sums[par];
            float gx[4], part = 0.f, mx = 0.f;
            TSTAMP(1, 27);
            gdc_wait();
            TSTAMP(1, 1);
#pragma unroll
            for (int i = 0; i < 4; i++) gx[i] = __ldcg(sums + tid + 384 * i);
            if (blockIdx.x == 120 && tid < (LN_RING + 3) * 2) (&g_flag[0][0][0])[tid * 8] = 0;
            if (blockIdx.x == 121 && tid == 0) atomicAdd(&g_epoch, 1u);
            float z = __uint_as_float(__reduce_max_sync(0xffffffffu, __float_as_uint(pre[2] + pre[3])));
#pragma unroll
            for (int i = 0; i < 4; i++) {
                asm("sqrt.approx.f32 %0, %1;\n" : "=f"(gx[i]) : "f"(fmaf(gx[i], HSCALE * HSCALE, 1e-6f)));
                part += gx[i];
                gx[i] *= bf_lo(gg[i]);
                mx = fmaxf(mx, fabsf(gx[i]));
            }
#pragma unroll
            for (int o = 16; o > 0; o >>= 1) part += __shfl_xor_sync(0xffffffffu, part, o);
            mx = __uint_as_float(__reduce_max_sync(0xffffffffu, __float_as_uint(mx)));
            TSTAMP(1, 26);
            if (lane == 0) s_red[warp] = make_float4(part, mx, z, 0.f);
            bar_sync(1, 384);
            float tot = 0.f;
            {
                const float4 t = s_red[min(lane & 15, 11)];
                tot = (lane & 15) < 12 ? t.x : 0.f;
#pragma unroll
                for (int o = 8; o > 0; o >>= 1) tot += __shfl_xor_sync(0xffffffffu, tot, o);
                mx = __uint_as_float(__reduce_max_sync(0xffffffffu, __float_as_uint(t.y)));
                z = __uint_as_float(__reduce_max_sync(0xffffffffu, __float_as_uint(t.z)));
            }
            const float inv = __fdividef(1.0f, fmaf(tot, 1.0f / HID, 1e-6f));
            const uint32_t j = max(__float_as_uint(fmaf(mx, inv, 1.0f) * 1.01f) >> 23, 130u) - 130u;
            const float dn = __uint_as_float((127u - j) << 23);
#pragma unroll
            for (int i = 0; i < 4; i++)
                *reinterpret_cast<uint16_t*>(smem + P2_OFF_GRN + (tid + 384 * i) * 2) = pack_f16(fmaf(gx[i], inv, 1.0f) * dn, 0.f);
            up = (HSCALE * 1.00235f) * __uint_as_float(min(acc_exp(z) - 9u + j, 253u) << 23);
            TSTAMP(1, 25);
            bar_sync(1, 384);
            reinterpret_cast<float*>(smem + P2_OFF_BIAS)[tid] = pre[0] + pre[1];
            if (wg == 1 && blockIdx.x < 96) {
                const uint4* src = g_w2img[0] + blockIdx.x * 768 + tid - 128;
                const uint4 fk = *reinterpret_cast<const uint4*>(smem + P2_OFF_GRN + blockIdx.x * 32 + (tid & 8) * 2);
                uint4 v[6];
#pragma unroll
                for (int i = 0; i < 6; i++) v[i] = __ldcg(src + i * 128);
                auto fold = [&](uint32_t b, uint32_t f) { return (h2_mul(b, f) + 0x00040004u) & 0xfff8fff8u; };
#pragma unroll
                for (int i = 0; i < 6; i++)
                    g_w2img[1][blockIdx.x * 768 + tid - 128 + i * 128] = make_uint4(fold(v[i].x, fk.x), fold(v[i].y, fk.y), fold(v[i].z, fk.z), fold(v[i].w, fk.w));
                asm volatile("fence.proxy.async.global;\n" ::: "memory");
                __threadfence();
                __syncwarp();
                if (lane == 0) asm volatile("red.release.gpu.global.add.u32 [%0], 1;\n" ::"l"(&g_img[1]) : "memory");
            }
        }
        TSTAMP(1, 28);
        int kt = k0, pos;
        const uint32_t be = lane < 2 ? mapa(bar_bempty, lane) : 0, be0 = mapa(bar_bempty, 0);
        uint32_t prev = 0, sa = 0, pa = 0;
        auto release_b = [&](uint32_t p, bool on) {
            asm volatile("{\n.reg .pred p, q;\nsetp.ne.u32 q, %2, 0;\nsetp.ne.and.u32 p, %1, 0, q;\n@p mbarrier.arrive.shared::cluster.b64 _, [%0];\n}\n"
                         ::"r"(be + p), "r"(be), "r"((uint32_t)on) : "memory");
        };
        auto arrive1 = [&](uint32_t bar) {
            asm volatile("{\n.reg .pred p;\nsetp.eq.u32 p, %1, %2;\n@p mbarrier.arrive.shared::cta.b64 _, [%0];\n}\n" ::"r"(bar), "r"(be), "r"(be0) : "memory");
        };
        auto seek = [&](int p) {
            pos = p;
            st = p % P2_NB * 8;
            ph = p / P2_NB & 1;
            int v;
            while (true) {
                asm volatile("ld.volatile.shared.u32 %0, [%1];\n" : "=r"(v) : "r"(s_pos) : "memory");
                if (__all_sync(0xffffffffu, v >= p)) break;
                __nanosleep(200);
                SAFE_BREAK
            }
        };
        bool ok_a = false;
        auto fetch = [&](uint4 (&a)[2], uint32_t done, bool rel, bool early) {
            if (!ok_a) mbar_wait(af + sa, pa);
            uint32_t o[6];
            const uint32_t src = s_a + sa * (P2_A / 8);
            asm volatile("ldmatrix.sync.aligned.m8n8.x4.trans.shared.b16 {%0,%1,%2,%3}, [%4];\n"
                         : "=r"(o[0]), "=r"(o[1]), "=r"(o[2]), "=r"(o[3]) : "r"(src) : "memory");
            asm volatile("ldmatrix.sync.aligned.m8n8.x2.trans.shared.b16 {%0,%1}, [%2];\n"
                         : "=r"(o[4]), "=r"(o[5]) : "r"(src + 2048) : "memory");
            if ((sa += 8) == P2_NA * 8) { sa = 0; pa ^= 1; }
            wg_wait<1>();
            release_b(done, rel);
            ok_a = mbar_test(af + sa, pa);
            const bool ok_b = mbar_test(bar_bfull + st, ph);
            p2_unpack(a[0], o[0], o[1], o[2]);
            p2_unpack(a[1], o[3], o[4], o[5]);
            if (early) {
                const uint32_t* t = reinterpret_cast<const uint32_t*>(smem + P2_OFF_GRN) + kt * 16 + q;
#pragma unroll
                for (int i = 0; i < 2; i++)
                    a[i] = make_uint4(h2_mul(a[i].x, t[8 * i]), h2_mul(a[i].y, t[8 * i]), h2_mul(a[i].z, t[8 * i + 4]), h2_mul(a[i].w, t[8 * i + 4]));
                if (++kt == 48) kt = 0;
            }
            if (!ok_b) mbar_wait(bar_bfull + st, ph);
        };
        const uint64_t db0 = make_desc(sbase, 128, 256);
        auto step = [&](const uint4 (&a)[2], uint4 (&an)[2], bool cont, bool early) {
            TR2(0);
            const uint64_t db = db0 + st * (P2_B / 128);
            wg_fence();
            mma_rs_n192(acc0, a[0], db, cont);
            mma_rs_n192(acc1, a[0], db + 384, cont);
            mma_rs_n192(acc0, a[1], db + 768, 1);
            mma_rs_n192(acc1, a[1], db + 768 + 384, 1);
            wg_commit();
            arrive1(af + 3 * P2_NA * 8 - 8 + (sa ? sa : P2_NA * 8));
            const uint32_t done = prev;
            prev = st;
            if ((st += 8) == P2_NB * 8) { st = 0; ph ^= 1; }
            fetch(an, done, cont, early);
            pos++;
        };
        int n = wg == 2 && head ? -1 : wg;
        seek(p2_start(n));
        fetch(a0, 0, false, n <= 0);
#pragma unroll 1
        for (;; n += 3) {
            TSTAMP(1, 2 + n);
            const int p0 = n < 0 || n == P2_ITEMS ? 12 : 0, pe = n <= 0 ? p0 + P2_FOLD / 2 : 0;
            const bool more = n + 3 < P2_ITEMS + tail;
#pragma unroll 1
            for (int p = p0; p < 24; p++) {
                step(a0, a1, p != p0, p < pe);
                step(a1, a0, true, p < pe);
            }
            if (n == P2_ITEMS) {
                flag_wait<true>(&g_half[pair][rank], 1);
                TR2(1);
                wg_wait<0>();
                TR2(2);
                release_b(prev, true);
                uint8_t* o = reinterpret_cast<uint8_t*>(out) + (size_t)((2 * p2_tile(cl, -1) + rank) * 64 + (g & 1) * 32 + w * 8 + (g >> 1)) * P2_XROW + q * 16;
                p2_epilogue_add(acc0, o, up, zero);
                p2_epilogue_add(acc1, o + 384, up, zero);
                TR2(3);
                break;
            }
            mbar_wait(bar_xfull, (n + head) & 1);
            TR2(1);
            wg_wait<0>();
            TR2(2);
            release_b(prev, true);
            p2_epilogue(acc0, acc1, sx, sbase + P2_OFF_BIAS + q * 32, up, zero);
            TR2(3);
            asm volatile("fence.proxy.async.shared::cta;\n" ::: "memory");
            __syncwarp();
            arrive1(bar_oready);
            if (!more) break;
            ok_a = false;
            seek(p2_start(n + 3));
            mbar_wait(bar_bfull + st, ph);
        }
        TSTAMP(1, 30);
    }
}

}

extern "C" void kernel_launch(void* const* d_in, const int* in_sizes, int n_in, void* d_out, int out_size) {
    const __nv_bfloat16* x = (const __nv_bfloat16*)d_in[0];
    const __nv_bfloat16* dw = (const __nv_bfloat16*)d_in[1];
    const __nv_bfloat16* w1 = (const __nv_bfloat16*)d_in[2];
    const __nv_bfloat16* w2 = (const __nv_bfloat16*)d_in[3];
    const __nv_bfloat16* grn_g = (const __nv_bfloat16*)d_in[4];
    const __nv_bfloat16* grn_b = (const __nv_bfloat16*)d_in[5];
    __nv_bfloat16* out = (__nv_bfloat16*)d_out;

    cudaFuncSetAttribute(pass1_kernel, cudaFuncAttributeMaxDynamicSharedMemorySize, P1_SMEM);
    cudaFuncSetAttribute(pass2_kernel, cudaFuncAttributeMaxDynamicSharedMemorySize, P2_SMEM);

    typedef CUresult (*EncodeFn)(CUtensorMap*, CUtensorMapDataType, cuuint32_t, void*, const cuuint64_t*, const cuuint64_t*,
                                 const cuuint32_t*, const cuuint32_t*, CUtensorMapInterleave, CUtensorMapSwizzle,
                                 CUtensorMapL2promotion, CUtensorMapFloatOOBfill);
    static EncodeFn encode = nullptr;
    if (!encode) {
        cudaDriverEntryPointQueryResult qres;
        cudaGetDriverEntryPoint("cuTensorMapEncodeTiled", (void**)&encode, cudaEnableDefault, &qres);
    }
    CUtensorMap wmap;
    const cuuint64_t gdim[2] = {HID, C_DIM};
    const cuuint64_t gstr[1] = {HID * 2};
    const cuuint32_t box[2] = {64, 192}, estr[2] = {1, 1};
    CUresult er = encode(&wmap, CU_TENSOR_MAP_DATA_TYPE_BFLOAT16, 2, (void*)w1, gdim, gstr, box, estr, CU_TENSOR_MAP_INTERLEAVE_NONE,
           CU_TENSOR_MAP_SWIZZLE_128B, CU_TENSOR_MAP_L2_PROMOTION_L2_128B, CU_TENSOR_MAP_FLOAT_OOB_FILL_NONE);
    if (er != CUDA_SUCCESS) printf("tensor map encode failed %d\n", (int)er);

    pass1_kernel<<<NUM_CTAS, 512, P1_SMEM>>>(wmap, x, dw, w1, w2, grn_b, 0);

    cudaLaunchAttribute attr[1];
    attr[0].id = cudaLaunchAttributeProgrammaticStreamSerialization;
    attr[0].val.programmaticStreamSerializationAllowed = 1;
    cudaLaunchConfig_t cfg = {};
    cfg.gridDim = dim3(NUM_CTAS);
    cfg.stream = 0;
    cfg.attrs = attr;
    cfg.numAttrs = 1;
    cfg.blockDim = dim3(512);
    cfg.dynamicSmemBytes = P2_SMEM;
    cudaLaunchKernelEx(&cfg, pass2_kernel, x, grn_g, out, 0);
}
```

```cpp
#include <cuda.h>
#include <cuda_runtime.h>
#include <cuda_bf16.h>
#include <stdint.h>
#include <stdio.h>

namespace {

constexpr int M_TOTAL = 384 * 384;
constexpr int C_DIM   = 384;
constexpr int HID     = 1536;
constexpr int NT128   = M_TOTAL / 128;
constexpr int NUM_CTAS = 132;

constexpr int NGRP = 15;
constexpr int LN_STEP = 2 * NGRP, LN_RING = 2 * LN_STEP;
#define P1_M 101
#define P1_D 10
__device__ __forceinline__ int p1_tile(int t, bool small) {
    return t + (small ? ((t + 1) * P1_M + P1_D - 1) / P1_D : t * P1_D / P1_M);
}
constexpr int LN_TILE = 128 * C_DIM * 2;
constexpr int H_TILE = 64 * HID * 3 / 2;
constexpr int H_HALF = 3072, H_STEP = 6144;

__device__ __align__(1024) uint4 g_h[(size_t)M_TOTAL * HID * 3 / 32];
__device__ __align__(1024) uint4 g_ln[LN_RING * LN_TILE / 16];
__device__ __align__(1024) uint4 g_w2img[2][HID * C_DIM * 2 / 16];
__device__ __align__(16) float g_sums[2][HID + 2 * C_DIM];
__device__ __align__(16) unsigned g_ex[HID];
__device__ unsigned g_epoch, g_par;
__device__ __align__(128) unsigned g_img[2];
__device__ __align__(128) unsigned g_prog;
__device__ __align__(128) unsigned g_half[32][2];
__device__ unsigned g_flag[LN_RING + 3][2][8];
#define TSTAMP(k, i)
#define STAMPT(t, i)
#define TRACE(wg, pos, i)
#define TRACEW(pos, i)

#define TR2(i)
#define TR2P(pos, i)
__host__ __device__ __forceinline__ int perm32(int n) {
    return (n & ~31) | (((n >> 1) & 3) << 3) | (((n >> 3) & 3) << 1) | (n & 1);
}

__device__ __forceinline__ uint32_t smem_u32(const void* p) { return (uint32_t)__cvta_generic_to_shared(p); }

__device__ __forceinline__ void mbar_init(uint32_t bar, uint32_t count) {
    asm volatile("mbarrier.init.shared::cta.b64 [%0], %1;\n" ::"r"(bar), "r"(count) : "memory");
}
__device__ __forceinline__ void mbar_expect_tx(uint32_t bar, uint32_t bytes) {
    asm volatile("mbarrier.arrive.expect_tx.shared::cta.b64 _, [%0], %1;\n" ::"r"(bar), "r"(bytes) : "memory");
}
__device__ __forceinline__ void mbar_arrive(uint32_t bar) {
    asm volatile("mbarrier.arrive.shared::cta.b64 _, [%0];\n" ::"r"(bar) : "memory");
}
__device__ __forceinline__ void mbar_arrive_cluster(uint32_t bar_cluster_addr) {
    asm volatile("mbarrier.arrive.shared::cluster.b64 _, [%0];\n" ::"r"(bar_cluster_addr) : "memory");
}
#define SAFE_BREAK
__device__ __forceinline__ void mbar_wait(uint32_t bar, uint32_t parity) {
    asm volatile(
        "{\n"
        ".reg .pred p;\n"
        "LAB_WAIT:\n"
        "mbarrier.try_wait.parity.shared::cta.b64 p, [%0], %1;\n"
        "@!p bra LAB_WAIT;\n"
        "}\n" ::"r"(bar), "r"(parity) : "memory");
}
__device__ __forceinline__ bool mbar_test(uint32_t bar, uint32_t parity) {
    uint32_t ok;
    asm volatile("{\n.reg .pred p;\n"
                 "mbarrier.test_wait.parity.shared::cta.b64 p, [%1], %2;\n"
                 "selp.u32 %0, 1, 0, p;\n}\n" : "=r"(ok) : "r"(bar), "r"(parity) : "memory");
    return ok != 0;
}
__device__ __forceinline__ uint32_t mapa(uint32_t addr, uint32_t rank) {
    uint32_t r;
    asm volatile("mapa.shared::cluster.u32 %0, %1, %2;\n" : "=r"(r) : "r"(addr), "r"(rank));
    return r;
}
__device__ __forceinline__ void bulk_g2s(uint32_t dst, const void* src, uint32_t bytes, uint32_t bar) {
    asm volatile("cp.async.bulk.shared::cluster.global.mbarrier::complete_tx::bytes [%0], [%1], %2, [%3];\n"
                 ::"r"(dst), "l"(src), "r"(bytes), "r"(bar) : "memory");
}
__device__ __forceinline__ void bulk_g2s_mc(uint32_t dst, const void* src, uint32_t bytes, uint32_t bar, uint16_t mask) {
    asm volatile("cp.async.bulk.shared::cluster.global.mbarrier::complete_tx::bytes.multicast::cluster [%0], [%1], %2, [%3], %4;\n"
                 ::"r"(dst), "l"(src), "r"(bytes), "r"(bar), "h"(mask) : "memory");
}
__device__ __forceinline__ void tma2(uint32_t dst, const CUtensorMap* map, int c0, int c1, uint32_t bar) {
    asm volatile("cp.async.bulk.tensor.2d.shared::cluster.global.tile.mbarrier::complete_tx::bytes [%0], [%1, {%2, %3}], [%4];\n"
                 ::"r"(dst), "l"(map), "r"(c0), "r"(c1), "r"(bar) : "memory");
}
template <bool ACQ>
__device__ __forceinline__ uint32_t flag_wait(const unsigned* p, unsigned target) {
    unsigned v, n = 0;
    do {
        if (ACQ) asm volatile("ld.acquire.gpu.global.u32 %0, [%1];\n" : "=r"(v) : "l"(p) : "memory");
        else asm volatile("ld.relaxed.gpu.global.u32 %0, [%1];\n" : "=r"(v) : "l"(p) : "memory");
        n++;
    } while (v < target);
    return n == 1;
}
__device__ __forceinline__ void ldsm4t(uint32_t (&r)[4], uint32_t addr) {
    asm volatile("ldmatrix.sync.aligned.m8n8.x4.trans.shared.b16 {%0,%1,%2,%3}, [%4];\n"
                 : "=r"(r[0]), "=r"(r[1]), "=r"(r[2]), "=r"(r[3]) : "r"(addr) : "memory");
}
__device__ __forceinline__ void bulk_s2g(void* dst, uint32_t src, uint32_t bytes) {
    asm volatile("cp.async.bulk.global.shared::cta.bulk_group [%0], [%1], %2;\n" ::"l"(dst), "r"(src), "r"(bytes) : "memory");
}
__device__ __forceinline__ void cluster_sync_relaxed() {
    asm volatile("barrier.cluster.arrive.relaxed.aligned;\nbarrier.cluster.wait.aligned;\n" ::: "memory");
}
__device__ __forceinline__ void gdc_wait() { asm volatile("griddepcontrol.wait;\n" ::: "memory"); }
__device__ __forceinline__ void gdc_launch() { asm volatile("griddepcontrol.launch_dependents;\n" ::: "memory"); }
__device__ __forceinline__ uint32_t cluster_rank() {
    uint32_t r;
    asm volatile("mov.u32 %0, %%cluster_ctarank;\n" : "=r"(r));
    return r;
}
__device__ __forceinline__ bool elect_one() {
    uint32_t pred;
    asm volatile("{\n.reg .pred p;\nelect.sync _|p, 0xffffffff;\nselp.u32 %0, 1, 0, p;\n}\n" : "=r"(pred));
    return pred != 0;
}
__device__ __forceinline__ void wg_fence() { asm volatile("wgmma.fence.sync.aligned;\n" ::: "memory"); }
__device__ __forceinline__ void wg_commit() { asm volatile("wgmma.commit_group.sync.aligned;\n" ::: "memory"); }
template <int N> __device__ __forceinline__ void wg_wait() {
    asm volatile("wgmma.wait_group.sync.aligned %0;\n" ::"n"(N) : "memory");
}
template <int R> __device__ __forceinline__ void reg_inc() { asm volatile("setmaxnreg.inc.sync.aligned.u32 %0;\n" ::"n"(R)); }
template <int R> __device__ __forceinline__ void reg_dec() { asm volatile("setmaxnreg.dec.sync.aligned.u32 %0;\n" ::"n"(R)); }
__device__ __forceinline__ void bar_sync(int id, int n) { asm volatile("bar.sync %0, %1;\n" ::"r"(id), "r"(n) : "memory"); }
__device__ __forceinline__ void bar_arrive(int id, int n) { asm volatile("bar.arrive %0, %1;\n" ::"r"(id), "r"(n) : "memory"); }

__device__ __forceinline__ uint64_t make_desc(uint32_t saddr, uint32_t lbo, uint32_t sbo) {
    return (uint64_t)((saddr & 0x3FFFF) >> 4) | ((uint64_t)(lbo >> 4) << 16) | ((uint64_t)(sbo >> 4) << 32);
}

__device__ __forceinline__ void stg128_cs(void* p, uint32_t a, uint32_t b, uint32_t c, uint32_t d) {
    asm volatile("st.global.cs.v4.u32 [%0], {%1,%2,%3,%4};\n" ::"l"(p), "r"(a), "r"(b), "r"(c), "r"(d) : "memory");
}
__device__ __forceinline__ uint32_t pack_bf16(float lo, float hi) {
    uint32_t r;
    asm("cvt.rn.bf16x2.f32 %0, %1, %2;\n" : "=r"(r) : "f"(hi), "f"(lo));
    return r;
}
__device__ __forceinline__ float bf_lo(uint32_t v) { return __uint_as_float(v << 16); }
__device__ __forceinline__ float bf_hi(uint32_t v) { return __uint_as_float(v & 0xffff0000u); }
__device__ __forceinline__ uint32_t bf2_mul(uint32_t a, uint32_t b) {
    uint32_t r;
    asm("mul.rn.bf16x2 %0, %1, %2;\n" : "=r"(r) : "r"(a), "r"(b));
    return r;
}
__device__ __forceinline__ uint32_t bf2_fma(uint32_t a, uint32_t b, uint32_t c) {
    uint32_t r;
    asm("fma.rn.bf16x2 %0, %1, %2, %3;\n" : "=r"(r) : "r"(a), "r"(b), "r"(c));
    return r;
}
__device__ __forceinline__ uint32_t bf2_add(uint32_t a, uint32_t b) {
    uint32_t r;
    asm("add.rn.bf16x2 %0, %1, %2;\n" : "=r"(r) : "r"(a), "r"(b));
    return r;
}
constexpr float KAPPA = 0.3292034911525734f;
constexpr float GELU_C = 2.423681954311584f;
constexpr float HSCALE = 1.0f / (2.0f * KAPPA);
__device__ __forceinline__ uint32_t acc_exp(float z) { return max(__float_as_uint(z) >> 23, 10u); }
__device__ __forceinline__ void sched_break(int zero) {
    asm volatile("{\n.reg .pred p;\nsetp.ne.s32 p, %0, 0;\nSB_LOOP:\n@p nanosleep.u32 1;\n@p bra SB_LOOP;\n}\n" ::"r"(zero));
}

#define ACCR8(d, o) "+r"(d[o + 0]), "+r"(d[o + 1]), "+r"(d[o + 2]), "+r"(d[o + 3]), "+r"(d[o + 4]), "+r"(d[o + 5]), "+r"(d[o + 6]), "+r"(d[o + 7])
__device__ __forceinline__ void mma_rs_n128(uint32_t (&d)[32], const uint32_t (&a)[4], uint64_t desc, int scale_d) {
    asm volatile(
        "{\n.reg .pred p;\nsetp.ne.b32 p, %37, 0;\n"
        "wgmma.mma_async.sync.aligned.m64n128k16.f16.f16.f16 "
        "{%0,%1,%2,%3,%4,%5,%6,%7,%8,%9,%10,%11,%12,%13,%14,%15,"
        "%16,%17,%18,%19,%20,%21,%22,%23,%24,%25,%26,%27,%28,%29,%30,%31},"
        "{%32,%33,%34,%35}, %36, p, 1, 1, 0;\n}\n"
        : ACCR8(d, 0), ACCR8(d, 8), ACCR8(d, 16), ACCR8(d, 24)
        : "r"(a[0]), "r"(a[1]), "r"(a[2]), "r"(a[3]), "l"(desc), "r"(scale_d));
}
__device__ __forceinline__ void mma_ss_n128(uint32_t (&d)[32], uint64_t da, uint64_t db) {
    asm volatile(
        "{\n.reg .pred p;\nsetp.ne.b32 p, %34, 0;\n"
        "wgmma.mma_async.sync.aligned.m64n128k16.f16.f16.f16 "
        "{%0,%1,%2,%3,%4,%5,%6,%7,%8,%9,%10,%11,%12,%13,%14,%15,"
        "%16,%17,%18,%19,%20,%21,%22,%23,%24,%25,%26,%27,%28,%29,%30,%31},"
        "%32, %33, p, 1, 1, 0, 0;\n}\n"
        : ACCR8(d, 0), ACCR8(d, 8), ACCR8(d, 16), ACCR8(d, 24)
        : "l"(da), "l"(db), "r"(1));
}
__device__ __forceinline__ uint32_t bf2_as_h2(uint32_t v) { return (v & 0x0fff0fffu) * 7u + v; }
__device__ __forceinline__ float h_lo(uint32_t v) {
    float r;
    asm("{\n.reg .b16 l, h;\nmov.b32 {l, h}, %1;\ncvt.f32.f16 %0, l;\n}\n" : "=f"(r) : "r"(v));
    return r;
}
__device__ __forceinline__ float h_hi(uint32_t v) {
    float r;
    asm("{\n.reg .b16 l, h;\nmov.b32 {l, h}, %1;\ncvt.f32.f16 %0, h;\n}\n" : "=f"(r) : "r"(v));
    return r;
}

__device__ __forceinline__ void mma_rs_n192(uint32_t (&d)[48], const uint4& a, uint64_t db, int scale_d) {
    asm volatile(
        "{\n.reg .pred p;\nsetp.ne.b32 p, %53, 0;\n"
        "wgmma.mma_async.sync.aligned.m64n192k16.f16.f16.f16 "
        "{%0,%1,%2,%3,%4,%5,%6,%7,%8,%9,%10,%11,%12,%13,%14,%15,"
        "%16,%17,%18,%19,%20,%21,%22,%23,%24,%25,%26,%27,%28,%29,%30,%31,"
        "%32,%33,%34,%35,%36,%37,%38,%39,%40,%41,%42,%43,%44,%45,%46,%47},"
        "{%48,%49,%50,%51}, %52, p, 1, 1, 0;\n}\n"
        : ACCR8(d, 0), ACCR8(d, 8), ACCR8(d, 16), ACCR8(d, 24), ACCR8(d, 32), ACCR8(d, 40)
        : "r"(a.x), "r"(a.y), "r"(a.z), "r"(a.w), "l"(db), "r"(scale_d));
}

__device__ __forceinline__ uint32_t pack_f16(float lo, float hi) {
    uint32_t r;
    asm("cvt.rn.f16x2.f32 %0, %1, %2;\n" : "=r"(r) : "f"(hi), "f"(lo));
    return r;
}

constexpr int P1_IMG = 900;
constexpr int P1_SLOT = LN_TILE / 2, P1_NST = 4;
constexpr int P1_X = 16 * C_DIM * 2;
constexpr int P1_OFF_X = P1_SLOT * P1_NST;
constexpr int P1_OFF_A = P1_OFF_X + 2 * P1_X;
constexpr int P1_OFF_BAR = P1_OFF_A + 3 * 2048;
constexpr int P1_OFF_TILE = P1_OFF_BAR + (2 * P1_NST + 3 + 2 + 3 + 2) * 8;
constexpr int P1_OFF_DW = P1_OFF_TILE + 64;
constexpr int P1_SMEM = P1_OFF_DW + C_DIM * 2;

__device__ __forceinline__ float rsqrt_fast(float x) {
    float r;
    asm("rsqrt.approx.ftz.f32 %0, %1;\n" : "=f"(r) : "f"(x));
    return r;
}
__device__ __forceinline__ float sum8(const uint32_t (&c)[4]) {
    const uint32_t u = bf2_add(bf2_add(c[0], c[1]), bf2_add(c[2], c[3]));
    return bf_lo(u) + bf_hi(u);
}
__device__ __forceinline__ void lds128(uint32_t (&v)[4], uint32_t a) {
    asm volatile("ld.shared.v4.u32 {%0,%1,%2,%3}, [%4];\n" : "=r"(v[0]), "=r"(v[1]), "=r"(v[2]), "=r"(v[3]) : "r"(a) : "memory");
}
template <class F>
__device__ __forceinline__ void ln_row(uint32_t (&v)[6][4], uint32_t sdw, F after_loads) {
    uint32_t c[4], s[4], d[4], nm;
#pragma unroll
    for (int i = 0; i < 6; i++) {
        lds128(d, sdw + i * 128);
        if (i == 0) {
#pragma unroll
            for (int k = 0; k < 4; k++) c[k] = bf2_mul(v[0][k], d[k]);
            const float p = sum8(c) * -0.125f;
            nm = pack_bf16(p, p);
        }
#pragma unroll
        for (int k = 0; k < 4; k++) {
            v[i][k] = bf2_fma(v[i][k], d[k], nm);
            s[k] = i ? bf2_add(v[i][k], s[k]) : v[i][k];
            c[k] = i ? bf2_fma(v[i][k], v[i][k], c[k]) : bf2_mul(v[i][k], v[i][k]);
        }
    }
    after_loads(c[0]);
    float m = fmaf(sum8(s), 1.0f / 48, -bf_lo(nm));
    float q = fmaf(-bf_lo(nm), fmaf(2.f, m, bf_lo(nm)), sum8(c) * (1.0f / 48));
#pragma unroll
    for (int o = 1; o < 8; o <<= 1) {
        m += __shfl_xor_sync(0xffffffffu, m, o);
        q += __shfl_xor_sync(0xffffffffu, q, o);
    }
    m *= 0.125f;
    const float r = KAPPA * rsqrt_fast(fmaxf(fmaf(-m, m, q * 0.125f), 0.f) + 1e-5f);
    const float e = (-bf_lo(nm) - m) * r * 0x1p-112f;
    const bool two = __any_sync(0xffffffffu, r < 0x1p-14f);
    const float r1 = r * (two ? 0x1p-56f : 0x1p-112f);
    uint32_t mul = pack_bf16(r1, r1), add = two ? 0u : pack_bf16(e, e);
#pragma unroll 1
    for (int it = !two; it < 2; it++) {
#pragma unroll
        for (int i = 0; i < 6; i++)
#pragma unroll
            for (int k = 0; k < 4; k++) v[i][k] = bf2_fma(v[i][k], mul, add);
        mul = 0x23802380u;
        add = pack_bf16(e, e);
    }
#pragma unroll
    for (int i = 0; i < 6; i++)
#pragma unroll
        for (int k = 0; k < 4; k++) v[i][k] = bf2_as_h2(v[i][k]);
}

__device__ __forceinline__ float gelu_s(float y) {
    float u = y * fmaf(y, y, GELU_C);
    float t;
    asm volatile("tanh.approx.f32 %0, %1;\n" : "=f"(t) : "f"(u));
    return fmaf(y, t, y);
}
__device__ __forceinline__ void p1_pack(int c, uint32_t (&p)[4], uint32_t (&dd)[4]) {
#pragma unroll
    for (int u = 0; u < 4; u++) {
        if ((c & 3) == 0) dd[u] = p[u];
        else {
            uint32_t n = dd[u];
            if ((c & 3) == 1) n = __byte_perm(n, 0, 0x2301);
            if ((c & 3) == 2) {
                dd[u] = __byte_perm(n >> 3, n >> 1, 0x6341);
                n = __byte_perm(n >> 3, n >> 1, 0x7250);
            }
            asm("lop3.b32 %0, %0, %1, 0x40074007, 0xd8;\n" : "+r"(p[u]) : "r"(n));
        }
    }
}
__device__ __forceinline__ void p1_store(int c, const uint32_t (&p)[4], uint8_t* hptr) {
    if (c & 3) stg128_cs(hptr + (c >> 2) * H_HALF + ((c & 3) - 1) * 512, p[0], p[1], p[2], p[3]);
}

template <bool GEN>
__device__ __forceinline__ void p1_epilogue(uint32_t (&acc)[32], float (&ssq)[2], uint32_t sc2, uint8_t* hp, int zero) {
    uint32_t sq[2], dd[4];
#pragma unroll
    for (int c = 0; c < 8; c++) {
        if (GEN) sched_break(zero);
        uint32_t p[4];
#pragma unroll
        for (int u = 0; u < 4; u++) {
            const uint32_t y = acc[8 * (c >> 1) + 2 * u + (c & 1)];
            if (GEN) {
                const float sc = c & 1 ? bf_hi(sc2) : bf_lo(sc2), fs = __uint_as_float(0x78000000u - __float_as_uint(sc));
                const float g0 = gelu_s(h_lo(y) * fs), g1 = gelu_s(h_hi(y) * fs);
                ssq[c & 1] = fmaf(g1, g1, fmaf(g0, g0, ssq[c & 1]));
                p[u] = pack_f16(g0 * sc, g1 * sc);
            } else {
                uint32_t g;
                asm("{\n.reg .b32 w;\n"
                    "fma.rn.f16x2 w, %1, %1, %2;\n"
                    "mul.rn.f16x2 w, w, %1;\n"
                    "tanh.approx.f16x2 w, w;\n"
                    "fma.rn.f16x2 %0, %1, w, %1;\n}\n" : "=r"(g) : "r"(y), "r"(0x40d940d9u));
                acc[8 * (c >> 1) + 2 * u + (c & 1)] = g;
                if (c < 2 && u == 0) asm("mul.rn.f16x2 %0, %1, %1;\n" : "=r"(sq[c & 1]) : "r"(g));
                else asm("fma.rn.f16x2 %0, %1, %1, %0;\n" : "+r"(sq[c & 1]) : "r"(g));
                if (c & 1) asm("{\n.reg .b16 l, h;\n.reg .b32 f;\nmov.b32 {l, h}, %2;\nmov.b32 f, {h, h};\nmul.rn.f16x2 %0, %1, f;\n}\n" : "=r"(p[u]) : "r"(g), "r"(sc2));
                else asm("{\n.reg .b16 l, h;\n.reg .b32 f;\nmov.b32 {l, h}, %2;\nmov.b32 f, {l, l};\nmul.rn.f16x2 %0, %1, f;\n}\n" : "=r"(p[u]) : "r"(g), "r"(sc2));
            }
        }
        p1_pack(c, p, dd);
        if (c & 3) {
#pragma unroll
            for (int u = 0; u < 4; u++) acc[4 * (c - 1 - (c >> 2)) + u] = p[u];
        }
        p1_store(c, p, hp);
    }
    if (!GEN) {
#pragma unroll
        for (int r = 0; r < 2; r++) ssq[r] += h_lo(sq[r]) + h_hi(sq[r]);
    }
}
__device__ __forceinline__ void p1_consumer(const uint32_t (&a)[24][4], uint32_t sc2, bool gen, uint32_t sbase, int wg, int nwg, int cb,
                                            int w, int lane, int zero) {
    const uint32_t bar_full = sbase + P1_OFF_BAR, bar_empty = bar_full + P1_NST * 8;
    const uint32_t empty_remote = mapa(bar_empty, lane & 1);
    const int g = lane >> 2, q = lane & 3, turn = wg + 1 == nwg ? 1 : wg + 2;
    float ssq[2] = {0.f, 0.f};
    uint32_t acc[32] = {};
    TSTAMP(0, 1);
    STAMPT(128, 4);
    STAMPT(256, 5);

    uint8_t* hp = reinterpret_cast<uint8_t*>(g_h) + ((cb * 2 + (w >> 1)) * H_STEP + (w & 1) * 1536) + g * 64 + (q ^ (g >> 1)) * 16;
    const uint64_t desc_base = make_desc(sbase, 16, 1024) | (1ull << 62);
    const uint64_t da = make_desc(sbase + P1_OFF_A + wg * 2048, 128, 256);
#pragma unroll 1
    for (int i = 0;; i++) {
        const int s0 = (i & 1) * 16, par = (i >> 1) & 1;
        const uint64_t d0 = desc_base + (uint64_t)((i & 1) * (LN_TILE / 16));
        TRACE(wg, i, 0);
        mbar_wait(bar_full + s0, par);
        bar_sync(1 + wg, 256);
        TRACE(wg, i, 1);
        uint32_t step, more;
        wg_fence();
#pragma unroll
        for (int k = 0; k < 24; k++) {
            if (k == 12) mbar_wait(bar_full + s0 + 8, par);
            const uint64_t db = d0 + (uint64_t)((k >> 2) * 1024 + (k & 3) * 2);
            if (k < 23) mma_rs_n128(acc, a[k], db, k ? 1 : zero);
            else mma_ss_n128(acc, da, db);
            if (k == 23) bar_arrive(turn, 256);
            if (k % 12 == 11) wg_commit();
        }
        asm volatile("ld.shared.v2.u32 {%0, %1}, [%2];\n" : "=r"(step), "=r"(more) : "r"(sbase + P1_OFF_TILE + (i & 3) * 16) : "memory");
        TRACE(wg, i, 2);
        wg_wait<1>();
        if (lane < 2) mbar_arrive_cluster(empty_remote + s0);
        hp += step;
        TRACE(wg, i, 3);
        wg_wait<0>();
        TRACE(wg, i, 4);
        if (lane < 2) mbar_arrive_cluster(empty_remote + s0 + 8);
        if (gen) p1_epilogue<true>(acc, ssq, sc2, hp, zero);
        else p1_epilogue<false>(acc, ssq, sc2, hp, zero);
        if (!more) break;
    }
    TSTAMP(0, 21);
    if (wg == 0) bar_sync(1, 256);
    uint32_t par;
    asm volatile("ld.shared.u32 %0, [%1];\n" : "=r"(par) : "r"(sbase + P1_OFF_TILE - 4) : "memory");
    float* sums = g_sums[par];
#pragma unroll
    for (int r = 0; r < 2; r++) {
        ssq[r] += __shfl_xor_sync(0xffffffffu, ssq[r], 1);
        ssq[r] += __shfl_xor_sync(0xffffffffu, ssq[r], 2);
        if (q == 0) atomicAdd(sums + cb * 64 + w * 16 + r * 8 + g, ssq[r]);
    }
}

__device__ __forceinline__ void p1_w2(const __nv_bfloat16* __restrict__ w2, const __nv_bfloat16* __restrict__ grn_b, int w, int lane) {
    const int gw = (blockIdx.x - 8 * NGRP) * 4 + w;
    float* sums = g_sums[__ldcg(&g_epoch) & 1] + HID;
    flag_wait<true>(&g_flag[40][1][0], 12);
    {
        const int col = gw % 6 * 64 + lane * 2;
        float bsum[2] = {0.f, 0.f}, asum[2] = {0.f, 0.f};
#pragma unroll 4
        for (int kk = 0; kk < 192; kk++) {
            const int k = gw / 6 * 192 + kk;
            const uint32_t v = *reinterpret_cast<const uint32_t*>(w2 + k * C_DIM + col);
            const float b = __bfloat162float(grn_b[k]), f = __uint_as_float(__ldcg(&g_ex[k]) << 23);
            bsum[0] = fmaf(b, bf_lo(v), bsum[0]);
            bsum[1] = fmaf(b, bf_hi(v), bsum[1]);
            asum[0] = fmaf(f, fabsf(bf_lo(v)), asum[0]);
            asum[1] = fmaf(f, fabsf(bf_hi(v)), asum[1]);
        }
#pragma unroll
        for (int j = 0; j < 2; j++) {
            atomicAdd(sums + col + j, bsum[j]);
            atomicAdd(sums + C_DIM + col + j, asum[j]);
        }
        __threadfence();
        __syncwarp();
        if (lane == 0) asm volatile("red.relaxed.gpu.global.add.u32 [%0], 1;\n" ::"l"(&g_flag[LN_RING + 2][0][0]) : "memory");
    }
    while (*(volatile unsigned*)&g_flag[P1_IMG % LN_RING][1][0] < 12 * (P1_IMG / LN_RING + 1)) {
        __nanosleep(2000);
        SAFE_BREAK
    }
    flag_wait<true>(&g_flag[LN_RING + 2][0][0], 48);
    float z = 0.f;
#pragma unroll
    for (int j = 0; j < C_DIM / 32; j++) z = fmaxf(z, __ldcg(sums + C_DIM + j * 32 + lane));
    const float sc = __uint_as_float((263u - acc_exp(__uint_as_float(__reduce_max_sync(0xffffffffu, __float_as_uint(z))))) << 23);
    const int np = gw % 6 * 64 + lane * 2;
#pragma unroll 2
    for (int cc = 0; cc < 24; cc++) {
        const int c = gw / 6 * 24 + cc;
        uint32_t v[8], o[2][4];
#pragma unroll
        for (int e = 0; e < 8; e++) v[e] = *reinterpret_cast<const uint32_t*>(w2 + (c * 8 + e) * C_DIM + perm32(np));
#pragma unroll
        for (int e = 0; e < 4; e++) {
            const uint2 t = __ldcg(reinterpret_cast<const uint2*>(g_ex) + c * 4 + e);
            const float f0 = __uint_as_float(t.x << 23), f1 = __uint_as_float(t.y << 23);
            o[0][e] = pack_f16(bf_lo(v[2 * e]) * f0 * sc, bf_lo(v[2 * e + 1]) * f1 * sc);
            o[1][e] = pack_f16(bf_hi(v[2 * e]) * f0 * sc, bf_hi(v[2 * e + 1]) * f1 * sc);
        }
#pragma unroll
        for (int j = 0; j < 2; j++)
            g_w2img[0][(((c >> 1) * 48 + (np >> 3)) * 2 + (c & 1)) * 8 + (np & 7) + j] = make_uint4(o[j][0], o[j][1], o[j][2], o[j][3]);
    }
    asm volatile("fence.proxy.async.global;\n" ::: "memory");
    __threadfence();
    __syncwarp();
    if (lane == 0) asm volatile("red.relaxed.gpu.global.add.u32 [%0], 1;\n" ::"l"(&g_img[0]) : "memory");
}

__global__ void __cluster_dims__(2, 1, 1) __launch_bounds__(512, 1)
pass1_kernel(const __grid_constant__ CUtensorMap wmap, const __nv_bfloat16* __restrict__ x, const __nv_bfloat16* __restrict__ dw,
             const __nv_bfloat16* __restrict__ w1, const __nv_bfloat16* __restrict__ w2, const __nv_bfloat16* __restrict__ grn_b, int zero) {
    extern __shared__ __align__(1024) uint8_t smem[];
    const uint32_t sbase = smem_u32(smem);
    const uint32_t bar_full = sbase + P1_OFF_BAR, bar_empty = bar_full + P1_NST * 8, bar_w = bar_empty + P1_NST * 8;
    const uint32_t bar_xfull = bar_w + 24, bar_raw = bar_xfull + 16, bar_done = bar_raw + 16;
    const int tid = threadIdx.x;
    const int warp = __shfl_sync(0xffffffffu, tid >> 5, 0), lane = tid & 31;
    const uint32_t rank = cluster_rank();
    const int cl = blockIdx.x >> 1;
    const bool small = cl >= 4 * NGRP;
    const int nwg = small ? 2 : 3, cb0 = small ? (blockIdx.x - 8 * NGRP) * 2 : (blockIdx.x & 7) * 3;
    uint8_t* const ring = reinterpret_cast<uint8_t*>(g_ln);
    const int ln0 = 2 + (blockIdx.x >> 2), items = blockIdx.x >= 128 ? -1 : small ? 1 : (NT128 - 1 - ln0) / LN_STEP + 1;

    TSTAMP(0, 0);
    TRACEW(110 + warp, 0);

    if (warp >= 12) {
        reg_dec<56>();
        asm volatile("barrier.cluster.arrive.relaxed.aligned;\n" ::: "memory");
        asm volatile("barrier.cluster.wait.aligned;\n" ::: "memory");
        {
            auto ring_row = [&](int p) {
                const int n = (p & 8) * 8 + (lane >> 3) * 8 + (p & 3) * 2 + (p >> 2 & 1);
                return n * 128 + (((lane ^ n) & 7) << 4);
            };
            const uint8_t* xsrc = reinterpret_cast<const uint8_t*>(x) + (size_t)(32 * 8 + blockIdx.x * 2 + (warp & 1)) * P1_X;
            const uint32_t xbar = bar_xfull + (warp & 1) * 8, xdst = sbase + P1_OFF_X + (warp & 1) * P1_X;
            const uint32_t sdw = sbase + P1_OFF_DW + (lane & 7) * 16;
            uint32_t src = xdst - P1_OFF_X + (lane >> 3) * (C_DIM * 2) + (lane & 7) * 16;
            int row0 = ring_row((blockIdx.x & 7) * 2 + (warp & 1)) ^ 288, slot = blockIdx.x >> 3, used = 0;
            auto next = [&]() {
                xsrc += (size_t)LN_STEP * 8 * P1_X;
                if (elect_one()) {
                    mbar_expect_tx(xbar, P1_X);
                    bulk_g2s(xdst, xsrc, P1_X, xbar);
                }
                __syncwarp();
            };
#pragma unroll 1
            for (int i = -1; i < items; i++) {
                if (warp == 14) TRACEW(128 + i, 0);
                const int last = i > 0 ? 3 : i ? 2 + (warp >> 1 & 1) : 1;
#pragma unroll 1
                for (int ps = i < 0 ? last - 4 : 0; ps <= last; ps += i < 0 ? 4 : 1) {
                    if (i < 0 && ps > 0) STAMPT(416, 6);
                    if (i < 0 && ps > 0) mbar_wait(bar_raw, 0);
                    if (i < 0 && ps > 0) STAMPT(416, 7);
                    if (ps == 0) {
                        if (used) flag_wait<false>(&g_flag[slot][1][0], used);
                        if (i && i + 1 < items && elect_one())
                            asm volatile("cp.async.bulk.prefetch.L2.global [%0], %1;\n" ::"l"(xsrc + (size_t)LN_STEP * 8 * P1_X), "r"(P1_X) : "memory");
                        if (i) mbar_wait(xbar, ~i & 1);
                        else mbar_wait(bar_raw + 8, 0);
                        if (warp == 14) TRACEW(128 + i, 1);
                    }
                    uint32_t v[6][4];
#pragma unroll
                    for (int j = 0; j < 6; j++) lds128(v[j], src + (ps & 3) * (4 * C_DIM * 2) + j * 128);
                    ln_row(v, sdw, [&](uint32_t dep) {
                        if (i == 0 && ps == 1 && lane < 2) mbar_arrive_cluster(mapa(bar_empty, lane) + (dep & zero));
                        if (ps == 3 && i > 0 && i + 1 < items && !__any_sync(0xffffffffu, dep & zero)) next();
                    });
                    uint8_t* dst = ring + (slot * LN_TILE + (ps & 1) * 4096 + (row0 ^ (ps & 2) * 144));
#pragma unroll
                    for (int j = 0; j < 6; j++)
                        asm volatile("{\n.reg .pred p;\nsetp.ge.s32 p, %5, 0;\n@p st.global.v4.u32 [%0], {%1,%2,%3,%4};\n}\n"
                                     ::"l"(dst + j * 16384), "r"(v[j][0]), "r"(v[j][1]), "r"(v[j][2]), "r"(v[j][3]), "r"(ps) : "memory");
                }
                if (warp == 14) TRACEW(128 + i, 2);
                asm volatile("fence.proxy.async.global;\nfence.acq_rel.cta;\n" ::: "memory");
                if (i < 0) {
                    bar_sync(4, 128);
                    if (warp < 14) break;
                    row0 ^= 288;
                    slot += 16;
                } else {
                    if (i) mbar_wait(bar_done, ~i & 1);
                    else {
                        src += P1_OFF_X;
                        slot = ln0;
                        row0 = ring_row((blockIdx.x & 3) * 4 + (warp & 1) * 2);
                    }
                    __syncwarp();
                    if (lane == 0) mbar_arrive(bar_done);
                    if ((slot += LN_STEP) >= LN_RING) { slot -= LN_RING; used += 12; }
                }
            }
            if ((warp < 14 || items < 0) && lane < 2) mbar_arrive_cluster(mapa(bar_empty, lane));
        }
        if (warp == 12) {
            int prev = 0, t = p1_tile(small ? 0 : cl >> 2, small), next = p1_tile(small ? 1 : (cl >> 2) + NGRP, small);
            const uint32_t rbase = mapa(sbase, lane & 1);
            int i = 0;
#pragma unroll 1
            for (; t < NT128; i++) {
                const int s0 = (i & 1) * 2, par = (i >> 1) & 1;
                const int round = t / LN_RING, slot = t - round * LN_RING;
                const uint8_t* src = ring + slot * LN_TILE + rank * (P1_SLOT / 2);
                int draw = i + 2;
                if (rank == 0 && lane == 0 && !small) draw = 2 * NGRP + atomicAdd(&g_flag[LN_RING + ((cl >> 1) & 1)][cl & 1][0], 1u);
                flag_wait<true>(&g_flag[slot][0][0], 8 * round + 8);
                TRACEW(i, 2);
                if (i == 0) STAMPT(384, 10);
                if (i == 2) STAMPT(384, 13);
                if (i == 3) STAMPT(384, 14);
                asm volatile("fence.proxy.async.global;\n" ::: "memory");
                draw = p1_tile(__shfl_sync(0xffffffffu, draw, 0), small);
#pragma unroll
                for (int h = 0; h < 2; h++) {
                    mbar_wait(bar_empty + (s0 + h) * 8, par);
                    TRACEW(i, 4 + h);
                    if (i == 0 && h == 1) STAMPT(384, 11);
                    if (elect_one()) {
                        mbar_expect_tx(bar_full + (s0 + h) * 8, P1_SLOT + 16 - 16 * h);
                        bulk_g2s_mc(sbase + (s0 + h) * P1_SLOT + rank * (P1_SLOT / 2), src + h * P1_SLOT, P1_SLOT / 2, bar_full + (s0 + h) * 8, (uint16_t)3);
                    }
                    __syncwarp();
                    if (h == 0 && rank == 0 && lane < 2)
                        asm volatile("st.async.shared::cluster.mbarrier::complete_tx::bytes.v4.u32 [%0], {%1, %2, %3, %3}, [%4];\n"
                                     ::"r"(rbase + P1_OFF_TILE + (i & 3) * 16), "r"((t - prev) * (2 * H_TILE)), "r"((int)(next < NT128)), "r"(draw),
                                       "r"(rbase + P1_OFF_BAR + s0 * 8) : "memory");
                }
                prev = t;
                t = next;
                next = draw;
                if (rank != 0) {
                    mbar_wait(bar_full + s0 * 8, (i >> 1) & 1);
                    mbar_wait(bar_full + s0 * 8 + 8, (i >> 1) & 1);
                    if (lane == 0) asm volatile("red.relaxed.gpu.global.add.u32 [%0], %1;\n" ::"l"(&g_flag[slot][1][0]), "r"(nwg) : "memory");
                    asm volatile("ld.shared.u32 %0, [%1];\n" : "=r"(next) : "r"(sbase + P1_OFF_TILE + (i & 3) * 16 + 8) : "memory");
                    TRACEW(i, 3);
                }
            }
#pragma unroll 1
            for (int j = 2 * i; j < 2 * i + 4; j++) mbar_wait(bar_empty + (j & 3) * 8, (j >> 2) & 1);
        } else if (warp == 13) {
            STAMPT(416, 8);
            if (lane == 0 && blockIdx.x < 128) asm volatile("red.release.gpu.global.add.u32 [%0], 1;\n" ::"l"(&g_flag[blockIdx.x >> 3][0][0]) : "memory");
            __syncwarp();
            STAMPT(416, 9);
            const uint32_t ep = g_epoch & 1;
            asm volatile("st.shared.u32 [%0], %1;\n" ::"r"(sbase + P1_OFF_TILE - 4), "r"(ep) : "memory");
            if (blockIdx.x == 18) g_par = ep;
            if (blockIdx.x < 18) reinterpret_cast<float4*>(g_sums[ep ^ 1])[blockIdx.x * 32 + lane] = make_float4(0.f, 0.f, 0.f, 0.f);
#pragma unroll 1
            for (int i = 0; i < items; i++) {
                mbar_wait(bar_done, i & 1);
                asm volatile("fence.proxy.async.global;\n" ::: "memory");
                if (lane == 0) {
                    mbar_arrive(bar_done);
                    asm volatile("red.release.gpu.global.add.u32 [%0], %1;\n"
                                 ::"l"(&g_flag[i ? (ln0 + (i & 1) * LN_STEP) % LN_RING : 16 + (blockIdx.x >> 3)][0][0]), "r"(i ? 2 : 1) : "memory");
                }
                __syncwarp();
                TRACEW(128 + i, 3);
            }
            flag_wait<true>(&g_flag[LN_RING + 2][0][0], 48);
        }
    } else {
        if (tid == 0) {
            mbar_init(bar_raw, 1);
            mbar_init(bar_raw + 8, 1);
            mbar_init(bar_xfull, 1);
            mbar_init(bar_xfull + 8, 1);
            for (int i = 0; i < 3; i++) mbar_init(bar_w + i * 8, 1);
            asm volatile("fence.mbarrier_init.release.cluster;\n" ::: "memory");
            if (blockIdx.x < 128) {
                mbar_expect_tx(bar_raw, P1_X + C_DIM * 2);
                bulk_g2s(sbase + P1_OFF_DW, dw, C_DIM * 2, bar_raw);
                for (int i = 0; i < 2; i++) bulk_g2s(sbase + i * P1_X + P1_X / 2, x + (size_t)(blockIdx.x * 16 + i * 8) * C_DIM, P1_X / 2, bar_raw);
                asm volatile("cp.async.bulk.prefetch.L2.global [%0], 9216;\n" ::"l"(w1 + blockIdx.x * 4608) : "memory");
                mbar_expect_tx(bar_raw + 8, P1_X);
                for (int i = 0; i < 2; i++) bulk_g2s(sbase + i * P1_X, x + (size_t)(16 * 128 + blockIdx.x * 16 + i * 8) * C_DIM, P1_X / 2, bar_raw + 8);
            }
            for (int i = 0; i < nwg; i++) {
                mbar_expect_tx(bar_w + i * 8, P1_SLOT);
                tma2(sbase + (1 + i) * P1_SLOT, &wmap, (cb0 + i) * 64, 0, bar_w + i * 8);
                tma2(sbase + (1 + i) * P1_SLOT + P1_SLOT / 2, &wmap, (cb0 + i) * 64, 192, bar_w + i * 8);
            }
            for (int i = 0; i < 2 && !small; i++) {
                mbar_expect_tx(bar_xfull + i * 8, P1_X);
                bulk_g2s(sbase + P1_OFF_X + i * P1_X, x + (size_t)(32 * 128 + blockIdx.x * 32 + i * 16) * C_DIM, P1_X, bar_xfull + i * 8);
            }
        }
        if (tid == 32) {
            mbar_init(bar_done, 3);
            mbar_arrive(bar_done);
            asm volatile("fence.mbarrier_init.release.cluster;\n" ::: "memory");
        }
        if (tid == 64) {
            for (int i = 0; i < P1_NST; i++) {
                mbar_init(bar_full + i * 8, 1);
                mbar_init(bar_empty + i * 8, 8 * nwg);
            }
            asm volatile("fence.mbarrier_init.release.cluster;\n" ::: "memory");
            if (blockIdx.x < 64) (&g_half[0][0])[blockIdx.x] = 0;
            else if (blockIdx.x == 64) g_prog = 0;
            else if (blockIdx.x < 67) g_img[blockIdx.x - 65] = 0;
        }
        __syncwarp();
        asm volatile("barrier.cluster.arrive.relaxed.aligned;\n" ::: "memory");
        reg_inc<152>();
        TRACEW(110 + warp, 1);
        const int wg = warp >> 2, w = warp & 3;
        gdc_launch();
        asm volatile("barrier.cluster.wait.aligned;\n" ::: "memory");
        if (wg == nwg) {
            p1_w2(w2, grn_b, w, lane);
            return;
        }
        const uint32_t slot_free = mapa(bar_empty, lane & 1) + (lane >> 1) * 8;
        if (lane < 8 && (lane >> 1) != 1 + wg && (wg || lane > 1)) mbar_arrive_cluster(slot_free);
        if (wg == 1) bar_arrive(1, 256);
        uint32_t a[24][4], ex[2], gen = 0;
        const uint32_t wsrc = sbase + (1 + wg) * P1_SLOT + ((lane >> 4) * 8 + (lane & 7)) * 128 + (((2 * w + ((lane >> 3) & 1)) ^ (lane & 7)) << 4);
#pragma unroll 1
        for (int it = 0; it < 2; it++) {
            if (it) mbar_wait(bar_w + wg * 8, 0);
            TRACEW(110 + warp, 5);
            if (it || wg == 0) {
#pragma unroll
            for (int k = 0; k < 24; k++) ldsm4t(a[k], wsrc + k * 2048);
#pragma unroll
            for (int r = 0; r < 2; r++) {
                float t = 0.f;
#pragma unroll
                for (int j = 0; j < 6; j++) {
                    uint32_t c = bf2_mul(a[4 * j][r], a[4 * j][r]);
#pragma unroll
                    for (int k = 1; k < 8; k++) c = bf2_fma(a[4 * j + k / 2][r + (k & 1) * 2], a[4 * j + k / 2][r + (k & 1) * 2], c);
                    t += bf_lo(c) + bf_hi(c);
                }
                t += __shfl_xor_sync(0xffffffffu, t, 1);
                t += __shfl_xor_sync(0xffffffffu, t, 2);
                asm("sqrt.approx.f32 %0, %0;\n" : "+f"(t));
                ex[r] = min(max(__float_as_uint(13.9f * t) >> 23, 72u), 198u);
            }
            asm volatile("{\n.reg .pred p;\nsetp.gt.u32 p, %1, 7;\nbar.red.or.pred p, %2, 128, p;\nselp.u32 %0, 1, 0, p;\n}\n"
                         : "=r"(gen) : "r"(max(ex[0] - 125u, ex[1] - 125u)), "r"(5 + wg) : "memory");
            gen = __shfl_sync(0xffffffffu, gen, 0) & it;
            if (it) {
                if ((lane & 3) < 2) g_ex[(cb0 + wg) * 64 + w * 16 + (lane & 1) * 8 + (lane >> 2)] = lane & 1 ? ex[1] : ex[0];
                if ((lane >> 1) == 1 + wg) mbar_arrive_cluster(slot_free);
                __syncwarp();
            }
            }
            if (gen) {
#pragma unroll
                for (int k = 0; k < 24; k++)
#pragma unroll
                    for (int j = 0; j < 4; j++) a[k][j] = bf2_mul(a[k][j], (268u - ex[j & 1]) * 0x00800080u);
            }
            if (it || wg == 1) {
#pragma unroll
                for (int k = 0; k < 24; k++)
#pragma unroll
                    for (int j = 0; j < 4; j++) {
                        a[k][j] = bf2_as_h2(bf2_mul(a[k][j], 0x07800780u));
                        asm volatile("" : "+r"(a[k][j]));
                    }
            }
            TRACEW(110 + warp, 6);
        }
#pragma unroll
        for (int j = 0; j < 4; j++)
            asm volatile("st.shared.u32 [%0], %1;\n" ::"r"(sbase + P1_OFF_A + warp * 512 + (j & 1) * 256 + (j >> 1) * 128 + lane * 4), "r"(a[23][j]) : "memory");
        asm volatile("fence.proxy.async.shared::cta;\n" ::: "memory");
        TRACEW(110 + warp, 7);
        const uint32_t ex2 = ex[0] | ex[1] << 16;
        p1_consumer(a, gen ? 0x7f007f00u - (ex2 << 7) : (0x008e008eu - ex2) << 10, gen, sbase, wg, nwg, cb0 + wg, w, lane, zero);
        TSTAMP(0, 30);
    }
}

constexpr int P2_B = 24576, P2_NB = 5;
constexpr int P2_A = 3072, P2_NA = 5;
constexpr int P2_XROW = C_DIM * 2;
constexpr int P2_OFF_A = P2_B * P2_NB;
constexpr int P2_OFF_X = P2_OFF_A + 3 * P2_NA * P2_A;
constexpr int P2_XHALF = 32 * P2_XROW + 64;
constexpr int P2_OFF_BIAS = P2_OFF_X + 64 * P2_XROW + 64;
constexpr int P2_OFF_GRN = P2_OFF_BIAS + C_DIM * 4;
constexpr int P2_OFF_BAR = P2_OFF_GRN + HID * 2;
constexpr int P2_SMEM = P2_OFF_BAR + (2 * P2_NB + 6 * P2_NA + 3) * 8;
constexpr int P2_LAG = 17;
constexpr int P2_NCL = NUM_CTAS / 2, P2_ITEMS = NT128 / P2_NCL, P2_SHARED = NT128 - P2_ITEMS * P2_NCL;
constexpr int P2_POS = P2_LAG * (P2_ITEMS - 1) + 48;
__device__ __forceinline__ int p2_start(int n) { return n < 0 ? 0 : n == P2_ITEMS ? P2_POS - 24 : P2_LAG * n; }
constexpr int P2_FOLD = 17;
constexpr int P2_XC = 8 * P2_XROW;
constexpr int P2_DELTA = 7;
__device__ __forceinline__ int p2_tile(int cl, int n) {
    return n == 0 ? NT128 - 1 - cl : n < 0 || n == P2_ITEMS ? NT128 - 1 - P2_NCL - (cl >> 1) : cl + P2_NCL * (n - 1);
}

constexpr int P2_EG = 2;
__device__ __forceinline__ void p2_epilogue(const uint32_t (&acc0)[48], const uint32_t (&acc1)[48], uint32_t sx, uint32_t sb, float up, int zero) {
    uint32_t v[2][P2_EG][4];
    float b[2][8];
    auto load = [&](int c, uint32_t a) {
#pragma unroll
        for (int j = 0; j < 2; j++)
            asm volatile("ld.shared.v4.f32 {%0,%1,%2,%3}, [%4];\n" : "=f"(b[c & 1][4 * j]), "=f"(b[c & 1][4 * j + 1]), "=f"(b[c & 1][4 * j + 2]), "=f"(b[c & 1][4 * j + 3])
                         : "r"(sb + c * 128 + j * 16) : "memory");
#pragma unroll
        for (int j = 0; j < P2_EG; j++) {
            const int u = c * P2_EG + j;
            asm volatile("ld.shared.v4.u32 {%0,%1,%2,%3}, [%4];\n" : "=r"(v[c & 1][j][0]), "=r"(v[c & 1][j][1]), "=r"(v[c & 1][j][2]), "=r"(v[c & 1][j][3])
                         : "r"(a + (u >> 1) * 64 + (u & 1) * 4 * P2_XROW) : "memory");
        }
    };
    load(0, sx);
#pragma unroll
    for (int c = 0; c < 24 / P2_EG; c++) {
        if (c + 1 < 24 / P2_EG) load(c + 1, sx + (v[c & 1][P2_EG - 1][0] & zero));
#pragma unroll
        for (int j = 0; j < P2_EG; j++) {
            const int u = c * P2_EG + j, i = 8 * ((u >> 1) % 6) + (u & 1);
            const uint32_t (&acc)[48] = u < 12 ? acc0 : acc1;
            uint32_t (&w)[4] = v[c & 1][j];
#pragma unroll
            for (int e = 0; e < 4; e++)
                w[e] = bf2_add(pack_bf16(fmaf(h_lo(acc[i + 2 * e]), up, b[c & 1][2 * e]), fmaf(h_hi(acc[i + 2 * e]), up, b[c & 1][2 * e + 1])), w[e]);
            asm volatile("st.shared.v4.u32 [%4], {%0,%1,%2,%3};\n" ::"r"(w[0]), "r"(w[1]), "r"(w[2]), "r"(w[3]),
                         "r"(sx + (u >> 1) * 64 + (u & 1) * 4 * P2_XROW) : "memory");
        }
    }
}

__device__ __forceinline__ void p2_unpack(uint4& u, uint32_t o1, uint32_t o2, uint32_t o3) {
    u.z = o1 & 0xbff8bff8u;
    u.y = o2 & 0xbff8bff8u;
    u.w = o3 & 0xbff8bff8u;
    u.x = (__byte_perm(o1, 0, 0x2301) & 0x07400740u) | ((__byte_perm(o2, o3, 0x6240) << 3) & 0x38383838u) | ((__byte_perm(o2, o3, 0x3715) << 1) & 0x80808080u);
}
__device__ __forceinline__ uint32_t h2_mul(uint32_t a, uint32_t b) {
    uint32_t r;
    asm("mul.rn.f16x2 %0, %1, %2;\n" : "=r"(r) : "r"(a), "r"(b));
    return r;
}
__device__ __forceinline__ void p2_epilogue_add(const uint32_t (&acc)[48], uint8_t* o, float f, int zero) {
#pragma unroll
    for (int t = 0; t < 12; t++) {
        uint32_t v[4];
#pragma unroll
        for (int e = 0; e < 4; e++) {
            v[e] = acc[8 * (t >> 1) + (t & 1) + 2 * e];
            asm volatile("" : "+r"(v[e]));
            v[e] = pack_bf16(h_lo(v[e]) * f, h_hi(v[e]) * f);
        }
        asm volatile("red.global.add.noftz.v4.bf16x2 [%0], {%1,%2,%3,%4};\n" ::"l"(o + (t >> 1) * 64 + (t & 1) * 4 * P2_XROW),
                     "r"(v[0]), "r"(v[1]), "r"(v[2]), "r"(v[3]) : "memory");
        if (t % 3 == 2) sched_break(zero);
    }
}

__global__ void __cluster_dims__(2, 1, 1) __launch_bounds__(512, 1)
pass2_kernel(const __nv_bfloat16* __restrict__ x, const __nv_bfloat16* __restrict__ grn_g, __nv_bfloat16* __restrict__ out, int zero) {
    extern __shared__ __align__(1024) uint8_t smem[];
    const uint32_t sbase = smem_u32(smem);
    const uint32_t bar_bfull = sbase + P2_OFF_BAR, bar_bempty = bar_bfull + P2_NB * 8;
    const uint32_t bar_afull = bar_bempty + P2_NB * 8, bar_aempty = bar_afull + 3 * P2_NA * 8;
    const uint32_t bar_xfull = bar_aempty + 3 * P2_NA * 8, bar_oready = bar_xfull + 8, s_pos = bar_xfull + 16;
    int tid;
    asm volatile("mov.u32 %0, %%tid.x;\n" : "=r"(tid));
    const int warp = __shfl_sync(0xffffffffu, tid >> 5, 0), lane = tid & 31;
    const uint32_t rank = cluster_rank();
    const int cl = blockIdx.x >> 1, pair = cl >> 1;
    const int k0 = (4 * pair + (cl & 1) * (48 - P2_POS % 48)) % 48;
    const int head = pair < P2_SHARED && !(cl & 1), tail = pair < P2_SHARED && (cl & 1);

    uint32_t par, gg[4];
    float pre[4];
    if (warp < 12) {
        asm volatile("ld.global.cg.u32 %0, [%1];\n" : "=r"(par) : "l"(&g_par) : "memory");
#pragma unroll
        for (int i = 0; i < 4; i++) {
            asm volatile("ld.global.cg.f32 %0, [%1];\n" : "=f"(pre[i]) : "l"(&g_sums[i & 1][HID + (i >> 1) * C_DIM + tid]) : "memory");
            asm volatile("ld.global.nc.u16 %0, [%1];\n" : "=r"(gg[i]) : "l"(grn_g + tid + 384 * i) : "memory");
        }
    }
    TSTAMP(1, 0);
    if (tid == 384) {
        for (int i = 0; i < P2_NB; i++) {
            mbar_init(bar_bfull + i * 8, 1);
            mbar_init(bar_bempty + i * 8, 24);
        }
        for (int i = 0; i < 3 * P2_NA; i++) {
            mbar_init(bar_afull + i * 8, 1);
            mbar_init(bar_aempty + i * 8, 4);
        }
        mbar_init(bar_xfull, 2);
        mbar_init(bar_oready, 4);
        asm volatile("st.shared.u32 [%0], 0;\n" ::"r"(s_pos) : "memory");
        asm volatile("fence.mbarrier_init.release.cluster;\n" ::: "memory");
    }
    __syncthreads();
    cluster_sync_relaxed();

    if (warp >= 12) {
        reg_dec<32>();
        if (warp == 12) {
            const uint8_t* wsrc = reinterpret_cast<const uint8_t*>(g_w2img) + rank * (P2_B / 2);
            int st = 0, ph = 1, kb = k0, m = 0, r = 0;
            const int busy = head ? 0 : tail ? P2_POS - 24 : P2_POS;
#pragma unroll 1
            for (int p = 0; p < P2_POS; p++) {
                if (p == 0 || p == P2_FOLD) {
                    flag_wait<true>(&g_img[p != 0], p ? 96 * 4 : 48);
                    asm volatile("fence.proxy.async.global;\n" ::: "memory");
                    if (p) wsrc += sizeof(g_w2img[0]);
                }
                mbar_wait(bar_bempty + st * 8, ph);
                TR2P(p, 0);
                if (elect_one()) {
                    mbar_expect_tx(bar_bfull + st * 8, P2_B);
                    bulk_g2s_mc(sbase + st * P2_B + rank * (P2_B / 2), wsrc + kb * P2_B, P2_B / 2, bar_bfull + st * 8, (uint16_t)3);
                    asm volatile("st.volatile.shared.u32 [%0], %1;\n" ::"r"(s_pos), "r"(p) : "memory");
                    const int idle = 2 - min(m, P2_ITEMS - 1) + max(m - 2 + (r >= 48 - 2 * P2_LAG), 0) - ((unsigned)(p - busy) < 24);
                    if (idle) asm volatile("mbarrier.arrive.shared::cta.b64 _, [%0], %1;\n" ::"r"(bar_bempty + st * 8), "r"(idle * 8) : "memory");
                    if (rank == 0) asm volatile("red.relaxed.gpu.global.add.u32 [%0], 1;\n" ::"l"(&g_prog) : "memory");
                }
                __syncwarp();
                if (++st == P2_NB) { st = 0; ph ^= 1; }
                if (++kb == 48) kb = 0;
                if (++r == P2_LAG) { r = 0; m++; }
            }
            mbar_wait(bar_bempty + st * 8, ph);
            if (lane == 0) mbar_arrive(bar_bfull + st * 8);
#pragma unroll 1
            for (int p = 1; p < P2_NB; p++) {
                if (++st == P2_NB) { st = 0; ph ^= 1; }
                mbar_wait(bar_bempty + st * 8, ph);
            }
        } else if (warp == 13) {
            const uint8_t* src[3];
            int n[3], left[3], wrap[3];
            uint32_t st[3];
            auto item = [&](int w) {
                const int u = (k0 + p2_start(n[w])) % 48;
                left[w] = n[w] < 0 || n[w] == P2_ITEMS ? 24 : 48;
                wrap[w] = left[w] - (48 - u);
                src[w] = reinterpret_cast<const uint8_t*>(g_h) + (size_t)p2_tile(cl, n[w]) * (2 * H_TILE) + rank * H_HALF + u * H_STEP;
            };
#pragma unroll
            for (int w = 0; w < 3; w++) {
                n[w] = w == 2 && head ? -1 : w;
                st[w] = 0x80000000u;
                item(w);
            }
            gdc_wait();
#pragma unroll 1
            for (int done = 0; done < 3;) {
                bool idle = true;
#pragma unroll
                for (int w = 0; w < 3; w++) {
                    const uint32_t o = (st[w] & 0xff) + w * P2_NA * 8;
                    if (left[w] >= 0 && mbar_test(bar_aempty + o, st[w] >> 31)) {
                        idle = false;
                        if (left[w] == 0) {
                            if (lane == 0) mbar_arrive(bar_afull + o);
                            left[w] = -1;
                            done++;
                        } else {
                            if (elect_one()) {
                                mbar_expect_tx(bar_afull + o, P2_A);
                                bulk_g2s(sbase + P2_OFF_A + o * (P2_A / 8), src[w], P2_A, bar_afull + o);
                            }
                            __syncwarp();
                            src[w] += H_STEP;
                            st[w] += 8;
                            if ((st[w] & 0xff) == P2_NA * 8) st[w] ^= 0x80000000u | (P2_NA * 8);
                            if (--left[w] == wrap[w]) src[w] -= 48 * H_STEP;
                            if (left[w] == 0 && (n[w] += 3) < P2_ITEMS + tail) item(w);
                        }
                    }
                }
                if (idle) __nanosleep(64);
                SAFE_BREAK
            }
        } else if (warp == 14) {
            const uint32_t sx = sbase + P2_OFF_X;
            size_t o = 0;
            auto pace = [&](int target) {
                int v;
                while (true) {
                    asm volatile("ld.volatile.shared.u32 %0, [%1];\n" : "=r"(v) : "r"(s_pos) : "memory");
                    if (v * 16 >= target) break;
                    __nanosleep(100);
                    SAFE_BREAK
                }
            };
#pragma unroll 1
            for (int n = -head; n <= P2_ITEMS; n++) {
                const size_t on = (size_t)(2 * p2_tile(cl, n) + rank) * (64 * C_DIM * 2);
                const bool st = n + head > 0, ld = n < P2_ITEMS;
                if (st) mbar_wait(bar_oready, (n - 1 + head) & 1);
                TR2P(n + 1, 1);
                if (lane == 0) {
                    if (n == 1 && head) {
                        asm volatile("cp.async.bulk.wait_group 0;\nfence.proxy.async.global;\n" ::: "memory");
                        asm volatile("st.release.gpu.global.u32 [%0], 1;\n" ::"l"(&g_half[pair][rank]) : "memory");
                    }
                    if (ld) mbar_expect_tx(bar_xfull, 64 * C_DIM * 2);
                    const bool paced = st && n < P2_ITEMS - 1;
                    int t = (P2_LAG * (n - 1) + 52) * 16;
#pragma unroll 1
                    for (int c = 0; st && c < 64 * P2_XROW; c += P2_XC) {
                        if (paced) pace(t += 11);
                        bulk_s2g(reinterpret_cast<uint8_t*>(out) + o + c, sx + c + (c >= 32 * P2_XROW ? 64 : 0), P2_XC);
                        asm volatile("cp.async.bulk.commit_group;\n" ::: "memory");
                    }
#pragma unroll 1
                    for (int c = 0; ld && c < 64 * P2_XROW; c += P2_XC) {
                        if (c == 0) asm volatile("cp.async.bulk.wait_group.read 4;\n" ::: "memory");
                        if (c == 32 * P2_XROW) asm volatile("cp.async.bulk.wait_group.read 0;\n" ::: "memory");
                        if (paced) pace(t += 11);
                        bulk_g2s(sx + c + (c >= 32 * P2_XROW ? 64 : 0), reinterpret_cast<const uint8_t*>(x) + on + c, P2_XC, bar_xfull);
                    }
                    TR2P(n + 1, 2);
                    if (rank == 0 && n > 0 && n < P2_ITEMS - 2)
                        flag_wait<false>(&g_prog, P2_NCL * (P2_LAG * n + 48) + (tail ? P2_SHARED - P2_NCL : P2_SHARED) * P2_DELTA);
                    if (ld) mbar_arrive(bar_xfull);
                    TR2P(n + 1, 3);
                }
                __syncwarp();
                o = on;
            }
            asm volatile("cp.async.bulk.wait_group 0;\n" ::: "memory");
            TR2P(30, 1);
        }
    } else {
        reg_inc<160>();
        const int wg = warp >> 2, w = warp & 3, g = lane >> 2, q = lane & 3;
        const uint32_t sx = sbase + P2_OFF_X + (g & 1) * P2_XHALF + (w * 8 + (g >> 1)) * P2_XROW + q * 16;
        const uint32_t af = bar_afull + wg * P2_NA * 8;
        const uint32_t s_a = sbase + P2_OFF_A + wg * P2_NA * P2_A + (lane >> 3) * 512 + (lane & 7) * 64 +
                             ((w ^ ((lane & 7) >> 1)) << 4);
        uint32_t acc0[48], acc1[48];
        float up;
        uint4 a0[2], a1[2];
        uint32_t st = 0, ph = 0;

        {
            float4* s_red = reinterpret_cast<float4*>(smem + P2_OFF_BIAS);
            const float* sums = g_sums[par];
            float gx[4], part = 0.f, mx = 0.f;
            TSTAMP(1, 27);
            gdc_wait();
            TSTAMP(1, 1);
#pragma unroll
            for (int i = 0; i < 4; i++) gx[i] = __ldcg(sums + tid + 384 * i);
            if (blockIdx.x == 120 && tid < (LN_RING + 3) * 2) (&g_flag[0][0][0])[tid * 8] = 0;
            if (blockIdx.x == 121 && tid == 0) atomicAdd(&g_epoch, 1u);
            float z = __uint_as_float(__reduce_max_sync(0xffffffffu, __float_as_uint(pre[2] + pre[3])));
#pragma unroll
            for (int i = 0; i < 4; i++) {
                asm("sqrt.approx.f32 %0, %1;\n" : "=f"(gx[i]) : "f"(fmaf(gx[i], HSCALE * HSCALE, 1e-6f)));
                part += gx[i];
                gx[i] *= bf_lo(gg[i]);
                mx = fmaxf(mx, fabsf(gx[i]));
            }
#pragma unroll
            for (int o = 16; o > 0; o >>= 1) part += __shfl_xor_sync(0xffffffffu, part, o);
            mx = __uint_as_float(__reduce_max_sync(0xffffffffu, __float_as_uint(mx)));
            TSTAMP(1, 26);
            if (lane == 0) s_red[warp] = make_float4(part, mx, z, 0.f);
            bar_sync(1, 384);
            float tot = 0.f;
            {
                const float4 t = s_red[min(lane & 15, 11)];
                tot = (lane & 15) < 12 ? t.x : 0.f;
#pragma unroll
                for (int o = 8; o > 0; o >>= 1) tot += __shfl_xor_sync(0xffffffffu, tot, o);
                mx = __uint_as_float(__reduce_max_sync(0xffffffffu, __float_as_uint(t.y)));
                z = __uint_as_float(__reduce_max_sync(0xffffffffu, __float_as_uint(t.z)));
            }
            const float inv = __fdividef(1.0f, fmaf(tot, 1.0f / HID, 1e-6f));
            const uint32_t j = max(__float_as_uint(fmaf(mx, inv, 1.0f) * 1.01f) >> 23, 130u) - 130u;
            const float dn = __uint_as_float((127u - j) << 23);
#pragma unroll
            for (int i = 0; i < 4; i++)
                *reinterpret_cast<uint16_t*>(smem + P2_OFF_GRN + (tid + 384 * i) * 2) = pack_f16(fmaf(gx[i], inv, 1.0f) * dn, 0.f);
            up = (HSCALE * 1.00235f) * __uint_as_float(min(acc_exp(z) - 9u + j, 253u) << 23);
            TSTAMP(1, 25);
            bar_sync(1, 384);
            reinterpret_cast<float*>(smem + P2_OFF_BIAS)[tid] = pre[0] + pre[1];
            if (wg == 1 && blockIdx.x < 96) {
                const uint4* src = g_w2img[0] + blockIdx.x * 768 + tid - 128;
                const uint4 fk = *reinterpret_cast<const uint4*>(smem + P2_OFF_GRN + blockIdx.x * 32 + (tid & 8) * 2);
                uint4 v[6];
#pragma unroll
                for (int i = 0; i < 6; i++) v[i] = __ldcg(src + i * 128);
                auto fold = [&](uint32_t b, uint32_t f) { return (h2_mul(b, f) + 0x00040004u) & 0xfff8fff8u; };
#pragma unroll
                for (int i = 0; i < 6; i++)
                    g_w2img[1][blockIdx.x * 768 + tid - 128 + i * 128] = make_uint4(fold(v[i].x, fk.x), fold(v[i].y, fk.y), fold(v[i].z, fk.z), fold(v[i].w, fk.w));
                asm volatile("fence.proxy.async.global;\n" ::: "memory");
                __threadfence();
                __syncwarp();
                if (lane == 0) asm volatile("red.release.gpu.global.add.u32 [%0], 1;\n" ::"l"(&g_img[1]) : "memory");
            }
        }
        TSTAMP(1, 28);
        int kt = k0, pos;
        const uint32_t be = lane < 2 ? mapa(bar_bempty, lane) : 0, be0 = mapa(bar_bempty, 0);
        uint32_t prev = 0, sa = 0, pa = 0;
        auto release_b = [&](uint32_t p, bool on) {
            asm volatile("{\n.reg .pred p, q;\nsetp.ne.u32 q, %2, 0;\nsetp.ne.and.u32 p, %1, 0, q;\n@p mbarrier.arrive.shared::cluster.b64 _, [%0];\n}\n"
                         ::"r"(be + p), "r"(be), "r"((uint32_t)on) : "memory");
        };
        auto arrive1 = [&](uint32_t bar) {
            asm volatile("{\n.reg .pred p;\nsetp.eq.u32 p, %1, %2;\n@p mbarrier.arrive.shared::cta.b64 _, [%0];\n}\n" ::"r"(bar), "r"(be), "r"(be0) : "memory");
        };
        auto seek = [&](int p) {
            pos = p;
            st = p % P2_NB * 8;
            ph = p / P2_NB & 1;
            int v;
            while (true) {
                asm volatile("ld.volatile.shared.u32 %0, [%1];\n" : "=r"(v) : "r"(s_pos) : "memory");
                if (__all_sync(0xffffffffu, v >= p)) break;
                __nanosleep(200);
                SAFE_BREAK
            }
        };
        bool ok_a = false;
        auto fetch = [&](uint4 (&a)[2], uint32_t done, bool rel, bool early) {
            if (!ok_a) mbar_wait(af + sa, pa);
            uint32_t o[6];
            const uint32_t src = s_a + sa * (P2_A / 8);
            asm volatile("ldmatrix.sync.aligned.m8n8.x4.trans.shared.b16 {%0,%1,%2,%3}, [%4];\n"
                         : "=r"(o[0]), "=r"(o[1]), "=r"(o[2]), "=r"(o[3]) : "r"(src) : "memory");
            asm volatile("ldmatrix.sync.aligned.m8n8.x2.trans.shared.b16 {%0,%1}, [%2];\n"
                         : "=r"(o[4]), "=r"(o[5]) : "r"(src + 2048) : "memory");
            if ((sa += 8) == P2_NA * 8) { sa = 0; pa ^= 1; }
            wg_wait<1>();
            release_b(done, rel);
            ok_a = mbar_test(af + sa, pa);
            const bool ok_b = mbar_test(bar_bfull + st, ph);
            p2_unpack(a[0], o[0], o[1], o[2]);
            p2_unpack(a[1], o[3], o[4], o[5]);
            if (early) {
                const uint32_t* t = reinterpret_cast<const uint32_t*>(smem + P2_OFF_GRN) + kt * 16 + q;
#pragma unroll
                for (int i = 0; i < 2; i++)
                    a[i] = make_uint4(h2_mul(a[i].x, t[8 * i]), h2_mul(a[i].y, t[8 * i]), h2_mul(a[i].z, t[8 * i + 4]), h2_mul(a[i].w, t[8 * i + 4]));
                if (++kt == 48) kt = 0;
            }
            if (!ok_b) mbar_wait(bar_bfull + st, ph);
        };
        const uint64_t db0 = make_desc(sbase, 128, 256);
        auto step = [&](const uint4 (&a)[2], uint4 (&an)[2], bool cont, bool early) {
            TR2(0);
            const uint64_t db = db0 + st * (P2_B / 128);
            wg_fence();
            mma_rs_n192(acc0, a[0], db, cont);
            mma_rs_n192(acc1, a[0], db + 384, cont);
            mma_rs_n192(acc0, a[1], db + 768, 1);
            mma_rs_n192(acc1, a[1], db + 768 + 384, 1);
            wg_commit();
            arrive1(af + 3 * P2_NA * 8 - 8 + (sa ? sa : P2_NA * 8));
            const uint32_t done = prev;
            prev = st;
            if ((st += 8) == P2_NB * 8) { st = 0; ph ^= 1; }
            fetch(an, done, cont, early);
            pos++;
        };
        int n = wg == 2 && head ? -1 : wg;
        seek(p2_start(n));
        fetch(a0, 0, false, n <= 0);
#pragma unroll 1
        for (;; n += 3) {
            TSTAMP(1, 2 + n);
            const int p0 = n < 0 || n == P2_ITEMS ? 12 : 0, pe = n <= 0 ? p0 + P2_FOLD / 2 : 0;
            const bool more = n + 3 < P2_ITEMS + tail;
#pragma unroll 1
            for (int p = p0; p < 24; p++) {
                step(a0, a1, p != p0, p < pe);
                step(a1, a0, true, p < pe);
            }
            if (n == P2_ITEMS) {
                flag_wait<true>(&g_half[pair][rank], 1);
                TR2(1);
                wg_wait<0>();
                TR2(2);
                release_b(prev, true);
                uint8_t* o = reinterpret_cast<uint8_t*>(out) + (size_t)((2 * p2_tile(cl, -1) + rank) * 64 + (g & 1) * 32 + w * 8 + (g >> 1)) * P2_XROW + q * 16;
                p2_epilogue_add(acc0, o, up, zero);
                p2_epilogue_add(acc1, o + 384, up, zero);
                TR2(3);
                break;
            }
            mbar_wait(bar_xfull, (n + head) & 1);
            TR2(1);
            wg_wait<0>();
            TR2(2);
            release_b(prev, true);
            p2_epilogue(acc0, acc1, sx, sbase + P2_OFF_BIAS + q * 32, up, zero);
            TR2(3);
            asm volatile("fence.proxy.async.shared::cta;\n" ::: "memory");
            __syncwarp();
            arrive1(bar_oready);
            if (!more) break;
            ok_a = false;
            seek(p2_start(n + 3));
            mbar_wait(bar_bfull + st, ph);
        }
        TSTAMP(1, 30);
    }
}

}

extern "C" void kernel_launch(void* const* d_in, const int* in_sizes, int n_in, void* d_out, int out_size) {
    const __nv_bfloat16* x = (const __nv_bfloat16*)d_in[0];
    const __nv_bfloat16* dw = (const __nv_bfloat16*)d_in[1];
    const __nv_bfloat16* w1 = (const __nv_bfloat16*)d_in[2];
    const __nv_bfloat16* w2 = (const __nv_bfloat16*)d_in[3];
    const __nv_bfloat16* grn_g = (const __nv_bfloat16*)d_in[4];
    const __nv_bfloat16* grn_b = (const __nv_bfloat16*)d_in[5];
    __nv_bfloat16* out = (__nv_bfloat16*)d_out;

    cudaFuncSetAttribute(pass1_kernel, cudaFuncAttributeMaxDynamicSharedMemorySize, P1_SMEM);
    cudaFuncSetAttribute(pass2_kernel, cudaFuncAttributeMaxDynamicSharedMemorySize, P2_SMEM);

    typedef CUresult (*EncodeFn)(CUtensorMap*, CUtensorMapDataType, cuuint32_t, void*, const cuuint64_t*, const cuuint64_t*,
                                 const cuuint32_t*, const cuuint32_t*, CUtensorMapInterleave, CUtensorMapSwizzle,
                                 CUtensorMapL2promotion, CUtensorMapFloatOOBfill);
    static EncodeFn encode = nullptr;
    if (!encode) {
        cudaDriverEntryPointQueryResult qres;
        cudaGetDriverEntryPoint("cuTensorMapEncodeTiled", (void**)&encode, cudaEnableDefault, &qres);
    }
    CUtensorMap wmap;
    const cuuint64_t gdim[2] = {HID, C_DIM};
    const cuuint64_t gstr[1] = {HID * 2};
    const cuuint32_t box[2] = {64, 192}, estr[2] = {1, 1};
    CUresult er = encode(&wmap, CU_TENSOR_MAP_DATA_TYPE_BFLOAT16, 2, (void*)w1, gdim, gstr, box, estr, CU_TENSOR_MAP_INTERLEAVE_NONE,
           CU_TENSOR_MAP_SWIZZLE_128B, CU_TENSOR_MAP_L2_PROMOTION_L2_128B, CU_TENSOR_MAP_FLOAT_OOB_FILL_NONE);
    if (er != CUDA_SUCCESS) printf("tensor map encode failed %d\n", (int)er);

    pass1_kernel<<<NUM_CTAS, 512, P1_SMEM>>>(wmap, x, dw, w1, w2, grn_b, 0);

    cudaLaunchAttribute attr[1];
    attr[0].id = cudaLaunchAttributeProgrammaticStreamSerialization;
    attr[0].val.programmaticStreamSerializationAllowed = 1;
    cudaLaunchConfig_t cfg = {};
    cfg.gridDim = dim3(NUM_CTAS);
    cfg.stream = 0;
    cfg.attrs = attr;
    cfg.numAttrs = 1;
    cfg.blockDim = dim3(512);
    cfg.dynamicSmemBytes = P2_SMEM;
    cudaLaunchKernelEx(&cfg, pass2_kernel, x, grn_g, out, 0);
}
```

```cpp
#include <cuda.h>
#include <cuda_runtime.h>
#include <cuda_bf16.h>
#include <stdint.h>
#include <stdio.h>

namespace {

constexpr int M_TOTAL = 384 * 384;
constexpr int C_DIM   = 384;
constexpr int HID     = 1536;
constexpr int NT128   = M_TOTAL / 128;
constexpr int NUM_CTAS = 132;

constexpr int NGRP = 15;
constexpr int LN_STEP = 2 * NGRP, LN_RING = 2 * LN_STEP;
#define P1_M 101
#define P1_D 10
__device__ __forceinline__ int p1_tile(int t, bool small) {
    return t + (small ? ((t + 1) * P1_M + P1_D - 1) / P1_D : t * P1_D / P1_M);
}
constexpr int LN_TILE = 128 * C_DIM * 2;
constexpr int H_TILE = 64 * HID * 3 / 2;
constexpr int H_HALF = 3072, H_STEP = 6144;

__device__ __align__(1024) uint4 g_h[(size_t)M_TOTAL * HID * 3 / 32];
__device__ __align__(1024) uint4 g_ln[LN_RING * LN_TILE / 16];
__device__ __align__(1024) uint4 g_w2img[2][HID * C_DIM * 2 / 16];
__device__ __align__(16) float g_sums[2][HID + 2 * C_DIM];
__device__ __align__(16) unsigned g_ex[HID];
__device__ unsigned g_epoch, g_par;
__device__ __align__(128) unsigned g_img[2];
__device__ __align__(128) unsigned g_prog;
__device__ __align__(128) unsigned g_half[32][2];
__device__ unsigned g_flag[LN_RING + 3][2][8];
#define TSTAMP(k, i)
#define STAMPT(t, i)
#define TRACE(wg, pos, i)
#define TRACEW(pos, i)

#define TR2(i)
#define TR2P(pos, i)
__host__ __device__ __forceinline__ int perm32(int n) {
    return (n & ~31) | (((n >> 1) & 3) << 3) | (((n >> 3) & 3) << 1) | (n & 1);
}

__device__ __forceinline__ uint32_t smem_u32(const void* p) { return (uint32_t)__cvta_generic_to_shared(p); }

__device__ __forceinline__ void mbar_init(uint32_t bar, uint32_t count) {
    asm volatile("mbarrier.init.shared::cta.b64 [%0], %1;\n" ::"r"(bar), "r"(count) : "memory");
}
__device__ __forceinline__ void mbar_expect_tx(uint32_t bar, uint32_t bytes) {
    asm volatile("mbarrier.arrive.expect_tx.shared::cta.b64 _, [%0], %1;\n" ::"r"(bar), "r"(bytes) : "memory");
}
__device__ __forceinline__ void mbar_arrive(uint32_t bar) {
    asm volatile("mbarrier.arrive.shared::cta.b64 _, [%0];\n" ::"r"(bar) : "memory");
}
__device__ __forceinline__ void mbar_arrive_cluster(uint32_t bar_cluster_addr) {
    asm volatile("mbarrier.arrive.shared::cluster.b64 _, [%0];\n" ::"r"(bar_cluster_addr) : "memory");
}
#define SAFE_BREAK
__device__ __forceinline__ void mbar_wait(uint32_t bar, uint32_t parity) {
    asm volatile(
        "{\n"
        ".reg .pred p;\n"
        "LAB_WAIT:\n"
        "mbarrier.try_wait.parity.shared::cta.b64 p, [%0], %1;\n"
        "@!p bra LAB_WAIT;\n"
        "}\n" ::"r"(bar), "r"(parity) : "memory");
}
__device__ __forceinline__ bool mbar_test(uint32_t bar, uint32_t parity) {
    uint32_t ok;
    asm volatile("{\n.reg .pred p;\n"
                 "mbarrier.test_wait.parity.shared::cta.b64 p, [%1], %2;\n"
                 "selp.u32 %0, 1, 0, p;\n}\n" : "=r"(ok) : "r"(bar), "r"(parity) : "memory");
    return ok != 0;
}
__device__ __forceinline__ uint32_t mapa(uint32_t addr, uint32_t rank) {
    uint32_t r;
    asm volatile("mapa.shared::cluster.u32 %0, %1, %2;\n" : "=r"(r) : "r"(addr), "r"(rank));
    return r;
}
__device__ __forceinline__ void bulk_g2s(uint32_t dst, const void* src, uint32_t bytes, uint32_t bar) {
    asm volatile("cp.async.bulk.shared::cluster.global.mbarrier::complete_tx::bytes [%0], [%1], %2, [%3];\n"
                 ::"r"(dst), "l"(src), "r"(bytes), "r"(bar) : "memory");
}
__device__ __forceinline__ void bulk_g2s_mc(uint32_t dst, const void* src, uint32_t bytes, uint32_t bar, uint16_t mask) {
    asm volatile("cp.async.bulk.shared::cluster.global.mbarrier::complete_tx::bytes.multicast::cluster [%0], [%1], %2, [%3], %4;\n"
                 ::"r"(dst), "l"(src), "r"(bytes), "r"(bar), "h"(mask) : "memory");
}
__device__ __forceinline__ void tma2(uint32_t dst, const CUtensorMap* map, int c0, int c1, uint32_t bar) {
    asm volatile("cp.async.bulk.tensor.2d.shared::cluster.global.tile.mbarrier::complete_tx::bytes [%0], [%1, {%2, %3}], [%4];\n"
                 ::"r"(dst), "l"(map), "r"(c0), "r"(c1), "r"(bar) : "memory");
}
template <bool ACQ>
__device__ __forceinline__ uint32_t flag_wait(const unsigned* p, unsigned target) {
    unsigned v, n = 0;
    do {
        if (ACQ) asm volatile("ld.acquire.gpu.global.u32 %0, [%1];\n" : "=r"(v) : "l"(p) : "memory");
        else asm volatile("ld.relaxed.gpu.global.u32 %0, [%1];\n" : "=r"(v) : "l"(p) : "memory");
        n++;
    } while (v < target);
    return n == 1;
}
__device__ __forceinline__ void ldsm4t(uint32_t (&r)[4], uint32_t addr) {
    asm volatile("ldmatrix.sync.aligned.m8n8.x4.trans.shared.b16 {%0,%1,%2,%3}, [%4];\n"
                 : "=r"(r[0]), "=r"(r[1]), "=r"(r[2]), "=r"(r[3]) : "r"(addr) : "memory");
}
__device__ __forceinline__ void bulk_s2g(void* dst, uint32_t src, uint32_t bytes) {
    asm volatile("cp.async.bulk.global.shared::cta.bulk_group [%0], [%1], %2;\n" ::"l"(dst), "r"(src), "r"(bytes) : "memory");
}
__device__ __forceinline__ void cluster_sync_relaxed() {
    asm volatile("barrier.cluster.arrive.relaxed.aligned;\nbarrier.cluster.wait.aligned;\n" ::: "memory");
}
__device__ __forceinline__ void gdc_wait() { asm volatile("griddepcontrol.wait;\n" ::: "memory"); }
__device__ __forceinline__ void gdc_launch() { asm volatile("griddepcontrol.launch_dependents;\n" ::: "memory"); }
__device__ __forceinline__ uint32_t cluster_rank() {
    uint32_t r;
    asm volatile("mov.u32 %0, %%cluster_ctarank;\n" : "=r"(r));
    return r;
}
__device__ __forceinline__ bool elect_one() {
    uint32_t pred;
    asm volatile("{\n.reg .pred p;\nelect.sync _|p, 0xffffffff;\nselp.u32 %0, 1, 0, p;\n}\n" : "=r"(pred));
    return pred != 0;
}
__device__ __forceinline__ void wg_fence() { asm volatile("wgmma.fence.sync.aligned;\n" ::: "memory"); }
__device__ __forceinline__ void wg_commit() { asm volatile("wgmma.commit_group.sync.aligned;\n" ::: "memory"); }
template <int N> __device__ __forceinline__ void wg_wait() {
    asm volatile("wgmma.wait_group.sync.aligned %0;\n" ::"n"(N) : "memory");
}
template <int R> __device__ __forceinline__ void reg_inc() { asm volatile("setmaxnreg.inc.sync.aligned.u32 %0;\n" ::"n"(R)); }
template <int R> __device__ __forceinline__ void reg_dec() { asm volatile("setmaxnreg.dec.sync.aligned.u32 %0;\n" ::"n"(R)); }
__device__ __forceinline__ void bar_sync(int id, int n) { asm volatile("bar.sync %0, %1;\n" ::"r"(id), "r"(n) : "memory"); }
__device__ __forceinline__ void bar_arrive(int id, int n) { asm volatile("bar.arrive %0, %1;\n" ::"r"(id), "r"(n) : "memory"); }

__device__ __forceinline__ uint64_t make_desc(uint32_t saddr, uint32_t lbo, uint32_t sbo) {
    return (uint64_t)((saddr & 0x3FFFF) >> 4) | ((uint64_t)(lbo >> 4) << 16) | ((uint64_t)(sbo >> 4) << 32);
}

__device__ __forceinline__ void stg128_cs(void* p, uint32_t a, uint32_t b, uint32_t c, uint32_t d) {
    asm volatile("st.global.cs.v4.u32 [%0], {%1,%2,%3,%4};\n" ::"l"(p), "r"(a), "r"(b), "r"(c), "r"(d) : "memory");
}
__device__ __forceinline__ uint32_t pack_bf16(float lo, float hi) {
    uint32_t r;
    asm("cvt.rn.bf16x2.f32 %0, %1, %2;\n" : "=r"(r) : "f"(hi), "f"(lo));
    return r;
}
__device__ __forceinline__ float bf_lo(uint32_t v) { return __uint_as_float(v << 16); }
__device__ __forceinline__ float bf_hi(uint32_t v) { return __uint_as_float(v & 0xffff0000u); }
__device__ __forceinline__ uint32_t bf2_mul(uint32_t a, uint32_t b) {
    uint32_t r;
    asm("mul.rn.bf16x2 %0, %1, %2;\n" : "=r"(r) : "r"(a), "r"(b));
    return r;
}
__device__ __forceinline__ uint32_t bf2_fma(uint32_t a, uint32_t b, uint32_t c) {
    uint32_t r;
    asm("fma.rn.bf16x2 %0, %1, %2, %3;\n" : "=r"(r) : "r"(a), "r"(b), "r"(c));
    return r;
}
__device__ __forceinline__ uint32_t bf2_add(uint32_t a, uint32_t b) {
    uint32_t r;
    asm("add.rn.bf16x2 %0, %1, %2;\n" : "=r"(r) : "r"(a), "r"(b));
    return r;
}
constexpr float KAPPA = 0.3292034911525734f;
constexpr float GELU_C = 2.423681954311584f;
constexpr float HSCALE = 1.0f / (2.0f * KAPPA);
__device__ __forceinline__ uint32_t acc_exp(float z) { return max(__float_as_uint(z) >> 23, 10u); }
__device__ __forceinline__ void sched_break(int zero) {
    asm volatile("{\n.reg .pred p;\nsetp.ne.s32 p, %0, 0;\nSB_LOOP:\n@p nanosleep.u32 1;\n@p bra SB_LOOP;\n}\n" ::"r"(zero));
}

#define ACCR8(d, o) "+r"(d[o + 0]), "+r"(d[o + 1]), "+r"(d[o + 2]), "+r"(d[o + 3]), "+r"(d[o + 4]), "+r"(d[o + 5]), "+r"(d[o + 6]), "+r"(d[o + 7])
__device__ __forceinline__ void mma_rs_n128(uint32_t (&d)[32], const uint32_t (&a)[4], uint64_t desc, int scale_d) {
    asm volatile(
        "{\n.reg .pred p;\nsetp.ne.b32 p, %37, 0;\n"
        "wgmma.mma_async.sync.aligned.m64n128k16.f16.f16.f16 "
        "{%0,%1,%2,%3,%4,%5,%6,%7,%8,%9,%10,%11,%12,%13,%14,%15,"
        "%16,%17,%18,%19,%20,%21,%22,%23,%24,%25,%26,%27,%28,%29,%30,%31},"
        "{%32,%33,%34,%35}, %36, p, 1, 1, 0;\n}\n"
        : ACCR8(d, 0), ACCR8(d, 8), ACCR8(d, 16), ACCR8(d, 24)
        : "r"(a[0]), "r"(a[1]), "r"(a[2]), "r"(a[3]), "l"(desc), "r"(scale_d));
}
__device__ __forceinline__ void mma_ss_n128(uint32_t (&d)[32], uint64_t da, uint64_t db) {
    asm volatile(
        "{\n.reg .pred p;\nsetp.ne.b32 p, %34, 0;\n"
        "wgmma.mma_async.sync.aligned.m64n128k16.f16.f16.f16 "
        "{%0,%1,%2,%3,%4,%5,%6,%7,%8,%9,%10,%11,%12,%13,%14,%15,"
        "%16,%17,%18,%19,%20,%21,%22,%23,%24,%25,%26,%27,%28,%29,%30,%31},"
        "%32, %33, p, 1, 1, 0, 0;\n}\n"
        : ACCR8(d, 0), ACCR8(d, 8), ACCR8(d, 16), ACCR8(d, 24)
        : "l"(da), "l"(db), "r"(1));
}
__device__ __forceinline__ uint32_t bf2_as_h2(uint32_t v) { return (v & 0x0fff0fffu) * 7u + v; }
__device__ __forceinline__ float h_lo(uint32_t v) {
    float r;
    asm("{\n.reg .b16 l, h;\nmov.b32 {l, h}, %1;\ncvt.f32.f16 %0, l;\n}\n" : "=f"(r) : "r"(v));
    return r;
}
__device__ __forceinline__ float h_hi(uint32_t v) {
    float r;
    asm("{\n.reg .b16 l, h;\nmov.b32 {l, h}, %1;\ncvt.f32.f16 %0, h;\n}\n" : "=f"(r) : "r"(v));
    return r;
}

__device__ __forceinline__ void mma_rs_n192(uint32_t (&d)[48], const uint4& a, uint64_t db, int scale_d) {
    asm volatile(
        "{\n.reg .pred p;\nsetp.ne.b32 p, %53, 0;\n"
        "wgmma.mma_async.sync.aligned.m64n192k16.f16.f16.f16 "
        "{%0,%1,%2,%3,%4,%5,%6,%7,%8,%9,%10,%11,%12,%13,%14,%15,"
        "%16,%17,%18,%19,%20,%21,%22,%23,%24,%25,%26,%27,%28,%29,%30,%31,"
        "%32,%33,%34,%35,%36,%37,%38,%39,%40,%41,%42,%43,%44,%45,%46,%47},"
        "{%48,%49,%50,%51}, %52, p, 1, 1, 0;\n}\n"
        : ACCR8(d, 0), ACCR8(d, 8), ACCR8(d, 16), ACCR8(d, 24), ACCR8(d, 32), ACCR8(d, 40)
        : "r"(a.x), "r"(a.y), "r"(a.z), "r"(a.w), "l"(db), "r"(scale_d));
}

__device__ __forceinline__ uint32_t pack_f16(float lo, float hi) {
    uint32_t r;
    asm("cvt.rn.f16x2.f32 %0, %1, %2;\n" : "=r"(r) : "f"(hi), "f"(lo));
    return r;
}

constexpr int P1_IMG = 900;
constexpr int P1_SLOT = LN_TILE / 2, P1_NST = 4;
constexpr int P1_X = 16 * C_DIM * 2;
constexpr int P1_OFF_X = P1_SLOT * P1_NST;
constexpr int P1_OFF_A = P1_OFF_X + 2 * P1_X;
constexpr int P1_OFF_BAR = P1_OFF_A + 3 * 2048;
constexpr int P1_OFF_TILE = P1_OFF_BAR + (2 * P1_NST + 3 + 2 + 3 + 2) * 8;
constexpr int P1_OFF_DW = P1_OFF_TILE + 64;
constexpr int P1_SMEM = P1_OFF_DW + C_DIM * 2;

__device__ __forceinline__ float rsqrt_fast(float x) {
    float r;
    asm("rsqrt.approx.ftz.f32 %0, %1;\n" : "=f"(r) : "f"(x));
    return r;
}
__device__ __forceinline__ float sum8(const uint32_t (&c)[4]) {
    const uint32_t u = bf2_add(bf2_add(c[0], c[1]), bf2_add(c[2], c[3]));
    return bf_lo(u) + bf_hi(u);
}
__device__ __forceinline__ void lds128(uint32_t (&v)[4], uint32_t a) {
    asm volatile("ld.shared.v4.u32 {%0,%1,%2,%3}, [%4];\n" : "=r"(v[0]), "=r"(v[1]), "=r"(v[2]), "=r"(v[3]) : "r"(a) : "memory");
}
template <class F>
__device__ __forceinline__ void ln_row(uint32_t (&v)[6][4], uint32_t sdw, F after_loads) {
    uint32_t c[4], s[4], d[4], nm;
#pragma unroll
    for (int i = 0; i < 6; i++) {
        lds128(d, sdw + i * 128);
        if (i == 0) {
#pragma unroll
            for (int k = 0; k < 4; k++) c[k] = bf2_mul(v[0][k], d[k]);
            const float p = sum8(c) * -0.125f;
            nm = pack_bf16(p, p);
        }
#pragma unroll
        for (int k = 0; k < 4; k++) {
            v[i][k] = bf2_fma(v[i][k], d[k], nm);
            s[k] = i ? bf2_add(v[i][k], s[k]) : v[i][k];
            c[k] = i ? bf2_fma(v[i][k], v[i][k], c[k]) : bf2_mul(v[i][k], v[i][k]);
        }
    }
    after_loads(c[0]);
    float m = fmaf(sum8(s), 1.0f / 48, -bf_lo(nm));
    float q = fmaf(-bf_lo(nm), fmaf(2.f, m, bf_lo(nm)), sum8(c) * (1.0f / 48));
#pragma unroll
    for (int o = 1; o < 8; o <<= 1) {
        m += __shfl_xor_sync(0xffffffffu, m, o);
        q += __shfl_xor_sync(0xffffffffu, q, o);
    }
    m *= 0.125f;
    const float r = KAPPA * rsqrt_fast(fmaxf(fmaf(-m, m, q * 0.125f), 0.f) + 1e-5f);
    const float e = (-bf_lo(nm) - m) * r * 0x1p-112f;
    const bool two = __any_sync(0xffffffffu, r < 0x1p-14f);
    const float r1 = r * (two ? 0x1p-56f : 0x1p-112f);
    uint32_t mul = pack_bf16(r1, r1), add = two ? 0u : pack_bf16(e, e);
#pragma unroll 1
    for (int it = !two; it < 2; it++) {
#pragma unroll
        for (int i = 0; i < 6; i++)
#pragma unroll
            for (int k = 0; k < 4; k++) v[i][k] = bf2_fma(v[i][k], mul, add);
        mul = 0x23802380u;
        add = pack_bf16(e, e);
    }
#pragma unroll
    for (int i = 0; i < 6; i++)
#pragma unroll
        for (int k = 0; k < 4; k++) v[i][k] = bf2_as_h2(v[i][k]);
}

__device__ __forceinline__ float gelu_s(float y) {
    float u = y * fmaf(y, y, GELU_C);
    float t;
    asm volatile("tanh.approx.f32 %0, %1;\n" : "=f"(t) : "f"(u));
    return fmaf(y, t, y);
}
__device__ __forceinline__ void p1_pack(int c, uint32_t (&p)[4], uint32_t (&dd)[4]) {
#pragma unroll
    for (int u = 0; u < 4; u++) {
        if ((c & 3) == 0) dd[u] = p[u];
        else {
            uint32_t n = dd[u];
            if ((c & 3) == 1) n = __byte_perm(n, 0, 0x2301);
            if ((c & 3) == 2) {
                dd[u] = __byte_perm(n >> 3, n >> 1, 0x6341);
                n = __byte_perm(n >> 3, n >> 1, 0x7250);
            }
            asm("lop3.b32 %0, %0, %1, 0x40074007, 0xd8;\n" : "+r"(p[u]) : "r"(n));
        }
    }
}
__device__ __forceinline__ void p1_store(int c, const uint32_t (&p)[4], uint8_t* hptr) {
    if (c & 3) stg128_cs(hptr + (c >> 2) * H_HALF + ((c & 3) - 1) * 512, p[0], p[1], p[2], p[3]);
}

template <bool GEN>
__device__ __forceinline__ void p1_epilogue(uint32_t (&acc)[32], float (&ssq)[2], uint32_t sc2, uint8_t* hp, int zero) {
    uint32_t sq[2], dd[4];
#pragma unroll
    for (int c = 0; c < 8; c++) {
        if (GEN) sched_break(zero);
        uint32_t p[4];
#pragma unroll
        for (int u = 0; u < 4; u++) {
            const uint32_t y = acc[8 * (c >> 1) + 2 * u + (c & 1)];
            if (GEN) {
                const float sc = c & 1 ? bf_hi(sc2) : bf_lo(sc2), fs = __uint_as_float(0x78000000u - __float_as_uint(sc));
                const float g0 = gelu_s(h_lo(y) * fs), g1 = gelu_s(h_hi(y) * fs);
                ssq[c & 1] = fmaf(g1, g1, fmaf(g0, g0, ssq[c & 1]));
                p[u] = pack_f16(g0 * sc, g1 * sc);
            } else {
                uint32_t g;
                asm("{\n.reg .b32 w;\n"
                    "fma.rn.f16x2 w, %1, %1, %2;\n"
                    "mul.rn.f16x2 w, w, %1;\n"
                    "tanh.approx.f16x2 w, w;\n"
                    "fma.rn.f16x2 %0, %1, w, %1;\n}\n" : "=r"(g) : "r"(y), "r"(0x40d940d9u));
                acc[8 * (c >> 1) + 2 * u + (c & 1)] = g;
                if (c < 2 && u == 0) asm("mul.rn.f16x2 %0, %1, %1;\n" : "=r"(sq[c & 1]) : "r"(g));
                else asm("fma.rn.f16x2 %0, %1, %1, %0;\n" : "+r"(sq[c & 1]) : "r"(g));
                if (c & 1) asm("{\n.reg .b16 l, h;\n.reg .b32 f;\nmov.b32 {l, h}, %2;\nmov.b32 f, {h, h};\nmul.rn.f16x2 %0, %1, f;\n}\n" : "=r"(p[u]) : "r"(g), "r"(sc2));
                else asm("{\n.reg .b16 l, h;\n.reg .b32 f;\nmov.b32 {l, h}, %2;\nmov.b32 f, {l, l};\nmul.rn.f16x2 %0, %1, f;\n}\n" : "=r"(p[u]) : "r"(g), "r"(sc2));
            }
        }
        p1_pack(c, p, dd);
        if (c & 3) {
#pragma unroll
            for (int u = 0; u < 4; u++) acc[4 * (c - 1 - (c >> 2)) + u] = p[u];
        }
        p1_store(c, p, hp);
    }
    if (!GEN) {
#pragma unroll
        for (int r = 0; r < 2; r++) ssq[r] += h_lo(sq[r]) + h_hi(sq[r]);
    }
}
__device__ __forceinline__ void p1_consumer(const uint32_t (&a)[24][4], uint32_t sc2, bool gen, uint32_t sbase, int wg, int nwg, int cb,
                                            int w, int lane, int zero) {
    const uint32_t bar_full = sbase + P1_OFF_BAR, bar_empty = bar_full + P1_NST * 8;
    const uint32_t empty_remote = mapa(bar_empty, lane & 1);
    const int g = lane >> 2, q = lane & 3, turn = wg + 1 == nwg ? 1 : wg + 2;
    float ssq[2] = {0.f, 0.f};
    uint32_t acc[32] = {};
    TSTAMP(0, 1);
    STAMPT(128, 4);
    STAMPT(256, 5);

    uint8_t* hp = reinterpret_cast<uint8_t*>(g_h) + ((cb * 2 + (w >> 1)) * H_STEP + (w & 1) * 1536) + g * 64 + (q ^ (g >> 1)) * 16;
    const uint64_t desc_base = make_desc(sbase, 16, 1024) | (1ull << 62);
    const uint64_t da = make_desc(sbase + P1_OFF_A + wg * 2048, 128, 256);
#pragma unroll 1
    for (int i = 0;; i++) {
        const int s0 = (i & 1) * 16, par = (i >> 1) & 1;
        const uint64_t d0 = desc_base + (uint64_t)((i & 1) * (LN_TILE / 16));
        TRACE(wg, i, 0);
        mbar_wait(bar_full + s0, par);
        bar_sync(1 + wg, 256);
        TRACE(wg, i, 1);
        uint32_t step, more;
        wg_fence();
#pragma unroll
        for (int k = 0; k < 24; k++) {
            if (k == 12) mbar_wait(bar_full + s0 + 8, par);
            const uint64_t db = d0 + (uint64_t)((k >> 2) * 1024 + (k & 3) * 2);
            if (k < 23) mma_rs_n128(acc, a[k], db, k ? 1 : zero);
            else mma_ss_n128(acc, da, db);
            if (k == 23) bar_arrive(turn, 256);
            if (k % 12 == 11) wg_commit();
        }
        asm volatile("ld.shared.v2.u32 {%0, %1}, [%2];\n" : "=r"(step), "=r"(more) : "r"(sbase + P1_OFF_TILE + (i & 3) * 16) : "memory");
        TRACE(wg, i, 2);
        wg_wait<1>();
        if (lane < 2) mbar_arrive_cluster(empty_remote + s0);
        hp += step;
        TRACE(wg, i, 3);
        wg_wait<0>();
        TRACE(wg, i, 4);
        if (lane < 2) mbar_arrive_cluster(empty_remote + s0 + 8);
        if (gen) p1_epilogue<true>(acc, ssq, sc2, hp, zero);
        else p1_epilogue<false>(acc, ssq, sc2, hp, zero);
        if (!more) break;
    }
    TSTAMP(0, 21);
    if (wg == 0) bar_sync(1, 256);
    uint32_t par;
    asm volatile("ld.shared.u32 %0, [%1];\n" : "=r"(par) : "r"(sbase + P1_OFF_TILE - 4) : "memory");
    float* sums = g_sums[par];
#pragma unroll
    for (int r = 0; r < 2; r++) {
        ssq[r] += __shfl_xor_sync(0xffffffffu, ssq[r], 1);
        ssq[r] += __shfl_xor_sync(0xffffffffu, ssq[r], 2);
        if (q == 0) atomicAdd(sums + cb * 64 + w * 16 + r * 8 + g, ssq[r]);
    }
}

__device__ __forceinline__ void p1_w2(const __nv_bfloat16* __restrict__ w2, const __nv_bfloat16* __restrict__ grn_b, int w, int lane) {
    const int gw = (blockIdx.x - 8 * NGRP) * 4 + w;
    float* sums = g_sums[__ldcg(&g_epoch) & 1] + HID;
    flag_wait<true>(&g_flag[40][1][0], 12);
    {
        const int col = gw % 6 * 64 + lane * 2;
        float bsum[2] = {0.f, 0.f}, asum[2] = {0.f, 0.f};
#pragma unroll 4
        for (int kk = 0; kk < 192; kk++) {
            const int k = gw / 6 * 192 + kk;
            const uint32_t v = *reinterpret_cast<const uint32_t*>(w2 + k * C_DIM + col);
            const float b = __bfloat162float(grn_b[k]), f = __uint_as_float(__ldcg(&g_ex[k]) << 23);
            bsum[0] = fmaf(b, bf_lo(v), bsum[0]);
            bsum[1] = fmaf(b, bf_hi(v), bsum[1]);
            asum[0] = fmaf(f, fabsf(bf_lo(v)), asum[0]);
            asum[1] = fmaf(f, fabsf(bf_hi(v)), asum[1]);
        }
#pragma unroll
        for (int j = 0; j < 2; j++) {
            atomicAdd(sums + col + j, bsum[j]);
            atomicAdd(sums + C_DIM + col + j, asum[j]);
        }
        __threadfence();
        __syncwarp();
        if (lane == 0) asm volatile("red.relaxed.gpu.global.add.u32 [%0], 1;\n" ::"l"(&g_flag[LN_RING + 2][0][0]) : "memory");
    }
    while (*(volatile unsigned*)&g_flag[P1_IMG % LN_RING][1][0] < 12 * (P1_IMG / LN_RING + 1)) {
        __nanosleep(2000);
        SAFE_BREAK
    }
    flag_wait<true>(&g_flag[LN_RING + 2][0][0], 48);
    float z = 0.f;
#pragma unroll
    for (int j = 0; j < C_DIM / 32; j++) z = fmaxf(z, __ldcg(sums + C_DIM + j * 32 + lane));
    const float sc = __uint_as_float((263u - acc_exp(__uint_as_float(__reduce_max_sync(0xffffffffu, __float_as_uint(z))))) << 23);
    const int np = gw % 6 * 64 + lane * 2;
#pragma unroll 2
    for (int cc = 0; cc < 24; cc++) {
        const int c = gw / 6 * 24 + cc;
        uint32_t v[8], o[2][4];
#pragma unroll
        for (int e = 0; e < 8; e++) v[e] = *reinterpret_cast<const uint32_t*>(w2 + (c * 8 + e) * C_DIM + perm32(np));
#pragma unroll
        for (int e = 0; e < 4; e++) {
            const uint2 t = __ldcg(reinterpret_cast<const uint2*>(g_ex) + c * 4 + e);
            const float f0 = __uint_as_float(t.x << 23), f1 = __uint_as_float(t.y << 23);
            o[0][e] = pack_f16(bf_lo(v[2 * e]) * f0 * sc, bf_lo(v[2 * e + 1]) * f1 * sc);
            o[1][e] = pack_f16(bf_hi(v[2 * e]) * f0 * sc, bf_hi(v[2 * e + 1]) * f1 * sc);
        }
#pragma unroll
        for (int j = 0; j < 2; j++)
            g_w2img[0][(((c >> 1) * 48 + (np >> 3)) * 2 + (c & 1)) * 8 + (np & 7) + j] = make_uint4(o[j][0], o[j][1], o[j][2], o[j][3]);
    }
    asm volatile("fence.proxy.async.global;\n" ::: "memory");
    __threadfence();
    __syncwarp();
    if (lane == 0) asm volatile("red.relaxed.gpu.global.add.u32 [%0], 1;\n" ::"l"(&g_img[0]) : "memory");
}

__global__ void __cluster_dims__(2, 1, 1) __launch_bounds__(512, 1)
pass1_kernel(const __grid_constant__ CUtensorMap wmap, const __nv_bfloat16* __restrict__ x, const __nv_bfloat16* __restrict__ dw,
             const __nv_bfloat16* __restrict__ w1, const __nv_bfloat16* __restrict__ w2, const __nv_bfloat16* __restrict__ grn_b, int zero) {
    extern __shared__ __align__(1024) uint8_t smem[];
    const uint32_t sbase = smem_u32(smem);
    const uint32_t bar_full = sbase + P1_OFF_BAR, bar_empty = bar_full + P1_NST * 8, bar_w = bar_empty + P1_NST * 8;
    const uint32_t bar_xfull = bar_w + 24, bar_raw = bar_xfull + 16, bar_done = bar_raw + 16;
    const int tid = threadIdx.x;
    const int warp = __shfl_sync(0xffffffffu, tid >> 5, 0), lane = tid & 31;
    const uint32_t rank = cluster_rank();
    const int cl = blockIdx.x >> 1;
    const bool small = cl >= 4 * NGRP;
    const int nwg = small ? 2 : 3, cb0 = small ? (blockIdx.x - 8 * NGRP) * 2 : (blockIdx.x & 7) * 3;
    uint8_t* const ring = reinterpret_cast<uint8_t*>(g_ln);
    const int ln0 = 2 + (blockIdx.x >> 2), items = blockIdx.x >= 128 ? -1 : small ? 1 : (NT128 - 1 - ln0) / LN_STEP + 1;

    TSTAMP(0, 0);
    TRACEW(110 + warp, 0);

    if (warp >= 12) {
        reg_dec<56>();
        asm volatile("barrier.cluster.arrive.relaxed.aligned;\n" ::: "memory");
        asm volatile("barrier.cluster.wait.aligned;\n" ::: "memory");
        {
            auto ring_row = [&](int p) {
                const int n = (p & 8) * 8 + (lane >> 3) * 8 + (p & 3) * 2 + (p >> 2 & 1);
                return n * 128 + (((lane ^ n) & 7) << 4);
            };
            const uint8_t* xsrc = reinterpret_cast<const uint8_t*>(x) + (size_t)(32 * 8 + blockIdx.x * 2 + (warp & 1)) * P1_X;
            const uint32_t xbar = bar_xfull + (warp & 1) * 8, xdst = sbase + P1_OFF_X + (warp & 1) * P1_X;
            const uint32_t sdw = sbase + P1_OFF_DW + (lane & 7) * 16;
            uint32_t src = xdst - P1_OFF_X + (lane >> 3) * (C_DIM * 2) + (lane & 7) * 16;
            int row0 = ring_row((blockIdx.x & 7) * 2 + (warp & 1)) ^ 288, slot = blockIdx.x >> 3, used = 0;
            auto next = [&]() {
                xsrc += (size_t)LN_STEP * 8 * P1_X;
                if (elect_one()) {
                    mbar_expect_tx(xbar, P1_X);
                    bulk_g2s(xdst, xsrc, P1_X, xbar);
                }
                __syncwarp();
            };
#pragma unroll 1
            for (int i = -1; i < items; i++) {
                if (warp == 14) TRACEW(128 + i, 0);
                const int last = i > 0 ? 3 : i ? 2 + (warp >> 1 & 1) : 1;
#pragma unroll 1
                for (int ps = i < 0 ? last - 4 : 0; ps <= last; ps += i < 0 ? 4 : 1) {
                    if (i < 0 && ps > 0) STAMPT(416, 6);
                    if (i < 0 && ps > 0) mbar_wait(bar_raw, 0);
                    if (i < 0 && ps > 0) STAMPT(416, 7);
                    if (ps == 0) {
                        if (used) flag_wait<false>(&g_flag[slot][1][0], used);
                        if (i && i + 1 < items && elect_one())
                            asm volatile("cp.async.bulk.prefetch.L2.global [%0], %1;\n" ::"l"(xsrc + (size_t)LN_STEP * 8 * P1_X), "r"(P1_X) : "memory");
                        if (i) mbar_wait(xbar, ~i & 1);
                        else mbar_wait(bar_raw + 8, 0);
                        if (warp == 14) TRACEW(128 + i, 1);
                    }
                    uint32_t v[6][4];
#pragma unroll
                    for (int j = 0; j < 6; j++) lds128(v[j], src + (ps & 3) * (4 * C_DIM * 2) + j * 128);
                    ln_row(v, sdw, [&](uint32_t dep) {
                        if (i == 0 && ps == 1 && lane < 2) mbar_arrive_cluster(mapa(bar_empty, lane) + (dep & zero));
                        if (ps == 3 && i > 0 && i + 1 < items && !__any_sync(0xffffffffu, dep & zero)) next();
                    });
                    uint8_t* dst = ring + (slot * LN_TILE + (ps & 1) * 4096 + (row0 ^ (ps & 2) * 144));
#pragma unroll
                    for (int j = 0; j < 6; j++)
                        asm volatile("{\n.reg .pred p;\nsetp.ge.s32 p, %5, 0;\n@p st.global.v4.u32 [%0], {%1,%2,%3,%4};\n}\n"
                                     ::"l"(dst + j * 16384), "r"(v[j][0]), "r"(v[j][1]), "r"(v[j][2]), "r"(v[j][3]), "r"(ps) : "memory");
                }
                if (warp == 14) TRACEW(128 + i, 2);
                asm volatile("fence.proxy.async.global;\nfence.acq_rel.cta;\n" ::: "memory");
                if (i < 0) {
                    bar_sync(4, 128);
                    if (warp < 14) break;
                    row0 ^= 288;
                    slot += 16;
                } else {
                    if (i) mbar_wait(bar_done, ~i & 1);
                    else {
                        src += P1_OFF_X;
                        slot = ln0;
                        row0 = ring_row((blockIdx.x & 3) * 4 + (warp & 1) * 2);
                    }
                    __syncwarp();
                    if (lane == 0) mbar_arrive(bar_done);
                    if ((slot += LN_STEP) >= LN_RING) { slot -= LN_RING; used += 12; }
                }
            }
            if ((warp < 14 || items < 0) && lane < 2) mbar_arrive_cluster(mapa(bar_empty, lane));
        }
        if (warp == 12) {
            int prev = 0, t = p1_tile(small ? 0 : cl >> 2, small), next = p1_tile(small ? 1 : (cl >> 2) + NGRP, small);
            const uint32_t rbase = mapa(sbase, lane & 1);
            int i = 0;
#pragma unroll 1
            for (; t < NT128; i++) {
                const int s0 = (i & 1) * 2, par = (i >> 1) & 1;
                const int round = t / LN_RING, slot = t - round * LN_RING;
                const uint8_t* src = ring + slot * LN_TILE + rank * (P1_SLOT / 2);
                int draw = i + 2;
                if (rank == 0 && lane == 0 && !small) draw = 2 * NGRP + atomicAdd(&g_flag[LN_RING + ((cl >> 1) & 1)][cl & 1][0], 1u);
                flag_wait<true>(&g_flag[slot][0][0], 8 * round + 8);
                TRACEW(i, 2);
                if (i == 0) STAMPT(384, 10);
                if (i == 2) STAMPT(384, 13);
                if (i == 3) STAMPT(384, 14);
                asm volatile("fence.proxy.async.global;\n" ::: "memory");
                draw = p1_tile(__shfl_sync(0xffffffffu, draw, 0), small);
#pragma unroll
                for (int h = 0; h < 2; h++) {
                    mbar_wait(bar_empty + (s0 + h) * 8, par);
                    TRACEW(i, 4 + h);
                    if (i == 0 && h == 1) STAMPT(384, 11);
                    if (elect_one()) {
                        mbar_expect_tx(bar_full + (s0 + h) * 8, P1_SLOT + 16 - 16 * h);
                        bulk_g2s_mc(sbase + (s0 + h) * P1_SLOT + rank * (P1_SLOT / 2), src + h * P1_SLOT, P1_SLOT / 2, bar_full + (s0 + h) * 8, (uint16_t)3);
                    }
                    __syncwarp();
                    if (h == 0 && rank == 0 && lane < 2)
                        asm volatile("st.async.shared::cluster.mbarrier::complete_tx::bytes.v4.u32 [%0], {%1, %2, %3, %3}, [%4];\n"
                                     ::"r"(rbase + P1_OFF_TILE + (i & 3) * 16), "r"((t - prev) * (2 * H_TILE)), "r"((int)(next < NT128)), "r"(draw),
                                       "r"(rbase + P1_OFF_BAR + s0 * 8) : "memory");
                }
                prev = t;
                t = next;
                next = draw;
                if (rank != 0) {
                    mbar_wait(bar_full + s0 * 8, (i >> 1) & 1);
                    mbar_wait(bar_full + s0 * 8 + 8, (i >> 1) & 1);
                    if (lane == 0) asm volatile("red.relaxed.gpu.global.add.u32 [%0], %1;\n" ::"l"(&g_flag[slot][1][0]), "r"(nwg) : "memory");
                    asm volatile("ld.shared.u32 %0, [%1];\n" : "=r"(next) : "r"(sbase + P1_OFF_TILE + (i & 3) * 16 + 8) : "memory");
                    TRACEW(i, 3);
                }
            }
#pragma unroll 1
            for (int j = 2 * i; j < 2 * i + 4; j++) mbar_wait(bar_empty + (j & 3) * 8, (j >> 2) & 1);
        } else if (warp == 13) {
            STAMPT(416, 8);
            if (lane == 0 && blockIdx.x < 128) asm volatile("red.release.gpu.global.add.u32 [%0], 1;\n" ::"l"(&g_flag[blockIdx.x >> 3][0][0]) : "memory");
            __syncwarp();
            STAMPT(416, 9);
            const uint32_t ep = g_epoch & 1;
            asm volatile("st.shared.u32 [%0], %1;\n" ::"r"(sbase + P1_OFF_TILE - 4), "r"(ep) : "memory");
            if (blockIdx.x == 18) g_par = ep;
            if (blockIdx.x < 18) reinterpret_cast<float4*>(g_sums[ep ^ 1])[blockIdx.x * 32 + lane] = make_float4(0.f, 0.f, 0.f, 0.f);
#pragma unroll 1
            for (int i = 0; i < items; i++) {
                mbar_wait(bar_done, i & 1);
                asm volatile("fence.proxy.async.global;\n" ::: "memory");
                if (lane == 0) {
                    mbar_arrive(bar_done);
                    asm volatile("red.release.gpu.global.add.u32 [%0], %1;\n"
                                 ::"l"(&g_flag[i ? (ln0 + (i & 1) * LN_STEP) % LN_RING : 16 + (blockIdx.x >> 3)][0][0]), "r"(i ? 2 : 1) : "memory");
                }
                __syncwarp();
                TRACEW(128 + i, 3);
            }
            flag_wait<true>(&g_flag[LN_RING + 2][0][0], 48);
        }
    } else {
        if (tid == 0) {
            mbar_init(bar_raw, 1);
            mbar_init(bar_raw + 8, 1);
            mbar_init(bar_xfull, 1);
            mbar_init(bar_xfull + 8, 1);
            for (int i = 0; i < 3; i++) mbar_init(bar_w + i * 8, 1);
            asm volatile("fence.mbarrier_init.release.cluster;\n" ::: "memory");
            if (blockIdx.x < 128) {
                mbar_expect_tx(bar_raw, P1_X + C_DIM * 2);
                bulk_g2s(sbase + P1_OFF_DW, dw, C_DIM * 2, bar_raw);
                for (int i = 0; i < 2; i++) bulk_g2s(sbase + i * P1_X + P1_X / 2, x + (size_t)(blockIdx.x * 16 + i * 8) * C_DIM, P1_X / 2, bar_raw);
                asm volatile("cp.async.bulk.prefetch.L2.global [%0], 9216;\n" ::"l"(w1 + blockIdx.x * 4608) : "memory");
                mbar_expect_tx(bar_raw + 8, P1_X);
                for (int i = 0; i < 2; i++) bulk_g2s(sbase + i * P1_X, x + (size_t)(16 * 128 + blockIdx.x * 16 + i * 8) * C_DIM, P1_X / 2, bar_raw + 8);
            }
            for (int i = 0; i < nwg; i++) {
                mbar_expect_tx(bar_w + i * 8, P1_SLOT);
                tma2(sbase + (1 + i) * P1_SLOT, &wmap, (cb0 + i) * 64, 0, bar_w + i * 8);
                tma2(sbase + (1 + i) * P1_SLOT + P1_SLOT / 2, &wmap, (cb0 + i) * 64, 192, bar_w + i * 8);
            }
            for (int i = 0; i < 2 && !small; i++) {
                mbar_expect_tx(bar_xfull + i * 8, P1_X);
                bulk_g2s(sbase + P1_OFF_X + i * P1_X, x + (size_t)(32 * 128 + blockIdx.x * 32 + i * 16) * C_DIM, P1_X, bar_xfull + i * 8);
            }
        }
        if (tid == 32) {
            mbar_init(bar_done, 3);
            mbar_arrive(bar_done);
            asm volatile("fence.mbarrier_init.release.cluster;\n" ::: "memory");
        }
        if (tid == 64) {
            for (int i = 0; i < P1_NST; i++) {
                mbar_init(bar_full + i * 8, 1);
                mbar_init(bar_empty + i * 8, 8 * nwg);
            }
            asm volatile("fence.mbarrier_init.release.cluster;\n" ::: "memory");
            if (blockIdx.x < 64) (&g_half[0][0])[blockIdx.x] = 0;
            else if (blockIdx.x == 64) g_prog = 0;
            else if (blockIdx.x < 67) g_img[blockIdx.x - 65] = 0;
        }
        __syncwarp();
        asm volatile("barrier.cluster.arrive.relaxed.aligned;\n" ::: "memory");
        reg_inc<152>();
        TRACEW(110 + warp, 1);
        const int wg = warp >> 2, w = warp & 3;
        gdc_launch();
        asm volatile("barrier.cluster.wait.aligned;\n" ::: "memory");
        if (wg == nwg) {
            p1_w2(w2, grn_b, w, lane);
            return;
        }
        const uint32_t slot_free = mapa(bar_empty, lane & 1) + (lane >> 1) * 8;
        if (lane < 8 && (lane >> 1) != 1 + wg && (wg || lane > 1)) mbar_arrive_cluster(slot_free);
        if (wg == 1) bar_arrive(1, 256);
        uint32_t a[24][4], ex[2], gen = 0;
        const uint32_t wsrc = sbase + (1 + wg) * P1_SLOT + ((lane >> 4) * 8 + (lane & 7)) * 128 + (((2 * w + ((lane >> 3) & 1)) ^ (lane & 7)) << 4);
#pragma unroll 1
        for (int it = 0; it < 2; it++) {
            if (it) mbar_wait(bar_w + wg * 8, 0);
            TRACEW(110 + warp, 5);
            if (it || wg == 0) {
#pragma unroll
            for (int k = 0; k < 24; k++) ldsm4t(a[k], wsrc + k * 2048);
#pragma unroll
            for (int r = 0; r < 2; r++) {
                float t = 0.f;
#pragma unroll
                for (int j = 0; j < 6; j++) {
                    uint32_t c = bf2_mul(a[4 * j][r], a[4 * j][r]);
#pragma unroll
                    for (int k = 1; k < 8; k++) c = bf2_fma(a[4 * j + k / 2][r + (k & 1) * 2], a[4 * j + k / 2][r + (k & 1) * 2], c);
                    t += bf_lo(c) + bf_hi(c);
                }
                t += __shfl_xor_sync(0xffffffffu, t, 1);
                t += __shfl_xor_sync(0xffffffffu, t, 2);
                asm("sqrt.approx.f32 %0, %0;\n" : "+f"(t));
                ex[r] = min(max(__float_as_uint(13.9f * t) >> 23, 72u), 198u);
            }
            asm volatile("{\n.reg .pred p;\nsetp.gt.u32 p, %1, 7;\nbar.red.or.pred p, %2, 128, p;\nselp.u32 %0, 1, 0, p;\n}\n"
                         : "=r"(gen) : "r"(max(ex[0] - 125u, ex[1] - 125u)), "r"(5 + wg) : "memory");
            gen = __shfl_sync(0xffffffffu, gen, 0) & it;
            if (it) {
                if ((lane & 3) < 2) g_ex[(cb0 + wg) * 64 + w * 16 + (lane & 1) * 8 + (lane >> 2)] = lane & 1 ? ex[1] : ex[0];
                if ((lane >> 1) == 1 + wg) mbar_arrive_cluster(slot_free);
                __syncwarp();
            }
            }
            if (gen) {
#pragma unroll
                for (int k = 0; k < 24; k++)
#pragma unroll
                    for (int j = 0; j < 4; j++) a[k][j] = bf2_mul(a[k][j], (268u - ex[j & 1]) * 0x00800080u);
            }
            if (it || wg == 1) {
#pragma unroll
                for (int k = 0; k < 24; k++)
#pragma unroll
                    for (int j = 0; j < 4; j++) {
                        a[k][j] = bf2_as_h2(bf2_mul(a[k][j], 0x07800780u));
                        asm volatile("" : "+r"(a[k][j]));
                    }
            }
            TRACEW(110 + warp, 6);
        }
#pragma unroll
        for (int j = 0; j < 4; j++)
            asm volatile("st.shared.u32 [%0], %1;\n" ::"r"(sbase + P1_OFF_A + warp * 512 + (j & 1) * 256 + (j >> 1) * 128 + lane * 4), "r"(a[23][j]) : "memory");
        asm volatile("fence.proxy.async.shared::cta;\n" ::: "memory");
        TRACEW(110 + warp, 7);
        const uint32_t ex2 = ex[0] | ex[1] << 16;
        p1_consumer(a, gen ? 0x7f007f00u - (ex2 << 7) : (0x008e008eu - ex2) << 10, gen, sbase, wg, nwg, cb0 + wg, w, lane, zero);
        TSTAMP(0, 30);
    }
}

constexpr int P2_B = 24576, P2_NB = 5;
constexpr int P2_A = 3072, P2_NA = 5;
constexpr int P2_XROW = C_DIM * 2;
constexpr int P2_OFF_A = P2_B * P2_NB;
constexpr int P2_OFF_X = P2_OFF_A + 3 * P2_NA * P2_A;
constexpr int P2_XHALF = 32 * P2_XROW + 64;
constexpr int P2_OFF_BIAS = P2_OFF_X + 64 * P2_XROW + 64;
constexpr int P2_OFF_GRN = P2_OFF_BIAS + C_DIM * 4;
constexpr int P2_OFF_RED = P2_OFF_GRN + HID * 2;
constexpr int P2_OFF_BAR = P2_OFF_RED + 192;
constexpr int P2_SMEM = P2_OFF_BAR + (2 * P2_NB + 6 * P2_NA + 3) * 8;
constexpr int P2_LAG = 17;
constexpr int P2_NCL = NUM_CTAS / 2, P2_ITEMS = NT128 / P2_NCL, P2_SHARED = NT128 - P2_ITEMS * P2_NCL;
constexpr int P2_POS = P2_LAG * (P2_ITEMS - 1) + 48;
__device__ __forceinline__ int p2_start(int n) { return n < 0 ? 0 : n == P2_ITEMS ? P2_POS - 24 : P2_LAG * n; }
constexpr int P2_FOLD = 17;
constexpr int P2_XC = 8 * P2_XROW;
constexpr int P2_DELTA = 7;
__device__ __forceinline__ int p2_tile(int cl, int n) {
    return n == 0 ? NT128 - 1 - cl : n < 0 || n == P2_ITEMS ? NT128 - 1 - P2_NCL - (cl >> 1) : cl + P2_NCL * (n - 1);
}

constexpr int P2_EG = 2;
__device__ __forceinline__ void p2_init(uint32_t (&acc)[48], int c, uint32_t sb) {
#pragma unroll
    for (int i = 8 * (c % 6); i < 8 * (c % 6) + 8; i += 4)
        asm volatile("ld.shared.v4.u32 {%0,%1,%2,%3}, [%4];\n" : "=r"(acc[i]), "=r"(acc[i + 1]), "=r"(acc[i + 2]), "=r"(acc[i + 3])
                     : "r"(sb + c * 128 + i % 8 * 4) : "memory");
}
__device__ __forceinline__ void p2_epilogue(uint32_t (&acc0)[48], uint32_t (&acc1)[48], uint32_t sx, uint32_t sb, uint32_t up, int zero) {
    uint32_t v[2][P2_EG][4];
    auto load = [&](int c, uint32_t a) {
#pragma unroll
        for (int j = 0; j < P2_EG; j++) {
            const int u = c * P2_EG + j;
            asm volatile("ld.shared.v4.u32 {%0,%1,%2,%3}, [%4];\n" : "=r"(v[c & 1][j][0]), "=r"(v[c & 1][j][1]), "=r"(v[c & 1][j][2]), "=r"(v[c & 1][j][3])
                         : "r"(a + (u >> 1) * 64 + (u & 1) * 4 * P2_XROW) : "memory");
        }
    };
    load(0, sx);
#pragma unroll
    for (int c = 0; c < 24 / P2_EG; c++) {
        if (c + 1 < 24 / P2_EG) load(c + 1, sx + (v[c & 1][P2_EG - 1][0] & zero));
#pragma unroll
        for (int j = 0; j < P2_EG; j++) {
            const int u = c * P2_EG + j, i = 8 * ((u >> 1) % 6) + (u & 1);
            const uint32_t (&acc)[48] = u < 12 ? acc0 : acc1;
            uint32_t (&w)[4] = v[c & 1][j];
#pragma unroll
            for (int e = 0; e < 4; e++)
                w[e] = bf2_fma(pack_bf16(h_lo(acc[i + 2 * e]), h_hi(acc[i + 2 * e])), up, w[e]);
            asm volatile("st.shared.v4.u32 [%4], {%0,%1,%2,%3};\n" ::"r"(w[0]), "r"(w[1]), "r"(w[2]), "r"(w[3]),
                         "r"(sx + (u >> 1) * 64 + (u & 1) * 4 * P2_XROW) : "memory");
        }
        p2_init(c < 6 ? acc0 : acc1, c, sb + (v[c & 1][1][0] & zero));
    }
}

__device__ __forceinline__ void p2_unpack(uint4& u, uint32_t o1, uint32_t o2, uint32_t o3) {
    u.z = o1 & 0xbff8bff8u;
    u.y = o2 & 0xbff8bff8u;
    u.w = o3 & 0xbff8bff8u;
    u.x = (__byte_perm(o1, 0, 0x2301) & 0x07400740u) | ((__byte_perm(o2, o3, 0x6240) << 3) & 0x38383838u) | ((__byte_perm(o2, o3, 0x3715) << 1) & 0x80808080u);
}
__device__ __forceinline__ uint32_t h2_mul(uint32_t a, uint32_t b) {
    uint32_t r;
    asm("mul.rn.f16x2 %0, %1, %2;\n" : "=r"(r) : "r"(a), "r"(b));
    return r;
}
__device__ __forceinline__ void p2_epilogue_add(const uint32_t (&acc)[48], uint8_t* o, uint32_t up, int zero) {
#pragma unroll
    for (int t = 0; t < 12; t++) {
        uint32_t v[4];
#pragma unroll
        for (int e = 0; e < 4; e++) {
            v[e] = acc[8 * (t >> 1) + (t & 1) + 2 * e];
            asm volatile("" : "+r"(v[e]));
            v[e] = bf2_mul(pack_bf16(h_lo(v[e]), h_hi(v[e])), up);
        }
        asm volatile("red.global.add.noftz.v4.bf16x2 [%0], {%1,%2,%3,%4};\n" ::"l"(o + (t >> 1) * 64 + (t & 1) * 4 * P2_XROW),
                     "r"(v[0]), "r"(v[1]), "r"(v[2]), "r"(v[3]) : "memory");
        if (t % 3 == 2) sched_break(zero);
    }
}

__global__ void __cluster_dims__(2, 1, 1) __launch_bounds__(512, 1)
pass2_kernel(const __nv_bfloat16* __restrict__ x, const __nv_bfloat16* __restrict__ grn_g, __nv_bfloat16* __restrict__ out, int zero) {
    extern __shared__ __align__(1024) uint8_t smem[];
    const uint32_t sbase = smem_u32(smem);
    const uint32_t bar_bfull = sbase + P2_OFF_BAR, bar_bempty = bar_bfull + P2_NB * 8;
    const uint32_t bar_afull = bar_bempty + P2_NB * 8, bar_aempty = bar_afull + 3 * P2_NA * 8;
    const uint32_t bar_xfull = bar_aempty + 3 * P2_NA * 8, bar_oready = bar_xfull + 8, s_pos = bar_xfull + 16;
    int tid;
    asm volatile("mov.u32 %0, %%tid.x;\n" : "=r"(tid));
    const int warp = __shfl_sync(0xffffffffu, tid >> 5, 0), lane = tid & 31;
    const uint32_t rank = cluster_rank();
    const int cl = blockIdx.x >> 1, pair = cl >> 1;
    const int k0 = (4 * pair + (cl & 1) * (48 - P2_POS % 48)) % 48;
    const int head = pair < P2_SHARED && !(cl & 1), tail = pair < P2_SHARED && (cl & 1);

    uint32_t par, gg[4];
    float pre[4];
    if (warp < 12) {
        asm volatile("ld.global.cg.u32 %0, [%1];\n" : "=r"(par) : "l"(&g_par) : "memory");
#pragma unroll
        for (int i = 0; i < 4; i++) {
            asm volatile("ld.global.cg.f32 %0, [%1];\n" : "=f"(pre[i]) : "l"(&g_sums[i & 1][HID + (i >> 1) * C_DIM + tid]) : "memory");
            asm volatile("ld.global.nc.u16 %0, [%1];\n" : "=r"(gg[i]) : "l"(grn_g + tid + 384 * i) : "memory");
        }
    }
    TSTAMP(1, 0);
    if (tid == 384) {
        for (int i = 0; i < P2_NB; i++) {
            mbar_init(bar_bfull + i * 8, 1);
            mbar_init(bar_bempty + i * 8, 24);
        }
        for (int i = 0; i < 3 * P2_NA; i++) {
            mbar_init(bar_afull + i * 8, 1);
            mbar_init(bar_aempty + i * 8, 4);
        }
        mbar_init(bar_xfull, 2);
        mbar_init(bar_oready, 4);
        asm volatile("st.shared.u32 [%0], 0;\n" ::"r"(s_pos) : "memory");
        asm volatile("fence.mbarrier_init.release.cluster;\n" ::: "memory");
    }
    __syncthreads();
    cluster_sync_relaxed();

    if (warp >= 12) {
        reg_dec<32>();
        if (warp == 12) {
            const uint8_t* wsrc = reinterpret_cast<const uint8_t*>(g_w2img) + rank * (P2_B / 2);
            int st = 0, ph = 1, kb = k0, m = 0, r = 0;
            const int busy = head ? 0 : tail ? P2_POS - 24 : P2_POS;
#pragma unroll 1
            for (int p = 0; p < P2_POS; p++) {
                if (p == 0 || p == P2_FOLD) {
                    flag_wait<true>(&g_img[p != 0], p ? 96 * 4 : 48);
                    asm volatile("fence.proxy.async.global;\n" ::: "memory");
                    if (p) wsrc += sizeof(g_w2img[0]);
                }
                mbar_wait(bar_bempty + st * 8, ph);
                TR2P(p, 0);
                if (elect_one()) {
                    mbar_expect_tx(bar_bfull + st * 8, P2_B);
                    bulk_g2s_mc(sbase + st * P2_B + rank * (P2_B / 2), wsrc + kb * P2_B, P2_B / 2, bar_bfull + st * 8, (uint16_t)3);
                    asm volatile("st.volatile.shared.u32 [%0], %1;\n" ::"r"(s_pos), "r"(p) : "memory");
                    const int idle = 2 - min(m, P2_ITEMS - 1) + max(m - 2 + (r >= 48 - 2 * P2_LAG), 0) - ((unsigned)(p - busy) < 24);
                    if (idle) asm volatile("mbarrier.arrive.shared::cta.b64 _, [%0], %1;\n" ::"r"(bar_bempty + st * 8), "r"(idle * 8) : "memory");
                    if (rank == 0) asm volatile("red.relaxed.gpu.global.add.u32 [%0], 1;\n" ::"l"(&g_prog) : "memory");
                }
                __syncwarp();
                if (++st == P2_NB) { st = 0; ph ^= 1; }
                if (++kb == 48) kb = 0;
                if (++r == P2_LAG) { r = 0; m++; }
            }
            mbar_wait(bar_bempty + st * 8, ph);
            if (lane == 0) mbar_arrive(bar_bfull + st * 8);
#pragma unroll 1
            for (int p = 1; p < P2_NB; p++) {
                if (++st == P2_NB) { st = 0; ph ^= 1; }
                mbar_wait(bar_bempty + st * 8, ph);
            }
        } else if (warp == 13) {
            const uint8_t* src[3];
            int n[3], left[3], wrap[3];
            uint32_t st[3];
            auto item = [&](int w) {
                const int u = (k0 + p2_start(n[w])) % 48;
                left[w] = n[w] < 0 || n[w] == P2_ITEMS ? 24 : 48;
                wrap[w] = left[w] - (48 - u);
                src[w] = reinterpret_cast<const uint8_t*>(g_h) + (size_t)p2_tile(cl, n[w]) * (2 * H_TILE) + rank * H_HALF + u * H_STEP;
            };
#pragma unroll
            for (int w = 0; w < 3; w++) {
                n[w] = w == 2 && head ? -1 : w;
                st[w] = 0x80000000u;
                item(w);
            }
            gdc_wait();
#pragma unroll 1
            for (int done = 0; done < 3;) {
                bool idle = true;
#pragma unroll
                for (int w = 0; w < 3; w++) {
                    const uint32_t o = (st[w] & 0xff) + w * P2_NA * 8;
                    if (left[w] >= 0 && mbar_test(bar_aempty + o, st[w] >> 31)) {
                        idle = false;
                        if (left[w] == 0) {
                            if (lane == 0) mbar_arrive(bar_afull + o);
                            left[w] = -1;
                            done++;
                        } else {
                            if (elect_one()) {
                                mbar_expect_tx(bar_afull + o, P2_A);
                                bulk_g2s(sbase + P2_OFF_A + o * (P2_A / 8), src[w], P2_A, bar_afull + o);
                            }
                            __syncwarp();
                            src[w] += H_STEP;
                            st[w] += 8;
                            if ((st[w] & 0xff) == P2_NA * 8) st[w] ^= 0x80000000u | (P2_NA * 8);
                            if (--left[w] == wrap[w]) src[w] -= 48 * H_STEP;
                            if (left[w] == 0 && (n[w] += 3) < P2_ITEMS + tail) item(w);
                        }
                    }
                }
                if (idle) __nanosleep(64);
                SAFE_BREAK
            }
        } else if (warp == 14) {
            const uint32_t sx = sbase + P2_OFF_X;
            size_t o = 0;
            auto pace = [&](int target) {
                int v;
                while (true) {
                    asm volatile("ld.volatile.shared.u32 %0, [%1];\n" : "=r"(v) : "r"(s_pos) : "memory");
                    if (v * 16 >= target) break;
                    __nanosleep(100);
                    SAFE_BREAK
                }
            };
#pragma unroll 1
            for (int n = -head; n <= P2_ITEMS; n++) {
                const size_t on = (size_t)(2 * p2_tile(cl, n) + rank) * (64 * C_DIM * 2);
                const bool st = n + head > 0, ld = n < P2_ITEMS;
                if (st) mbar_wait(bar_oready, (n - 1 + head) & 1);
                TR2P(n + 1, 1);
                if (lane == 0) {
                    if (n == 1 && head) {
                        asm volatile("cp.async.bulk.wait_group 0;\nfence.proxy.async.global;\n" ::: "memory");
                        asm volatile("st.release.gpu.global.u32 [%0], 1;\n" ::"l"(&g_half[pair][rank]) : "memory");
                    }
                    if (ld) mbar_expect_tx(bar_xfull, 64 * C_DIM * 2);
                    const bool paced = st && n < P2_ITEMS - 1;
                    int t = (P2_LAG * (n - 1) + 52) * 16;
#pragma unroll 1
                    for (int c = 0; st && c < 64 * P2_XROW; c += P2_XC) {
                        if (paced) pace(t += 11);
                        bulk_s2g(reinterpret_cast<uint8_t*>(out) + o + c, sx + c + (c >= 32 * P2_XROW ? 64 : 0), P2_XC);
                        asm volatile("cp.async.bulk.commit_group;\n" ::: "memory");
                    }
#pragma unroll 1
                    for (int c = 0; ld && c < 64 * P2_XROW; c += P2_XC) {
                        if (c == 0) asm volatile("cp.async.bulk.wait_group.read 4;\n" ::: "memory");
                        if (c == 32 * P2_XROW) asm volatile("cp.async.bulk.wait_group.read 0;\n" ::: "memory");
                        if (paced) pace(t += 11);
                        bulk_g2s(sx + c + (c >= 32 * P2_XROW ? 64 : 0), reinterpret_cast<const uint8_t*>(x) + on + c, P2_XC, bar_xfull);
                    }
                    TR2P(n + 1, 2);
                    if (rank == 0 && n > 0 && n < P2_ITEMS - 2)
                        flag_wait<false>(&g_prog, P2_NCL * (P2_LAG * n + 48) + (tail ? P2_SHARED - P2_NCL : P2_SHARED) * P2_DELTA);
                    if (ld) mbar_arrive(bar_xfull);
                    TR2P(n + 1, 3);
                }
                __syncwarp();
                o = on;
            }
            asm volatile("cp.async.bulk.wait_group 0;\n" ::: "memory");
            TR2P(30, 1);
        }
    } else {
        reg_inc<160>();
        const int wg = warp >> 2, w = warp & 3, g = lane >> 2, q = lane & 3;
        const uint32_t sx = sbase + P2_OFF_X + (g & 1) * P2_XHALF + (w * 8 + (g >> 1)) * P2_XROW + q * 16;
        const uint32_t af = bar_afull + wg * P2_NA * 8;
        const uint32_t s_a = sbase + P2_OFF_A + wg * P2_NA * P2_A + (lane >> 3) * 512 + (lane & 7) * 64 +
                             ((w ^ ((lane & 7) >> 1)) << 4);
        uint32_t acc0[48], acc1[48];
        uint32_t up;
        uint4 a0[2], a1[2];
        uint32_t st = 0, ph = 0;

        {
            float4* s_red = reinterpret_cast<float4*>(smem + P2_OFF_RED);
            const float* sums = g_sums[par];
            float gx[4], part = 0.f, mx = 0.f;
            TSTAMP(1, 27);
            gdc_wait();
            TSTAMP(1, 1);
#pragma unroll
            for (int i = 0; i < 4; i++) gx[i] = __ldcg(sums + tid + 384 * i);
            if (blockIdx.x == 120 && tid < (LN_RING + 3) * 2) (&g_flag[0][0][0])[tid * 8] = 0;
            if (blockIdx.x == 121 && tid == 0) atomicAdd(&g_epoch, 1u);
            const float bias = pre[0] + pre[1];
            float z = __uint_as_float(__reduce_max_sync(0xffffffffu, __float_as_uint(pre[2] + pre[3])));
            uint32_t bm = __reduce_max_sync(0xffffffffu, __float_as_uint(fabsf(bias)));
#pragma unroll
            for (int i = 0; i < 4; i++) {
                asm("sqrt.approx.f32 %0, %1;\n" : "=f"(gx[i]) : "f"(fmaf(gx[i], HSCALE * HSCALE, 1e-6f)));
                part += gx[i];
                gx[i] *= bf_lo(gg[i]);
                mx = fmaxf(mx, fabsf(gx[i]));
            }
#pragma unroll
            for (int o = 16; o > 0; o >>= 1) part += __shfl_xor_sync(0xffffffffu, part, o);
            mx = __uint_as_float(__reduce_max_sync(0xffffffffu, __float_as_uint(mx)));
            TSTAMP(1, 26);
            if (lane == 0) s_red[warp] = make_float4(part, mx, z, __uint_as_float(bm));
            bar_sync(1, 384);
            float tot = 0.f;
            {
                const float4 t = s_red[min(lane & 15, 11)];
                tot = (lane & 15) < 12 ? t.x : 0.f;
#pragma unroll
                for (int o = 8; o > 0; o >>= 1) tot += __shfl_xor_sync(0xffffffffu, tot, o);
                mx = __uint_as_float(__reduce_max_sync(0xffffffffu, __float_as_uint(t.y)));
                z = __uint_as_float(__reduce_max_sync(0xffffffffu, __float_as_uint(t.z)));
                bm = __reduce_max_sync(0xffffffffu, __float_as_uint(t.w));
            }
            const float inv = __fdividef(1.0f, fmaf(tot, 1.0f / HID, 1e-6f));
            const uint32_t e0 = acc_exp(z) - 9u;
            const uint32_t j = min(max(max(__float_as_uint(fmaf(mx, inv, 1.0f) * 1.01f) >> 23, 130u) - 130u, max(bm >> 23, e0 + 12u) - (e0 + 12u)), 126u);
            const float dn = __uint_as_float((127u - j) << 23) * (HSCALE * 1.00235f);
#pragma unroll
            for (int i = 0; i < 4; i++)
                *reinterpret_cast<uint16_t*>(smem + P2_OFF_GRN + (tid + 384 * i) * 2) = pack_f16(fmaf(gx[i], inv, 1.0f) * dn, 0.f);
            const uint32_t e = min(e0 + j, 253u);
            up = e * 0x00800080u;
#pragma unroll
            for (int i = 0; i < 2; i++)
                *reinterpret_cast<uint16_t*>(smem + P2_OFF_BIAS + (tid >> 1) * 8 + i * 4 + (tid & 1) * 2) = pack_f16(bias * __uint_as_float((254u - e) << 23), 0.f);
            TSTAMP(1, 25);
            bar_sync(1, 384);
            if (wg == 1 && blockIdx.x < 96) {
                const uint4* src = g_w2img[0] + blockIdx.x * 768 + tid - 128;
                const uint4 fk = *reinterpret_cast<const uint4*>(smem + P2_OFF_GRN + blockIdx.x * 32 + (tid & 8) * 2);
                uint4 v[6];
#pragma unroll
                for (int i = 0; i < 6; i++) v[i] = __ldcg(src + i * 128);
                auto fold = [&](uint32_t b, uint32_t f) { return (h2_mul(b, f) + 0x00040004u) & 0xfff8fff8u; };
#pragma unroll
                for (int i = 0; i < 6; i++)
                    g_w2img[1][blockIdx.x * 768 + tid - 128 + i * 128] = make_uint4(fold(v[i].x, fk.x), fold(v[i].y, fk.y), fold(v[i].z, fk.z), fold(v[i].w, fk.w));
                asm volatile("fence.proxy.async.global;\n" ::: "memory");
                __threadfence();
                __syncwarp();
                if (lane == 0) asm volatile("red.release.gpu.global.add.u32 [%0], 1;\n" ::"l"(&g_img[1]) : "memory");
            }
        }
        TSTAMP(1, 28);
        int kt = k0, pos;
        const uint32_t be = lane < 2 ? mapa(bar_bempty, lane) : 0, be0 = mapa(bar_bempty, 0);
        uint32_t prev = 0, sa = 0, pa = 0;
        auto release_b = [&](uint32_t p, bool on) {
            asm volatile("{\n.reg .pred p, q;\nsetp.ne.u32 q, %2, 0;\nsetp.ne.and.u32 p, %1, 0, q;\n@p mbarrier.arrive.shared::cluster.b64 _, [%0];\n}\n"
                         ::"r"(be + p), "r"(be), "r"((uint32_t)on) : "memory");
        };
        auto arrive1 = [&](uint32_t bar) {
            asm volatile("{\n.reg .pred p;\nsetp.eq.u32 p, %1, %2;\n@p mbarrier.arrive.shared::cta.b64 _, [%0];\n}\n" ::"r"(bar), "r"(be), "r"(be0) : "memory");
        };
        auto seek = [&](int p) {
            pos = p;
            st = p % P2_NB * 8;
            ph = p / P2_NB & 1;
            int v;
            while (true) {
                asm volatile("ld.volatile.shared.u32 %0, [%1];\n" : "=r"(v) : "r"(s_pos) : "memory");
                if (__all_sync(0xffffffffu, v >= p)) break;
                __nanosleep(200);
                SAFE_BREAK
            }
        };
        bool ok_a = false;
        auto fetch = [&](uint4 (&a)[2], uint32_t done, bool rel, bool early) {
            if (!ok_a) mbar_wait(af + sa, pa);
            uint32_t o[6];
            const uint32_t src = s_a + sa * (P2_A / 8);
            asm volatile("ldmatrix.sync.aligned.m8n8.x4.trans.shared.b16 {%0,%1,%2,%3}, [%4];\n"
                         : "=r"(o[0]), "=r"(o[1]), "=r"(o[2]), "=r"(o[3]) : "r"(src) : "memory");
            asm volatile("ldmatrix.sync.aligned.m8n8.x2.trans.shared.b16 {%0,%1}, [%2];\n"
                         : "=r"(o[4]), "=r"(o[5]) : "r"(src + 2048) : "memory");
            if ((sa += 8) == P2_NA * 8) { sa = 0; pa ^= 1; }
            wg_wait<1>();
            release_b(done, rel);
            ok_a = mbar_test(af + sa, pa);
            const bool ok_b = mbar_test(bar_bfull + st, ph);
            p2_unpack(a[0], o[0], o[1], o[2]);
            p2_unpack(a[1], o[3], o[4], o[5]);
            if (early) {
                const uint32_t* t = reinterpret_cast<const uint32_t*>(smem + P2_OFF_GRN) + kt * 16 + q;
#pragma unroll
                for (int i = 0; i < 2; i++)
                    a[i] = make_uint4(h2_mul(a[i].x, t[8 * i]), h2_mul(a[i].y, t[8 * i]), h2_mul(a[i].z, t[8 * i + 4]), h2_mul(a[i].w, t[8 * i + 4]));
                if (++kt == 48) kt = 0;
            }
            if (!ok_b) mbar_wait(bar_bfull + st, ph);
        };
        const uint64_t db0 = make_desc(sbase, 128, 256);
        auto step = [&](const uint4 (&a)[2], uint4 (&an)[2], bool cont, bool add, bool early) {
            TR2(0);
            const uint64_t db = db0 + st * (P2_B / 128);
            wg_fence();
            mma_rs_n192(acc0, a[0], db, add);
            mma_rs_n192(acc1, a[0], db + 384, add);
            mma_rs_n192(acc0, a[1], db + 768, 1);
            mma_rs_n192(acc1, a[1], db + 768 + 384, 1);
            wg_commit();
            arrive1(af + 3 * P2_NA * 8 - 8 + (sa ? sa : P2_NA * 8));
            const uint32_t done = prev;
            prev = st;
            if ((st += 8) == P2_NB * 8) { st = 0; ph ^= 1; }
            fetch(an, done, cont, early);
            pos++;
        };
        int n = wg == 2 && head ? -1 : wg;
#pragma unroll
        for (int c = 0; c < 12; c++) p2_init(c < 6 ? acc0 : acc1, c, sbase + P2_OFF_BIAS + q * 32);
        seek(p2_start(n));
        fetch(a0, 0, false, n <= 0);
#pragma unroll 1
        for (;; n += 3) {
            TSTAMP(1, 2 + n);
            const int p0 = n < 0 || n == P2_ITEMS ? 12 : 0, pe = n <= 0 ? p0 + P2_FOLD / 2 : 0;
            const bool more = n + 3 < P2_ITEMS + tail;
#pragma unroll 1
            for (int p = p0; p < 24; p++) {
                step(a0, a1, p != p0, p != p0 || n != P2_ITEMS, p < pe);
                step(a1, a0, true, true, p < pe);
            }
            if (n == P2_ITEMS) {
                flag_wait<true>(&g_half[pair][rank], 1);
                TR2(1);
                wg_wait<0>();
                TR2(2);
                release_b(prev, true);
                uint8_t* o = reinterpret_cast<uint8_t*>(out) + (size_t)((2 * p2_tile(cl, -1) + rank) * 64 + (g & 1) * 32 + w * 8 + (g >> 1)) * P2_XROW + q * 16;
                p2_epilogue_add(acc0, o, up, zero);
                p2_epilogue_add(acc1, o + 384, up, zero);
                TR2(3);
                break;
            }
            mbar_wait(bar_xfull, (n + head) & 1);
            TR2(1);
            wg_wait<0>();
            TR2(2);
            release_b(prev, true);
            p2_epilogue(acc0, acc1, sx, sbase + P2_OFF_BIAS + q * 32, up, zero);
            TR2(3);
            asm volatile("fence.proxy.async.shared::cta;\n" ::: "memory");
            __syncwarp();
            arrive1(bar_oready);
            if (!more) break;
            ok_a = false;
            seek(p2_start(n + 3));
            mbar_wait(bar_bfull + st, ph);
        }
        TSTAMP(1, 30);
    }
}

}

extern "C" void kernel_launch(void* const* d_in, const int* in_sizes, int n_in, void* d_out, int out_size) {
    const __nv_bfloat16* x = (const __nv_bfloat16*)d_in[0];
    const __nv_bfloat16* dw = (const __nv_bfloat16*)d_in[1];
    const __nv_bfloat16* w1 = (const __nv_bfloat16*)d_in[2];
    const __nv_bfloat16* w2 = (const __nv_bfloat16*)d_in[3];
    const __nv_bfloat16* grn_g = (const __nv_bfloat16*)d_in[4];
    const __nv_bfloat16* grn_b = (const __nv_bfloat16*)d_in[5];
    __nv_bfloat16* out = (__nv_bfloat16*)d_out;

    cudaFuncSetAttribute(pass1_kernel, cudaFuncAttributeMaxDynamicSharedMemorySize, P1_SMEM);
    cudaFuncSetAttribute(pass2_kernel, cudaFuncAttributeMaxDynamicSharedMemorySize, P2_SMEM);

    typedef CUresult (*EncodeFn)(CUtensorMap*, CUtensorMapDataType, cuuint32_t, void*, const cuuint64_t*, const cuuint64_t*,
                                 const cuuint32_t*, const cuuint32_t*, CUtensorMapInterleave, CUtensorMapSwizzle,
                                 CUtensorMapL2promotion, CUtensorMapFloatOOBfill);
    static EncodeFn encode = nullptr;
    if (!encode) {
        cudaDriverEntryPointQueryResult qres;
        cudaGetDriverEntryPoint("cuTensorMapEncodeTiled", (void**)&encode, cudaEnableDefault, &qres);
    }
    CUtensorMap wmap;
    const cuuint64_t gdim[2] = {HID, C_DIM};
    const cuuint64_t gstr[1] = {HID * 2};
    const cuuint32_t box[2] = {64, 192}, estr[2] = {1, 1};
    CUresult er = encode(&wmap, CU_TENSOR_MAP_DATA_TYPE_BFLOAT16, 2, (void*)w1, gdim, gstr, box, estr, CU_TENSOR_MAP_INTERLEAVE_NONE,
           CU_TENSOR_MAP_SWIZZLE_128B, CU_TENSOR_MAP_L2_PROMOTION_L2_128B, CU_TENSOR_MAP_FLOAT_OOB_FILL_NONE);
    if (er != CUDA_SUCCESS) printf("tensor map encode failed %d\n", (int)er);

    pass1_kernel<<<NUM_CTAS, 512, P1_SMEM>>>(wmap, x, dw, w1, w2, grn_b, 0);

    cudaLaunchAttribute attr[1];
    attr[0].id = cudaLaunchAttributeProgrammaticStreamSerialization;
    attr[0].val.programmaticStreamSerializationAllowed = 1;
    cudaLaunchConfig_t cfg = {};
    cfg.gridDim = dim3(NUM_CTAS);
    cfg.stream = 0;
    cfg.attrs = attr;
    cfg.numAttrs = 1;
    cfg.blockDim = dim3(512);
    cfg.dynamicSmemBytes = P2_SMEM;
    cudaLaunchKernelEx(&cfg, pass2_kernel, x, grn_g, out, 0);
}
```

```cpp
#include <cuda.h>
#include <cuda_runtime.h>
#include <cuda_bf16.h>
#include <stdint.h>
#include <stdio.h>

namespace {

constexpr int M_TOTAL = 384 * 384;
constexpr int C_DIM   = 384;
constexpr int HID     = 1536;
constexpr int NT128   = M_TOTAL / 128;
constexpr int NUM_CTAS = 132;

#define P1_NSMALL 101
constexpr int NGRP = 15, NSMALL = P1_NSMALL;
constexpr int LN_STEP = 2 * NGRP, LN_RING = 2 * LN_STEP;
__device__ __forceinline__ int p1_tile(int t) { return t < LN_STEP ? t : t + min((t - LN_STEP) / 10 + 1, NSMALL); }
__device__ __forceinline__ int p1_place(int tile, int slot) {
    const int i = (tile + 3) / 11;
    return i * 11 == tile + 3 && (unsigned)(i - 3) < NSMALL ? LN_RING + i : slot;
}
constexpr int LN_TILE = 128 * C_DIM * 2;
constexpr int H_TILE = 64 * HID * 3 / 2;
constexpr int H_HALF = 3072, H_STEP = 6144;

__device__ __align__(1024) uint4 g_h[(size_t)M_TOTAL * HID * 3 / 32];
__device__ __align__(1024) uint4 g_ln[(LN_RING + 3 + NSMALL) * LN_TILE / 16];
__device__ __align__(1024) uint4 g_w2img[2][HID * C_DIM * 2 / 16];
__device__ __align__(16) float g_sums[2][HID + 2 * C_DIM];
__device__ __align__(16) unsigned g_ex[HID];
__device__ unsigned g_epoch;
__device__ __align__(128) unsigned g_img[3];
__device__ __align__(128) unsigned g_prog;
__device__ __align__(128) unsigned g_half[32][2];
__device__ unsigned g_flag[LN_RING + 3 + NSMALL][2][8];
#define TSTAMP(k, i)
#define STAMPT(t, i)
#define TRACE(wg, pos, i)
#define TRACEW(pos, i)

#define TR2(i)
#define TR2P(pos, i)
__host__ __device__ __forceinline__ int perm32(int n) {
    return (n & ~31) | (((n >> 1) & 3) << 3) | (((n >> 3) & 3) << 1) | (n & 1);
}

__device__ __forceinline__ uint32_t smem_u32(const void* p) { return (uint32_t)__cvta_generic_to_shared(p); }

__device__ __forceinline__ void mbar_init(uint32_t bar, uint32_t count) {
    asm volatile("mbarrier.init.shared::cta.b64 [%0], %1;\n" ::"r"(bar), "r"(count) : "memory");
}
__device__ __forceinline__ void mbar_expect_tx(uint32_t bar, uint32_t bytes) {
    asm volatile("mbarrier.arrive.expect_tx.shared::cta.b64 _, [%0], %1;\n" ::"r"(bar), "r"(bytes) : "memory");
}
__device__ __forceinline__ void mbar_arrive(uint32_t bar) {
    asm volatile("mbarrier.arrive.shared::cta.b64 _, [%0];\n" ::"r"(bar) : "memory");
}
__device__ __forceinline__ void mbar_arrive_cluster(uint32_t bar_cluster_addr) {
    asm volatile("mbarrier.arrive.shared::cluster.b64 _, [%0];\n" ::"r"(bar_cluster_addr) : "memory");
}
#define SAFE_BREAK
__device__ __forceinline__ void mbar_wait(uint32_t bar, uint32_t parity) {
    asm volatile(
        "{\n"
        ".reg .pred p;\n"
        "LAB_WAIT:\n"
        "mbarrier.try_wait.parity.shared::cta.b64 p, [%0], %1;\n"
        "@!p bra LAB_WAIT;\n"
        "}\n" ::"r"(bar), "r"(parity) : "memory");
}
__device__ __forceinline__ bool mbar_test(uint32_t bar, uint32_t parity) {
    uint32_t ok;
    asm volatile("{\n.reg .pred p;\n"
                 "mbarrier.test_wait.parity.shared::cta.b64 p, [%1], %2;\n"
                 "selp.u32 %0, 1, 0, p;\n}\n" : "=r"(ok) : "r"(bar), "r"(parity) : "memory");
    return ok != 0;
}
__device__ __forceinline__ uint32_t mapa(uint32_t addr, uint32_t rank) {
    uint32_t r;
    asm volatile("mapa.shared::cluster.u32 %0, %1, %2;\n" : "=r"(r) : "r"(addr), "r"(rank));
    return r;
}
__device__ __forceinline__ void bulk_g2s(uint32_t dst, const void* src, uint32_t bytes, uint32_t bar) {
    asm volatile("cp.async.bulk.shared::cluster.global.mbarrier::complete_tx::bytes [%0], [%1], %2, [%3];\n"
                 ::"r"(dst), "l"(src), "r"(bytes), "r"(bar) : "memory");
}
__device__ __forceinline__ void bulk_g2s_mc(uint32_t dst, const void* src, uint32_t bytes, uint32_t bar, uint16_t mask) {
    asm volatile("cp.async.bulk.shared::cluster.global.mbarrier::complete_tx::bytes.multicast::cluster [%0], [%1], %2, [%3], %4;\n"
                 ::"r"(dst), "l"(src), "r"(bytes), "r"(bar), "h"(mask) : "memory");
}
__device__ __forceinline__ void tma2(uint32_t dst, const CUtensorMap* map, int c0, int c1, uint32_t bar) {
    asm volatile("cp.async.bulk.tensor.2d.shared::cluster.global.tile.mbarrier::complete_tx::bytes [%0], [%1, {%2, %3}], [%4];\n"
                 ::"r"(dst), "l"(map), "r"(c0), "r"(c1), "r"(bar) : "memory");
}
template <bool ACQ>
__device__ __forceinline__ uint32_t flag_wait(const unsigned* p, unsigned target) {
    unsigned v, n = 0;
    do {
        if (ACQ) asm volatile("ld.acquire.gpu.global.u32 %0, [%1];\n" : "=r"(v) : "l"(p) : "memory");
        else asm volatile("ld.relaxed.gpu.global.u32 %0, [%1];\n" : "=r"(v) : "l"(p) : "memory");
        n++;
    } while (v < target);
    return n == 1;
}
__device__ __forceinline__ void ldsm4t(uint32_t (&r)[4], uint32_t addr) {
    asm volatile("ldmatrix.sync.aligned.m8n8.x4.trans.shared.b16 {%0,%1,%2,%3}, [%4];\n"
                 : "=r"(r[0]), "=r"(r[1]), "=r"(r[2]), "=r"(r[3]) : "r"(addr) : "memory");
}
__device__ __forceinline__ void bulk_s2g(void* dst, uint32_t src, uint32_t bytes) {
    asm volatile("cp.async.bulk.global.shared::cta.bulk_group [%0], [%1], %2;\n" ::"l"(dst), "r"(src), "r"(bytes) : "memory");
}
__device__ __forceinline__ void cluster_sync_relaxed() {
    asm volatile("barrier.cluster.arrive.relaxed.aligned;\nbarrier.cluster.wait.aligned;\n" ::: "memory");
}
__device__ __forceinline__ void gdc_wait() { asm volatile("griddepcontrol.wait;\n" ::: "memory"); }
__device__ __forceinline__ void gdc_launch() { asm volatile("griddepcontrol.launch_dependents;\n" ::: "memory"); }
__device__ __forceinline__ uint32_t cluster_rank() {
    uint32_t r;
    asm volatile("mov.u32 %0, %%cluster_ctarank;\n" : "=r"(r));
    return r;
}
__device__ __forceinline__ bool elect_one() {
    uint32_t pred;
    asm volatile("{\n.reg .pred p;\nelect.sync _|p, 0xffffffff;\nselp.u32 %0, 1, 0, p;\n}\n" : "=r"(pred));
    return pred != 0;
}
__device__ __forceinline__ void wg_fence() { asm volatile("wgmma.fence.sync.aligned;\n" ::: "memory"); }
__device__ __forceinline__ void wg_commit() { asm volatile("wgmma.commit_group.sync.aligned;\n" ::: "memory"); }
template <int N> __device__ __forceinline__ void wg_wait() {
    asm volatile("wgmma.wait_group.sync.aligned %0;\n" ::"n"(N) : "memory");
}
template <int R> __device__ __forceinline__ void reg_inc() { asm volatile("setmaxnreg.inc.sync.aligned.u32 %0;\n" ::"n"(R)); }
template <int R> __device__ __forceinline__ void reg_dec() { asm volatile("setmaxnreg.dec.sync.aligned.u32 %0;\n" ::"n"(R)); }
__device__ __forceinline__ void bar_sync(int id, int n) { asm volatile("bar.sync %0, %1;\n" ::"r"(id), "r"(n) : "memory"); }
__device__ __forceinline__ void bar_arrive(int id, int n) { asm volatile("bar.arrive %0, %1;\n" ::"r"(id), "r"(n) : "memory"); }

__device__ __forceinline__ uint64_t make_desc(uint32_t saddr, uint32_t lbo, uint32_t sbo) {
    return (uint64_t)((saddr & 0x3FFFF) >> 4) | ((uint64_t)(lbo >> 4) << 16) | ((uint64_t)(sbo >> 4) << 32);
}

__device__ __forceinline__ void stg128_cs(void* p, uint32_t a, uint32_t b, uint32_t c, uint32_t d) {
    asm volatile("st.global.cs.v4.u32 [%0], {%1,%2,%3,%4};\n" ::"l"(p), "r"(a), "r"(b), "r"(c), "r"(d) : "memory");
}
__device__ __forceinline__ uint32_t pack_bf16(float lo, float hi) {
    uint32_t r;
    asm("cvt.rn.bf16x2.f32 %0, %1, %2;\n" : "=r"(r) : "f"(hi), "f"(lo));
    return r;
}
__device__ __forceinline__ float bf_lo(uint32_t v) { return __uint_as_float(v << 16); }
__device__ __forceinline__ float bf_hi(uint32_t v) { return __uint_as_float(v & 0xffff0000u); }
__device__ __forceinline__ uint32_t bf2_mul(uint32_t a, uint32_t b) {
    uint32_t r;
    asm("mul.rn.bf16x2 %0, %1, %2;\n" : "=r"(r) : "r"(a), "r"(b));
    return r;
}
__device__ __forceinline__ uint32_t bf2_fma(uint32_t a, uint32_t b, uint32_t c) {
    uint32_t r;
    asm("fma.rn.bf16x2 %0, %1, %2, %3;\n" : "=r"(r) : "r"(a), "r"(b), "r"(c));
    return r;
}
__device__ __forceinline__ uint32_t bf2_add(uint32_t a, uint32_t b) {
    uint32_t r;
    asm("add.rn.bf16x2 %0, %1, %2;\n" : "=r"(r) : "r"(a), "r"(b));
    return r;
}
constexpr float KAPPA = 0.3292034911525734f;
constexpr float GELU_C = 2.423681954311584f;
constexpr float HSCALE = 1.0f / (2.0f * KAPPA);
__device__ __forceinline__ uint32_t acc_exp(float z) { return max(__float_as_uint(z) >> 23, 10u); }
__device__ __forceinline__ void sched_break(int zero) {
    asm volatile("{\n.reg .pred p;\nsetp.ne.s32 p, %0, 0;\nSB_LOOP:\n@p nanosleep.u32 1;\n@p bra SB_LOOP;\n}\n" ::"r"(zero));
}

#define ACCR8(d, o) "+r"(d[o + 0]), "+r"(d[o + 1]), "+r"(d[o + 2]), "+r"(d[o + 3]), "+r"(d[o + 4]), "+r"(d[o + 5]), "+r"(d[o + 6]), "+r"(d[o + 7])
__device__ __forceinline__ void mma_rs_n128(uint32_t (&d)[32], const uint32_t (&a)[4], uint64_t desc, int scale_d) {
    asm volatile(
        "{\n.reg .pred p;\nsetp.ne.b32 p, %37, 0;\n"
        "wgmma.mma_async.sync.aligned.m64n128k16.f16.f16.f16 "
        "{%0,%1,%2,%3,%4,%5,%6,%7,%8,%9,%10,%11,%12,%13,%14,%15,"
        "%16,%17,%18,%19,%20,%21,%22,%23,%24,%25,%26,%27,%28,%29,%30,%31},"
        "{%32,%33,%34,%35}, %36, p, 1, 1, 0;\n}\n"
        : ACCR8(d, 0), ACCR8(d, 8), ACCR8(d, 16), ACCR8(d, 24)
        : "r"(a[0]), "r"(a[1]), "r"(a[2]), "r"(a[3]), "l"(desc), "r"(scale_d));
}
__device__ __forceinline__ void mma_ss_n128(uint32_t (&d)[32], uint64_t da, uint64_t db) {
    asm volatile(
        "{\n.reg .pred p;\nsetp.ne.b32 p, %34, 0;\n"
        "wgmma.mma_async.sync.aligned.m64n128k16.f16.f16.f16 "
        "{%0,%1,%2,%3,%4,%5,%6,%7,%8,%9,%10,%11,%12,%13,%14,%15,"
        "%16,%17,%18,%19,%20,%21,%22,%23,%24,%25,%26,%27,%28,%29,%30,%31},"
        "%32, %33, p, 1, 1, 0, 0;\n}\n"
        : ACCR8(d, 0), ACCR8(d, 8), ACCR8(d, 16), ACCR8(d, 24)
        : "l"(da), "l"(db), "r"(1));
}
__device__ __forceinline__ uint32_t bf2_as_h2(uint32_t v) { return (v & 0x0fff0fffu) * 7u + v; }
__device__ __forceinline__ float h_lo(uint32_t v) {
    float r;
    asm("{\n.reg .b16 l, h;\nmov.b32 {l, h}, %1;\ncvt.f32.f16 %0, l;\n}\n" : "=f"(r) : "r"(v));
    return r;
}
__device__ __forceinline__ float h_hi(uint32_t v) {
    float r;
    asm("{\n.reg .b16 l, h;\nmov.b32 {l, h}, %1;\ncvt.f32.f16 %0, h;\n}\n" : "=f"(r) : "r"(v));
    return r;
}

__device__ __forceinline__ void mma_rs_n192(uint32_t (&d)[48], const uint4& a, uint64_t db, int scale_d) {
    asm volatile(
        "{\n.reg .pred p;\nsetp.ne.b32 p, %53, 0;\n"
        "wgmma.mma_async.sync.aligned.m64n192k16.f16.f16.f16 "
        "{%0,%1,%2,%3,%4,%5,%6,%7,%8,%9,%10,%11,%12,%13,%14,%15,"
        "%16,%17,%18,%19,%20,%21,%22,%23,%24,%25,%26,%27,%28,%29,%30,%31,"
        "%32,%33,%34,%35,%36,%37,%38,%39,%40,%41,%42,%43,%44,%45,%46,%47},"
        "{%48,%49,%50,%51}, %52, p, 1, 1, 0;\n}\n"
        : ACCR8(d, 0), ACCR8(d, 8), ACCR8(d, 16), ACCR8(d, 24), ACCR8(d, 32), ACCR8(d, 40)
        : "r"(a.x), "r"(a.y), "r"(a.z), "r"(a.w), "l"(db), "r"(scale_d));
}

__device__ __forceinline__ uint32_t pack_f16(float lo, float hi) {
    uint32_t r;
    asm("cvt.rn.f16x2.f32 %0, %1, %2;\n" : "=r"(r) : "f"(hi), "f"(lo));
    return r;
}

constexpr int P1_IMG = 900;
constexpr int P1_SLOT = LN_TILE / 2, P1_NST = 4;
constexpr int P1_X = 16 * C_DIM * 2;
constexpr int P1_OFF_A = P1_SLOT * P1_NST;
constexpr int P1_OFF_DW = P1_OFF_A + 3 * 2048;
constexpr int P1_OFF_X = P1_OFF_DW + C_DIM * 2;
constexpr int P1_OFF_BAR = P1_OFF_X + 2 * P1_X;
constexpr int P1_OFF_TILE = P1_OFF_BAR + (2 * P1_NST + 3 + 2 + 3 + 2) * 8;
constexpr int P1_SMEM = P1_OFF_TILE + 64;

__device__ __forceinline__ float rsqrt_fast(float x) {
    float r;
    asm("rsqrt.approx.ftz.f32 %0, %1;\n" : "=f"(r) : "f"(x));
    return r;
}
__device__ __forceinline__ float sum8(const uint32_t (&c)[4]) {
    const uint32_t u = bf2_add(bf2_add(c[0], c[1]), bf2_add(c[2], c[3]));
    return bf_lo(u) + bf_hi(u);
}
__device__ __forceinline__ void lds128(uint32_t (&v)[4], uint32_t a) {
    asm volatile("ld.shared.v4.u32 {%0,%1,%2,%3}, [%4];\n" : "=r"(v[0]), "=r"(v[1]), "=r"(v[2]), "=r"(v[3]) : "r"(a) : "memory");
}
template <class F>
__device__ __forceinline__ void ln_row(uint32_t (&v)[6][4], uint32_t sdw, F after_loads) {
    uint32_t c[4], s[4], d[4], nm;
#pragma unroll
    for (int i = 0; i < 6; i++) {
        lds128(d, sdw + i * 128);
        if (i == 0) {
#pragma unroll
            for (int k = 0; k < 4; k++) c[k] = bf2_mul(v[0][k], d[k]);
            const float p = sum8(c) * -0.125f;
            nm = pack_bf16(p, p);
        }
#pragma unroll
        for (int k = 0; k < 4; k++) {
            v[i][k] = bf2_fma(v[i][k], d[k], nm);
            s[k] = i ? bf2_add(v[i][k], s[k]) : v[i][k];
            c[k] = i ? bf2_fma(v[i][k], v[i][k], c[k]) : bf2_mul(v[i][k], v[i][k]);
        }
    }
    after_loads(c[0]);
    float m = fmaf(sum8(s), 1.0f / 48, -bf_lo(nm));
    float q = fmaf(-bf_lo(nm), fmaf(2.f, m, bf_lo(nm)), sum8(c) * (1.0f / 48));
#pragma unroll
    for (int o = 1; o < 8; o <<= 1) {
        m += __shfl_xor_sync(0xffffffffu, m, o);
        q += __shfl_xor_sync(0xffffffffu, q, o);
    }
    m *= 0.125f;
    const float r = KAPPA * rsqrt_fast(fmaxf(fmaf(-m, m, q * 0.125f), 0.f) + 1e-5f);
    const float e = (-bf_lo(nm) - m) * r * 0x1p-112f;
    const bool two = __any_sync(0xffffffffu, r < 0x1p-14f);
    const float r1 = r * (two ? 0x1p-56f : 0x1p-112f);
    uint32_t mul = pack_bf16(r1, r1), add = two ? 0u : pack_bf16(e, e);
#pragma unroll 1
    for (int it = !two; it < 2; it++) {
#pragma unroll
        for (int i = 0; i < 6; i++)
#pragma unroll
            for (int k = 0; k < 4; k++) v[i][k] = bf2_fma(v[i][k], mul, add);
        mul = 0x23802380u;
        add = pack_bf16(e, e);
    }
#pragma unroll
    for (int i = 0; i < 6; i++)
#pragma unroll
        for (int k = 0; k < 4; k++) v[i][k] = bf2_as_h2(v[i][k]);
}

__device__ __forceinline__ float gelu_s(float y) {
    float u = y * fmaf(y, y, GELU_C);
    float t;
    asm volatile("tanh.approx.f32 %0, %1;\n" : "=f"(t) : "f"(u));
    return fmaf(y, t, y);
}
__device__ __forceinline__ void p1_pack(int c, uint32_t (&p)[4], uint32_t (&dd)[4]) {
#pragma unroll
    for (int u = 0; u < 4; u++) {
        if ((c & 3) == 0) dd[u] = p[u];
        else {
            uint32_t n = dd[u];
            if ((c & 3) == 1) n = __byte_perm(n, 0, 0x2301);
            if ((c & 3) == 2) {
                dd[u] = __byte_perm(n >> 3, n >> 1, 0x6341);
                n = __byte_perm(n >> 3, n >> 1, 0x7250);
            }
            asm("lop3.b32 %0, %0, %1, 0x40074007, 0xd8;\n" : "+r"(p[u]) : "r"(n));
        }
    }
}
__device__ __forceinline__ void p1_store(int c, const uint32_t (&p)[4], uint8_t* hptr) {
    if (c & 3) stg128_cs(hptr + (c >> 2) * H_HALF + ((c & 3) - 1) * 512, p[0], p[1], p[2], p[3]);
}

template <bool GEN>
__device__ __forceinline__ void p1_epilogue(uint32_t (&acc)[32], float (&ssq)[2], uint32_t sc2, uint8_t* hp, int zero) {
    uint32_t sq[2], dd[4];
#pragma unroll
    for (int c = 0; c < 8; c++) {
        if (GEN) sched_break(zero);
        uint32_t p[4];
#pragma unroll
        for (int u = 0; u < 4; u++) {
            const uint32_t y = acc[8 * (c >> 1) + 2 * u + (c & 1)];
            if (GEN) {
                const float sc = c & 1 ? bf_hi(sc2) : bf_lo(sc2), fs = __uint_as_float(0x78000000u - __float_as_uint(sc));
                const float g0 = gelu_s(h_lo(y) * fs), g1 = gelu_s(h_hi(y) * fs);
                ssq[c & 1] = fmaf(g1, g1, fmaf(g0, g0, ssq[c & 1]));
                p[u] = pack_f16(g0 * sc, g1 * sc);
            } else {
                uint32_t g;
                asm("{\n.reg .b32 w;\n"
                    "fma.rn.f16x2 w, %1, %1, %2;\n"
                    "mul.rn.f16x2 w, w, %1;\n"
                    "tanh.approx.f16x2 w, w;\n"
                    "fma.rn.f16x2 %0, %1, w, %1;\n}\n" : "=r"(g) : "r"(y), "r"(0x40d940d9u));
                acc[8 * (c >> 1) + 2 * u + (c & 1)] = g;
                if (c < 2 && u == 0) asm("mul.rn.f16x2 %0, %1, %1;\n" : "=r"(sq[c & 1]) : "r"(g));
                else asm("fma.rn.f16x2 %0, %1, %1, %0;\n" : "+r"(sq[c & 1]) : "r"(g));
                if (c & 1) asm("{\n.reg .b16 l, h;\n.reg .b32 f;\nmov.b32 {l, h}, %2;\nmov.b32 f, {h, h};\nmul.rn.f16x2 %0, %1, f;\n}\n" : "=r"(p[u]) : "r"(g), "r"(sc2));
                else asm("{\n.reg .b16 l, h;\n.reg .b32 f;\nmov.b32 {l, h}, %2;\nmov.b32 f, {l, l};\nmul.rn.f16x2 %0, %1, f;\n}\n" : "=r"(p[u]) : "r"(g), "r"(sc2));
            }
        }
        p1_pack(c, p, dd);
        if (c & 3) {
#pragma unroll
            for (int u = 0; u < 4; u++) acc[4 * (c - 1 - (c >> 2)) + u] = p[u];
        }
        p1_store(c, p, hp);
    }
    if (!GEN) {
#pragma unroll
        for (int r = 0; r < 2; r++) ssq[r] += h_lo(sq[r]) + h_hi(sq[r]);
    }
}
template <int CS, int NWG>
__device__ __forceinline__ void p1_compute(uint32_t sbase, int cb0, int warp, int lane, int zero) {
    const uint32_t bar_full = sbase + P1_OFF_BAR, bar_empty = bar_full + P1_NST * 8, bar_w = bar_empty + P1_NST * 8;
    const int wg = warp >> 2, w = warp & 3, cb = cb0 + wg;
    const uint32_t slot_free = mapa(bar_empty, lane & (CS - 1)) + (lane / CS) * 8;
    if (lane < 4 * CS && lane / CS != 1 + wg && (NWG == 2 || wg || lane >= CS)) mbar_arrive_cluster(slot_free);
    if (wg == 1) bar_arrive(1, 256);
    uint32_t a[24][4], ex[2], gen = 0;
    const uint32_t wsrc = sbase + (1 + wg) * P1_SLOT + ((lane >> 4) * 8 + (lane & 7)) * 128 + (((2 * w + ((lane >> 3) & 1)) ^ (lane & 7)) << 4);
#pragma unroll 1
    for (int it = 0; it < 2; it++) {
        if (it) mbar_wait(bar_w + wg * 8, 0);
        TRACEW(110 + warp, 5);
        if (it || wg == 0) {
#pragma unroll
        for (int k = 0; k < 24; k++) ldsm4t(a[k], wsrc + k * 2048);
#pragma unroll
        for (int r = 0; r < 2; r++) {
            float t = 0.f;
#pragma unroll
            for (int j = 0; j < 6; j++) {
                uint32_t c = bf2_mul(a[4 * j][r], a[4 * j][r]);
#pragma unroll
                for (int k = 1; k < 8; k++) c = bf2_fma(a[4 * j + k / 2][r + (k & 1) * 2], a[4 * j + k / 2][r + (k & 1) * 2], c);
                t += bf_lo(c) + bf_hi(c);
            }
            t += __shfl_xor_sync(0xffffffffu, t, 1);
            t += __shfl_xor_sync(0xffffffffu, t, 2);
            asm("sqrt.approx.f32 %0, %0;\n" : "+f"(t));
            ex[r] = min(max(__float_as_uint(13.9f * t) >> 23, 72u), 198u);
        }
        asm volatile("{\n.reg .pred p;\nsetp.gt.u32 p, %1, 7;\nbar.red.or.pred p, %2, 128, p;\nselp.u32 %0, 1, 0, p;\n}\n"
                     : "=r"(gen) : "r"(max(ex[0] - 125u, ex[1] - 125u)), "r"(5 + wg) : "memory");
        gen = __shfl_sync(0xffffffffu, gen, 0) & it;
        if (it) {
            if ((lane & 3) < 2) g_ex[cb * 64 + w * 16 + (lane & 1) * 8 + (lane >> 2)] = lane & 1 ? ex[1] : ex[0];
            if (lane / CS == 1 + wg) mbar_arrive_cluster(slot_free);
            __syncwarp();
        }
        }
        if (gen) {
#pragma unroll
            for (int k = 0; k < 24; k++)
#pragma unroll
                for (int j = 0; j < 4; j++) a[k][j] = bf2_mul(a[k][j], (268u - ex[j & 1]) * 0x00800080u);
        }
        if (it || wg == 1) {
#pragma unroll
            for (int k = 0; k < 24; k++)
#pragma unroll
                for (int j = 0; j < 4; j++) {
                    a[k][j] = bf2_as_h2(bf2_mul(a[k][j], 0x07800780u));
                    asm volatile("" : "+r"(a[k][j]));
                }
        }
        TRACEW(110 + warp, 6);
    }
#pragma unroll
    for (int j = 0; j < 4; j++)
        asm volatile("st.shared.u32 [%0], %1;\n" ::"r"(sbase + P1_OFF_A + warp * 512 + (j & 1) * 256 + (j >> 1) * 128 + lane * 4), "r"(a[23][j]) : "memory");
    asm volatile("fence.proxy.async.shared::cta;\n" ::: "memory");
    TRACEW(110 + warp, 7);
    const uint32_t ex2 = ex[0] | ex[1] << 16;
    const uint32_t sc2 = gen ? 0x7f007f00u - (ex2 << 7) : (0x008e008eu - ex2) << 10;
    const uint32_t empty_remote = mapa(bar_empty, lane & (CS - 1));
    const int g = lane >> 2, q = lane & 3, turn = wg + 1 == NWG ? 1 : wg + 2;
    float ssq[2] = {0.f, 0.f};
    uint32_t acc[32] = {};
    TSTAMP(0, 1);
    STAMPT(128, 4);
    STAMPT(256, 5);

    uint8_t* hp = reinterpret_cast<uint8_t*>(g_h) + ((cb * 2 + (w >> 1)) * H_STEP + (w & 1) * 1536) + g * 64 + (q ^ (g >> 1)) * 16;
    const uint64_t desc_base = make_desc(sbase, 16, 1024) | (1ull << 62);
    const uint64_t da = make_desc(sbase + P1_OFF_A + wg * 2048, 128, 256);
#pragma unroll 1
    for (int i = 0;; i++) {
        const int s0 = (i & 1) * 16, par = (i >> 1) & 1;
        const uint64_t d0 = desc_base + (uint64_t)((i & 1) * (LN_TILE / 16));
        TRACE(wg, i, 0);
        mbar_wait(bar_full + s0, par);
        bar_sync(1 + wg, 256);
        TRACE(wg, i, 1);
        uint32_t step, more;
        wg_fence();
#pragma unroll
        for (int k = 0; k < 24; k++) {
            if (k == 12) mbar_wait(bar_full + s0 + 8, par);
            const uint64_t db = d0 + (uint64_t)((k >> 2) * 1024 + (k & 3) * 2);
            if (k < 23) mma_rs_n128(acc, a[k], db, k ? 1 : zero);
            else mma_ss_n128(acc, da, db);
            if (k == 23) bar_arrive(turn, 256);
            if (k % 12 == 11) wg_commit();
        }
        if (NWG == 2) {
            step = (i ? 11 : LN_STEP) * (2 * H_TILE);
            more = i + 1 < NSMALL;
        } else asm volatile("ld.shared.v2.u32 {%0, %1}, [%2];\n" : "=r"(step), "=r"(more) : "r"(sbase + P1_OFF_TILE + (i & 3) * 16) : "memory");
        TRACE(wg, i, 2);
        wg_wait<1>();
        if (lane < CS) mbar_arrive_cluster(empty_remote + s0);
        hp += step;
        TRACE(wg, i, 3);
        wg_wait<0>();
        TRACE(wg, i, 4);
        if (lane < CS) mbar_arrive_cluster(empty_remote + s0 + 8);
        if (gen) p1_epilogue<true>(acc, ssq, sc2, hp, zero);
        else p1_epilogue<false>(acc, ssq, sc2, hp, zero);
        if (!more) break;
    }
    TSTAMP(0, 21);
    if (wg == 0) bar_sync(1, 256);
    uint32_t par;
    if (NWG == 2) par = __ldcg(&g_epoch) & 1;
    else asm volatile("ld.shared.u32 %0, [%1];\n" : "=r"(par) : "r"(sbase + P1_OFF_TILE - 4) : "memory");
    float* sums = g_sums[par];
#pragma unroll
    for (int r = 0; r < 2; r++) {
        ssq[r] += __shfl_xor_sync(0xffffffffu, ssq[r], 1);
        ssq[r] += __shfl_xor_sync(0xffffffffu, ssq[r], 2);
        if (q == 0) atomicAdd(sums + cb * 64 + w * 16 + r * 8 + g, ssq[r]);
    }
    if (NWG == 2) {
        asm volatile("fence.proxy.async.global;\nfence.acq_rel.gpu;\n" ::: "memory");
        __syncwarp();
        if (lane == 0) asm volatile("red.relaxed.gpu.global.add.u32 [%0], 1;\n" ::"l"(&g_img[2]) : "memory");
    }
}

__device__ __forceinline__ void p1_w2(const __nv_bfloat16* __restrict__ w2, const __nv_bfloat16* __restrict__ grn_b, int w, int lane) {
    const int gw = blockIdx.x * 4 + w;
    float* sums = g_sums[__ldcg(&g_epoch) & 1] + HID;
    flag_wait<true>(&g_flag[40][1][0], 12);
    {
        const int col = gw % 6 * 64 + lane * 2;
        float bsum[2] = {0.f, 0.f}, asum[2] = {0.f, 0.f};
#pragma unroll 4
        for (int kk = 0; kk < 192; kk++) {
            const int k = gw / 6 * 192 + kk;
            const uint32_t v = *reinterpret_cast<const uint32_t*>(w2 + k * C_DIM + col);
            const float b = __bfloat162float(grn_b[k]), f = __uint_as_float(__ldcg(&g_ex[k]) << 23);
            bsum[0] = fmaf(b, bf_lo(v), bsum[0]);
            bsum[1] = fmaf(b, bf_hi(v), bsum[1]);
            asum[0] = fmaf(f, fabsf(bf_lo(v)), asum[0]);
            asum[1] = fmaf(f, fabsf(bf_hi(v)), asum[1]);
        }
#pragma unroll
        for (int j = 0; j < 2; j++) {
            atomicAdd(sums + col + j, bsum[j]);
            atomicAdd(sums + C_DIM + col + j, asum[j]);
        }
        __threadfence();
        __syncwarp();
        if (lane == 0) asm volatile("red.relaxed.gpu.global.add.u32 [%0], 1;\n" ::"l"(&g_flag[LN_RING + 2][0][0]) : "memory");
    }
    while (*(volatile unsigned*)&g_flag[P1_IMG % LN_RING][1][0] < 12 * (P1_IMG / LN_RING + 1)) {
        __nanosleep(2000);
        SAFE_BREAK
    }
    flag_wait<true>(&g_flag[LN_RING + 2][0][0], 48);
    float z = 0.f;
#pragma unroll
    for (int j = 0; j < C_DIM / 32; j++) z = fmaxf(z, __ldcg(sums + C_DIM + j * 32 + lane));
    const float sc = __uint_as_float((263u - acc_exp(__uint_as_float(__reduce_max_sync(0xffffffffu, __float_as_uint(z))))) << 23);
    const int np = gw % 6 * 64 + lane * 2;
#pragma unroll 2
    for (int cc = 0; cc < 24; cc++) {
        const int c = gw / 6 * 24 + cc;
        uint32_t v[8], o[2][4];
#pragma unroll
        for (int e = 0; e < 8; e++) v[e] = *reinterpret_cast<const uint32_t*>(w2 + (c * 8 + e) * C_DIM + perm32(np));
#pragma unroll
        for (int e = 0; e < 4; e++) {
            const uint2 t = __ldcg(reinterpret_cast<const uint2*>(g_ex) + c * 4 + e);
            const float f0 = __uint_as_float(t.x << 23), f1 = __uint_as_float(t.y << 23);
            o[0][e] = pack_f16(bf_lo(v[2 * e]) * f0 * sc, bf_lo(v[2 * e + 1]) * f1 * sc);
            o[1][e] = pack_f16(bf_hi(v[2 * e]) * f0 * sc, bf_hi(v[2 * e + 1]) * f1 * sc);
        }
#pragma unroll
        for (int j = 0; j < 2; j++)
            g_w2img[0][(((c >> 1) * 48 + (np >> 3)) * 2 + (c & 1)) * 8 + (np & 7) + j] = make_uint4(o[j][0], o[j][1], o[j][2], o[j][3]);
    }
    asm volatile("fence.proxy.async.global;\n" ::: "memory");
    __threadfence();
    __syncwarp();
    if (lane == 0) asm volatile("red.relaxed.gpu.global.add.u32 [%0], 1;\n" ::"l"(&g_img[0]) : "memory");
}

__device__ __forceinline__ void p1_load_w1(uint32_t sbase, const CUtensorMap* wmap, int cb0, int nwg) {
    const uint32_t bar_w = sbase + P1_OFF_BAR + 2 * P1_NST * 8;
    for (int i = 0; i < nwg; i++) {
        mbar_expect_tx(bar_w + i * 8, P1_SLOT);
        tma2(sbase + (1 + i) * P1_SLOT, wmap, (cb0 + i) * 64, 0, bar_w + i * 8);
        tma2(sbase + (1 + i) * P1_SLOT + P1_SLOT / 2, wmap, (cb0 + i) * 64, 192, bar_w + i * 8);
    }
}

template <int CS>
__global__ void __cluster_dims__(CS, 1, 1) __launch_bounds__(512, 1)
pass1_kernel(const __grid_constant__ CUtensorMap wmap, const __nv_bfloat16* __restrict__ x, const __nv_bfloat16* __restrict__ dw,
             const __nv_bfloat16* __restrict__ w1, int zero) {
    extern __shared__ __align__(1024) uint8_t smem[];
    const uint32_t sbase = smem_u32(smem);
    const uint32_t bar_full = sbase + P1_OFF_BAR, bar_empty = bar_full + P1_NST * 8, bar_w = bar_empty + P1_NST * 8;
    const uint32_t bar_xfull = bar_w + 24, bar_raw = bar_xfull + 16, bar_done = bar_raw + 16;
    const int tid = threadIdx.x;
    const int warp = __shfl_sync(0xffffffffu, tid >> 5, 0), lane = tid & 31;
    const uint32_t rank = cluster_rank();
    const int bid = blockIdx.x, cl = bid >> 1;
    uint8_t* const ring = reinterpret_cast<uint8_t*>(g_ln);
    const int ln0 = bid >> 2, items = (NT128 - 1 - ln0) / LN_STEP + 1;

    TSTAMP(0, 0);
    TRACEW(110 + warp, 0);

    if (warp >= 12) {
        reg_dec<56>();
        asm volatile("barrier.cluster.arrive.relaxed.aligned;\n" ::: "memory");
        asm volatile("barrier.cluster.wait.aligned;\n" ::: "memory");
        {
            auto ring_row = [&](int p) {
                const int n = (p & 8) * 8 + (lane >> 3) * 8 + (p & 3) * 2 + (p >> 2 & 1);
                return n * 128 + (((lane ^ n) & 7) << 4);
            };
            const uint8_t* xsrc = reinterpret_cast<const uint8_t*>(x) + (size_t)(LN_STEP * 8 + bid * 2 + (warp & 1)) * P1_X;
            const uint32_t xbar = bar_xfull + (warp & 1) * 8, xdst = sbase + P1_OFF_X + (warp & 1) * P1_X;
            const uint32_t sdw = sbase + P1_OFF_DW + (lane & 7) * 16;
            uint32_t src = xdst - P1_OFF_X + (lane >> 3) * (C_DIM * 2) + (lane & 7) * 16;
            int row0 = ring_row((bid & 7) * 2 + (warp & 1)) ^ 288, slot = bid >> 3, used = 0;
            auto next = [&]() {
                xsrc += (size_t)LN_STEP * 8 * P1_X;
                if (elect_one()) {
                    mbar_expect_tx(xbar, P1_X);
                    bulk_g2s(xdst, xsrc, P1_X, xbar);
                }
                __syncwarp();
            };
#pragma unroll 1
            for (int i = -1; i < items; i++) {
                if (warp == 14) TRACEW(128 + i, 0);
                const int place = p1_place(ln0 + i * LN_STEP, slot);
                const int last = i > 0 ? 3 : i ? 2 + (warp >> 1 & 1) : 1;
#pragma unroll 1
                for (int ps = i < 0 ? last - 4 : 0; ps <= last; ps += i < 0 ? 4 : 1) {
                    if (i < 0 && ps > 0) STAMPT(416, 6);
                    if (i < 0 && ps > 0) mbar_wait(bar_raw, 0);
                    if (i < 0 && ps > 0) STAMPT(416, 7);
                    if (ps == 0) {
                        if (used) flag_wait<false>(&g_flag[slot][1][0], used);
                        if (i && i + 1 < items && elect_one())
                            asm volatile("cp.async.bulk.prefetch.L2.global [%0], %1;\n" ::"l"(xsrc + (size_t)LN_STEP * 8 * P1_X), "r"(P1_X) : "memory");
                        if (i) mbar_wait(xbar, ~i & 1);
                        else mbar_wait(bar_raw + 8, 0);
                        if (warp == 14) TRACEW(128 + i, 1);
                    }
                    uint32_t v[6][4];
#pragma unroll
                    for (int j = 0; j < 6; j++) lds128(v[j], src + (ps & 3) * (4 * C_DIM * 2) + j * 128);
                    ln_row(v, sdw, [&](uint32_t dep) {
                        if (i == 0 && ps == 1 && lane < CS) mbar_arrive_cluster(mapa(bar_empty, lane) + (dep & zero));
                        if (ps == 3 && i > 0 && i + 1 < items && !__any_sync(0xffffffffu, dep & zero)) next();
                    });
                    uint8_t* dst = ring + (place * LN_TILE + (ps & 1) * 4096 + (row0 ^ (ps & 2) * 144));
#pragma unroll
                    for (int j = 0; j < 6; j++)
                        asm volatile("{\n.reg .pred p;\nsetp.ge.s32 p, %5, 0;\n@p st.global.v4.u32 [%0], {%1,%2,%3,%4};\n}\n"
                                     ::"l"(dst + j * 16384), "r"(v[j][0]), "r"(v[j][1]), "r"(v[j][2]), "r"(v[j][3]), "r"(ps) : "memory");
                }
                if (warp == 14) TRACEW(128 + i, 2);
                asm volatile("fence.proxy.async.global;\nfence.acq_rel.cta;\n" ::: "memory");
                if (i < 0) {
                    bar_sync(4, 128);
                    if (warp < 14) break;
                    row0 ^= 288;
                    slot += NGRP;
                } else {
                    if (i) mbar_wait(bar_done, ~i & 1);
                    else {
                        src += P1_OFF_X;
                        slot = ln0;
                        row0 = ring_row((bid & 3) * 4 + (warp & 1) * 2);
                    }
                    __syncwarp();
                    if (lane == 0) mbar_arrive(bar_done);
                    if ((slot += LN_STEP) >= LN_RING) { slot -= LN_RING; used += 12; }
                }
            }
            if (warp < 14 && lane < CS) mbar_arrive_cluster(mapa(bar_empty, lane));
        }
        if (warp == 12) {
            int prev = 0, t = cl >> 2, next = t + NGRP;
            const uint32_t rbase = mapa(sbase, lane & (CS - 1));
            int i = 0;
#pragma unroll 1
            for (; t < NT128; i++) {
                const int s0 = (i & 1) * 2, par = (i >> 1) & 1;
                const int round = t / LN_RING, slot = t - round * LN_RING;
                const uint8_t* src = ring + slot * LN_TILE + rank * (P1_SLOT / CS);
                int draw = 0;
                if (rank == 0 && lane == 0) draw = 2 * NGRP + atomicAdd(&g_flag[LN_RING + ((cl >> 1) & 1)][cl & 1][0], 1u);
                flag_wait<true>(&g_flag[slot][0][0], 8 * round + 8);
                TRACEW(i, 2);
                if (i == 0) STAMPT(384, 10);
                if (i == 2) STAMPT(384, 13);
                if (i == 3) STAMPT(384, 14);
                asm volatile("fence.proxy.async.global;\n" ::: "memory");
                draw = p1_tile(__shfl_sync(0xffffffffu, draw, 0));
#pragma unroll
                for (int h = 0; h < 2; h++) {
                    mbar_wait(bar_empty + (s0 + h) * 8, par);
                    TRACEW(i, 4 + h);
                    if (i == 0 && h == 1) STAMPT(384, 11);
                    if (elect_one()) {
                        mbar_expect_tx(bar_full + (s0 + h) * 8, P1_SLOT + 16 - 16 * h);
                        bulk_g2s_mc(sbase + (s0 + h) * P1_SLOT + rank * (P1_SLOT / CS), src + h * P1_SLOT, P1_SLOT / CS, bar_full + (s0 + h) * 8, (uint16_t)((1 << CS) - 1));
                    }
                    __syncwarp();
                    if (h == 0 && rank == 0 && lane < CS)
                        asm volatile("st.async.shared::cluster.mbarrier::complete_tx::bytes.v4.u32 [%0], {%1, %2, %3, %3}, [%4];\n"
                                     ::"r"(rbase + P1_OFF_TILE + (i & 3) * 16), "r"((t - prev) * (2 * H_TILE)), "r"((int)(next < NT128)), "r"(draw),
                                       "r"(rbase + P1_OFF_BAR + s0 * 8) : "memory");
                }
                prev = t;
                t = next;
                next = draw;
                if (rank != 0) {
                    mbar_wait(bar_full + s0 * 8, (i >> 1) & 1);
                    mbar_wait(bar_full + s0 * 8 + 8, (i >> 1) & 1);
                    if (lane == 0 && rank == 1) asm volatile("red.relaxed.gpu.global.add.u32 [%0], %1;\n" ::"l"(&g_flag[slot][1][0]), "r"(CS * 3 / 2) : "memory");
                    asm volatile("ld.shared.u32 %0, [%1];\n" : "=r"(next) : "r"(sbase + P1_OFF_TILE + (i & 3) * 16 + 8) : "memory");
                    TRACEW(i, 3);
                }
            }
#pragma unroll 1
            for (int j = 2 * i; j < 2 * i + 4; j++) mbar_wait(bar_empty + (j & 3) * 8, (j >> 2) & 1);
        } else if (warp == 13) {
            STAMPT(416, 8);
            if (lane == 0) asm volatile("red.release.gpu.global.add.u32 [%0], 1;\n" ::"l"(&g_flag[bid >> 3][0][0]) : "memory");
            __syncwarp();
            STAMPT(416, 9);
            const uint32_t ep = g_epoch & 1;
            asm volatile("st.shared.u32 [%0], %1;\n" ::"r"(sbase + P1_OFF_TILE - 4), "r"(ep) : "memory");
            if (bid < 18) reinterpret_cast<float4*>(g_sums[ep ^ 1])[bid * 32 + lane] = make_float4(0.f, 0.f, 0.f, 0.f);
#pragma unroll 1
            for (int i = 0; i < items; i++) {
                mbar_wait(bar_done, i & 1);
                asm volatile("fence.proxy.async.global;\n" ::: "memory");
                if (lane == 0) {
                    const int slot = i ? ln0 + (i & 1) * LN_STEP : NGRP + (bid >> 3), place = p1_place(ln0 + i * LN_STEP, slot);
                    mbar_arrive(bar_done);
                    asm volatile("red.release.gpu.global.add.u32 [%0], %1;\n" ::"l"(&g_flag[place][0][0]), "r"(i ? 2 : 1) : "memory");
                    if (place != slot) {
                        atomicAdd(&g_flag[slot][0][0], 2u);
                        atomicAdd(&g_flag[slot][1][0], 3u);
                    }
                }
                __syncwarp();
                TRACEW(128 + i, 3);
            }
        }
    } else {
        if (tid == 0) {
            mbar_init(bar_raw, 1);
            mbar_init(bar_raw + 8, 1);
            mbar_init(bar_xfull, 1);
            mbar_init(bar_xfull + 8, 1);
            for (int i = 0; i < 3; i++) mbar_init(bar_w + i * 8, 1);
            asm volatile("fence.mbarrier_init.release.cluster;\n" ::: "memory");
            {
                mbar_expect_tx(bar_raw, P1_X + C_DIM * 2);
                bulk_g2s(sbase + P1_OFF_DW, dw, C_DIM * 2, bar_raw);
                for (int i = 0; i < 2; i++) bulk_g2s(sbase + i * P1_X + P1_X / 2, x + (size_t)(bid * 16 + i * 8) * C_DIM, P1_X / 2, bar_raw);
                if (bid < 96) asm volatile("cp.async.bulk.prefetch.L2.global [%0], 12288;\n" ::"l"(w1 + bid * 6144) : "memory");
                mbar_expect_tx(bar_raw + 8, P1_X);
                for (int i = 0; i < 2; i++) bulk_g2s(sbase + i * P1_X, x + (size_t)(NGRP * 128 + bid * 16 + i * 8) * C_DIM, P1_X / 2, bar_raw + 8);
            }
            p1_load_w1(sbase, &wmap, (bid & 7) * 3, 3);
            for (int i = 0; i < 2; i++) {
                mbar_expect_tx(bar_xfull + i * 8, P1_X);
                bulk_g2s(sbase + P1_OFF_X + i * P1_X, x + (size_t)(LN_STEP * 128 + bid * 32 + i * 16) * C_DIM, P1_X, bar_xfull + i * 8);
            }
        }
        if (tid == 32) {
            mbar_init(bar_done, 3);
            mbar_arrive(bar_done);
            asm volatile("fence.mbarrier_init.release.cluster;\n" ::: "memory");
        }
        if (tid == 64) {
            for (int i = 0; i < P1_NST; i++) {
                mbar_init(bar_full + i * 8, 1);
                mbar_init(bar_empty + i * 8, 12 * CS);
            }
            asm volatile("fence.mbarrier_init.release.cluster;\n" ::: "memory");
            if (bid < 64) (&g_half[0][0])[bid] = 0;
            else if (bid == 64) g_prog = 0;
            else if (bid < 68) g_img[bid - 65] = 0;
        }
        __syncwarp();
        asm volatile("barrier.cluster.arrive.relaxed.aligned;\n" ::: "memory");
        reg_inc<152>();
        TRACEW(110 + warp, 1);
        gdc_launch();
        asm volatile("barrier.cluster.wait.aligned;\n" ::: "memory");
        p1_compute<CS, 3>(sbase, (bid & 7) * 3, warp, lane, zero);
        TSTAMP(0, 30);
    }
}

constexpr int P2_B = 24576, P2_NB = 5;
constexpr int P2_A = 3072, P2_NA = 5;
constexpr int P2_XROW = C_DIM * 2;
constexpr int P2_OFF_A = P2_B * P2_NB;
constexpr int P2_OFF_X = P2_OFF_A + 3 * P2_NA * P2_A;
constexpr int P2_XHALF = 32 * P2_XROW + 64;
constexpr int P2_OFF_BIAS = P2_OFF_X + 64 * P2_XROW + 64;
constexpr int P2_OFF_GRN = P2_OFF_BIAS + C_DIM * 4;
constexpr int P2_OFF_RED = P2_OFF_GRN + HID * 2;
constexpr int P2_OFF_BAR = P2_OFF_RED + 192;
static_assert(P2_OFF_BAR >= P1_OFF_DW && P2_OFF_BAR + (2 * P2_NB + 6 * P2_NA + 3) * 8 <= P1_OFF_BAR, "");
constexpr int P2_SMEM = P1_SMEM;
constexpr int P2_LAG = 17;
constexpr int P2_NCL = NUM_CTAS / 2, P2_ITEMS = NT128 / P2_NCL, P2_SHARED = NT128 - P2_ITEMS * P2_NCL;
constexpr int P2_POS = P2_LAG * (P2_ITEMS - 1) + 48;
__device__ __forceinline__ int p2_start(int n) { return n < 0 ? 0 : n == P2_ITEMS ? P2_POS - 24 : P2_LAG * n; }
constexpr int P2_FOLD = 17;
constexpr int P2_XC = 8 * P2_XROW;
constexpr int P2_DELTA = 7;
__device__ __forceinline__ int p2_tile(int cl, int n) {
    return n == 0 ? NT128 - 1 - cl : n < 0 || n == P2_ITEMS ? NT128 - 1 - P2_NCL - (cl >> 1) : cl + P2_NCL * (n - 1);
}

constexpr int P2_EG = 2;
__device__ __forceinline__ void p2_init(uint32_t (&acc)[48], int c, uint32_t sb) {
#pragma unroll
    for (int i = 8 * (c % 6); i < 8 * (c % 6) + 8; i += 4)
        asm volatile("ld.shared.v4.u32 {%0,%1,%2,%3}, [%4];\n" : "=r"(acc[i]), "=r"(acc[i + 1]), "=r"(acc[i + 2]), "=r"(acc[i + 3])
                     : "r"(sb + c * 128 + i % 8 * 4) : "memory");
}
__device__ __forceinline__ void p2_epilogue(uint32_t (&acc0)[48], uint32_t (&acc1)[48], uint32_t sx, uint32_t sb, uint32_t up, int zero) {
    uint32_t v[2][P2_EG][4];
    auto load = [&](int c, uint32_t a) {
#pragma unroll
        for (int j = 0; j < P2_EG; j++) {
            const int u = c * P2_EG + j;
            asm volatile("ld.shared.v4.u32 {%0,%1,%2,%3}, [%4];\n" : "=r"(v[c & 1][j][0]), "=r"(v[c & 1][j][1]), "=r"(v[c & 1][j][2]), "=r"(v[c & 1][j][3])
                         : "r"(a + (u >> 1) * 64 + (u & 1) * 4 * P2_XROW) : "memory");
        }
    };
    load(0, sx);
#pragma unroll
    for (int c = 0; c < 24 / P2_EG; c++) {
        if (c + 1 < 24 / P2_EG) load(c + 1, sx + (v[c & 1][P2_EG - 1][0] & zero));
#pragma unroll
        for (int j = 0; j < P2_EG; j++) {
            const int u = c * P2_EG + j, i = 8 * ((u >> 1) % 6) + (u & 1);
            const uint32_t (&acc)[48] = u < 12 ? acc0 : acc1;
            uint32_t (&w)[4] = v[c & 1][j];
#pragma unroll
            for (int e = 0; e < 4; e++)
                w[e] = bf2_fma(pack_bf16(h_lo(acc[i + 2 * e]), h_hi(acc[i + 2 * e])), up, w[e]);
            asm volatile("st.shared.v4.u32 [%4], {%0,%1,%2,%3};\n" ::"r"(w[0]), "r"(w[1]), "r"(w[2]), "r"(w[3]),
                         "r"(sx + (u >> 1) * 64 + (u & 1) * 4 * P2_XROW) : "memory");
        }
        p2_init(c < 6 ? acc0 : acc1, c, sb + (v[c & 1][1][0] & zero));
    }
}

__device__ __forceinline__ void p2_unpack(uint4& u, uint32_t o1, uint32_t o2, uint32_t o3) {
    u.z = o1 & 0xbff8bff8u;
    u.y = o2 & 0xbff8bff8u;
    u.w = o3 & 0xbff8bff8u;
    u.x = (__byte_perm(o1, 0, 0x2301) & 0x07400740u) | ((__byte_perm(o2, o3, 0x6240) << 3) & 0x38383838u) | ((__byte_perm(o2, o3, 0x3715) << 1) & 0x80808080u);
}
__device__ __forceinline__ uint32_t h2_mul(uint32_t a, uint32_t b) {
    uint32_t r;
    asm("mul.rn.f16x2 %0, %1, %2;\n" : "=r"(r) : "r"(a), "r"(b));
    return r;
}
__device__ __forceinline__ void p2_epilogue_add(const uint32_t (&acc)[48], uint8_t* o, uint32_t up, int zero) {
#pragma unroll
    for (int t = 0; t < 12; t++) {
        uint32_t v[4];
#pragma unroll
        for (int e = 0; e < 4; e++) {
            v[e] = acc[8 * (t >> 1) + (t & 1) + 2 * e];
            asm volatile("" : "+r"(v[e]));
            v[e] = bf2_mul(pack_bf16(h_lo(v[e]), h_hi(v[e])), up);
        }
        asm volatile("red.global.add.noftz.v4.bf16x2 [%0], {%1,%2,%3,%4};\n" ::"l"(o + (t >> 1) * 64 + (t & 1) * 4 * P2_XROW),
                     "r"(v[0]), "r"(v[1]), "r"(v[2]), "r"(v[3]) : "memory");
        if (t % 3 == 2) sched_break(zero);
    }
}

__global__ void __cluster_dims__(2, 1, 1) __launch_bounds__(512, 1)
pass2_kernel(const __grid_constant__ CUtensorMap wmap, const __nv_bfloat16* __restrict__ x, const __nv_bfloat16* __restrict__ w2,
             const __nv_bfloat16* __restrict__ grn_g, const __nv_bfloat16* __restrict__ grn_b, __nv_bfloat16* __restrict__ out, int zero) {
    extern __shared__ __align__(1024) uint8_t smem[];
    const uint32_t sbase = smem_u32(smem);
    const uint32_t bar_bfull = sbase + P2_OFF_BAR, bar_bempty = bar_bfull + P2_NB * 8;
    const uint32_t bar_afull = bar_bempty + P2_NB * 8, bar_aempty = bar_afull + 3 * P2_NA * 8;
    const uint32_t bar_xfull = bar_aempty + 3 * P2_NA * 8, bar_oready = bar_xfull + 8, s_pos = bar_xfull + 16;
    int tid;
    asm volatile("mov.u32 %0, %%tid.x;\n" : "=r"(tid));
    const int warp = __shfl_sync(0xffffffffu, tid >> 5, 0), lane = tid & 31;
    const uint32_t rank = cluster_rank();
    const int cl = blockIdx.x >> 1, pair = cl >> 1;
    const int k0 = (4 * pair + (cl & 1) * (48 - P2_POS % 48)) % 48;
    const int head = pair < P2_SHARED && !(cl & 1), tail = pair < P2_SHARED && (cl & 1);

    const bool small = blockIdx.x < NUM_CTAS - 8 * NGRP;
    uint32_t par, gg[4];
    auto early = [&]() {
        asm volatile("ld.global.cg.u32 %0, [%1];\n" : "=r"(par) : "l"(&g_epoch) : "memory");
#pragma unroll
        for (int i = 0; i < 4; i++) asm volatile("ld.global.nc.u16 %0, [%1];\n" : "=r"(gg[i]) : "l"(grn_g + tid + 384 * i) : "memory");
    };
    if (warp < 12) early();
    if (small && tid == 0) {
        for (int i = 0; i < 2 * P1_NST + 2; i++) mbar_init(sbase + P1_OFF_BAR + i * 8, (i & 12) == 4 ? 16 : 1);
        asm volatile("fence.mbarrier_init.release.cluster;\n" ::: "memory");
        p1_load_w1(sbase, &wmap, blockIdx.x * 2, 2);
    }
    if (small) TSTAMP(0, 0);
    TSTAMP(1, 0);
    if (tid == 384) {
        for (int i = 0; i < P2_NB; i++) {
            mbar_init(bar_bfull + i * 8, 1);
            mbar_init(bar_bempty + i * 8, 24);
        }
        for (int i = 0; i < 3 * P2_NA; i++) {
            mbar_init(bar_afull + i * 8, 1);
            mbar_init(bar_aempty + i * 8, 4);
        }
        mbar_init(bar_xfull, 2);
        mbar_init(bar_oready, 4);
        asm volatile("st.shared.u32 [%0], 0;\n" ::"r"(s_pos) : "memory");
        asm volatile("fence.mbarrier_init.release.cluster;\n" ::: "memory");
    }
    __syncthreads();
    cluster_sync_relaxed();

    if (warp >= 12) {
        reg_dec<32>();
        if (small) {
#pragma unroll 1
            for (int j = 0; warp == 12 && j < 2 * NSMALL; j++) {
                const uint32_t bar = sbase + P1_OFF_BAR + (j & 3) * 8;
                if (!(j & 1)) {
                    flag_wait<true>(&g_flag[LN_RING + 3 + (j >> 1)][0][0], 8);
                    asm volatile("fence.proxy.async.global;\n" ::: "memory");
                }
                mbar_wait(bar + P1_NST * 8, (j >> 2) & 1);
                if (elect_one()) {
                    mbar_expect_tx(bar, P1_SLOT);
                    bulk_g2s_mc(sbase + (j & 3) * P1_SLOT + rank * (P1_SLOT / 2),
                                reinterpret_cast<const uint8_t*>(g_ln) + (size_t)(2 * (LN_RING + 3) + j) * P1_SLOT + rank * (P1_SLOT / 2), P1_SLOT / 2, bar, (uint16_t)3);
                }
                __syncwarp();
            }
            asm volatile("barrier.cluster.arrive.aligned;\nbarrier.cluster.wait.aligned;\n" ::: "memory");
        }
        if (warp == 12) {
            const uint8_t* wsrc = reinterpret_cast<const uint8_t*>(g_w2img) + rank * (P2_B / 2);
            int st = 0, ph = 1, kb = k0, m = 0, r = 0;
            const int busy = head ? 0 : tail ? P2_POS - 24 : P2_POS;
#pragma unroll 1
            for (int p = 0; p < P2_POS; p++) {
                if (p == 0 || p == P2_FOLD) {
                    flag_wait<true>(&g_img[p != 0], p ? 96 * 4 : 48);
                    asm volatile("fence.proxy.async.global;\n" ::: "memory");
                    if (p) wsrc += sizeof(g_w2img[0]);
                }
                mbar_wait(bar_bempty + st * 8, ph);
                TR2P(p, 0);
                if (elect_one()) {
                    mbar_expect_tx(bar_bfull + st * 8, P2_B);
                    bulk_g2s_mc(sbase + st * P2_B + rank * (P2_B / 2), wsrc + kb * P2_B, P2_B / 2, bar_bfull + st * 8, (uint16_t)3);
                    asm volatile("st.volatile.shared.u32 [%0], %1;\n" ::"r"(s_pos), "r"(p) : "memory");
                    const int idle = 2 - min(m, P2_ITEMS - 1) + max(m - 2 + (r >= 48 - 2 * P2_LAG), 0) - ((unsigned)(p - busy) < 24);
                    if (idle) asm volatile("mbarrier.arrive.shared::cta.b64 _, [%0], %1;\n" ::"r"(bar_bempty + st * 8), "r"(idle * 8) : "memory");
                    if (rank == 0) asm volatile("red.relaxed.gpu.global.add.u32 [%0], 1;\n" ::"l"(&g_prog) : "memory");
                }
                __syncwarp();
                if (++st == P2_NB) { st = 0; ph ^= 1; }
                if (++kb == 48) kb = 0;
                if (++r == P2_LAG) { r = 0; m++; }
            }
            mbar_wait(bar_bempty + st * 8, ph);
            if (lane == 0) mbar_arrive(bar_bfull + st * 8);
#pragma unroll 1
            for (int p = 1; p < P2_NB; p++) {
                if (++st == P2_NB) { st = 0; ph ^= 1; }
                mbar_wait(bar_bempty + st * 8, ph);
            }
        } else if (warp == 13) {
            const uint8_t* src[3];
            int n[3], left[3], wrap[3];
            uint32_t st[3];
            auto item = [&](int w) {
                const int u = (k0 + p2_start(n[w])) % 48;
                left[w] = n[w] < 0 || n[w] == P2_ITEMS ? 24 : 48;
                wrap[w] = left[w] - (48 - u);
                src[w] = reinterpret_cast<const uint8_t*>(g_h) + (size_t)p2_tile(cl, n[w]) * (2 * H_TILE) + rank * H_HALF + u * H_STEP;
            };
#pragma unroll
            for (int w = 0; w < 3; w++) {
                n[w] = w == 2 && head ? -1 : w;
                st[w] = 0x80000000u;
                item(w);
            }
            flag_wait<true>(&g_img[2], (NUM_CTAS - 8 * NGRP) * 8);
            bar_arrive(3, 416);
            gdc_wait();
            asm volatile("fence.proxy.async.global;\n" ::: "memory");
#pragma unroll 1
            for (int fin = 0; fin < 3;) {
                bool idle = true;
#pragma unroll
                for (int w = 0; w < 3; w++) {
                    const uint32_t o = (st[w] & 0xff) + w * P2_NA * 8;
                    if (left[w] >= 0 && mbar_test(bar_aempty + o, st[w] >> 31)) {
                        idle = false;
                        if (left[w] == 0) {
                            if (lane == 0) mbar_arrive(bar_afull + o);
                            left[w] = -1;
                            fin++;
                        } else {
                            if (elect_one()) {
                                mbar_expect_tx(bar_afull + o, P2_A);
                                bulk_g2s(sbase + P2_OFF_A + o * (P2_A / 8), src[w], P2_A, bar_afull + o);
                            }
                            __syncwarp();
                            src[w] += H_STEP;
                            st[w] += 8;
                            if ((st[w] & 0xff) == P2_NA * 8) st[w] ^= 0x80000000u | (P2_NA * 8);
                            if (--left[w] == wrap[w]) src[w] -= 48 * H_STEP;
                            if (left[w] == 0 && (n[w] += 3) < P2_ITEMS + tail) item(w);
                        }
                    }
                }
                if (idle) __nanosleep(64);
                SAFE_BREAK
            }
        } else if (warp == 14) {
            const uint32_t sx = sbase + P2_OFF_X;
            size_t o = 0;
            auto pace = [&](int target) {
                int v;
                while (true) {
                    asm volatile("ld.volatile.shared.u32 %0, [%1];\n" : "=r"(v) : "r"(s_pos) : "memory");
                    if (v * 16 >= target) break;
                    __nanosleep(100);
                    SAFE_BREAK
                }
            };
#pragma unroll 1
            for (int n = -head; n <= P2_ITEMS; n++) {
                const size_t on = (size_t)(2 * p2_tile(cl, n) + rank) * (64 * C_DIM * 2);
                const bool st = n + head > 0, ld = n < P2_ITEMS;
                if (st) mbar_wait(bar_oready, (n - 1 + head) & 1);
                TR2P(n + 1, 1);
                if (lane == 0) {
                    if (n == 1 && head) {
                        asm volatile("cp.async.bulk.wait_group 0;\nfence.proxy.async.global;\n" ::: "memory");
                        asm volatile("st.release.gpu.global.u32 [%0], 1;\n" ::"l"(&g_half[pair][rank]) : "memory");
                    }
                    if (ld) mbar_expect_tx(bar_xfull, 64 * C_DIM * 2);
                    const bool paced = st && n < P2_ITEMS - 1;
                    int t = (P2_LAG * (n - 1) + 52) * 16;
#pragma unroll 1
                    for (int c = 0; st && c < 64 * P2_XROW; c += P2_XC) {
                        if (paced) pace(t += 11);
                        bulk_s2g(reinterpret_cast<uint8_t*>(out) + o + c, sx + c + (c >= 32 * P2_XROW ? 64 : 0), P2_XC);
                        asm volatile("cp.async.bulk.commit_group;\n" ::: "memory");
                    }
#pragma unroll 1
                    for (int c = 0; ld && c < 64 * P2_XROW; c += P2_XC) {
                        if (c == 0) asm volatile("cp.async.bulk.wait_group.read 4;\n" ::: "memory");
                        if (c == 32 * P2_XROW) asm volatile("cp.async.bulk.wait_group.read 0;\n" ::: "memory");
                        if (paced) pace(t += 11);
                        bulk_g2s(sx + c + (c >= 32 * P2_XROW ? 64 : 0), reinterpret_cast<const uint8_t*>(x) + on + c, P2_XC, bar_xfull);
                    }
                    TR2P(n + 1, 2);
                    if (rank == 0 && n > 0 && n < P2_ITEMS - 2)
                        flag_wait<false>(&g_prog, P2_NCL * (P2_LAG * n + 48) + (tail ? P2_SHARED - P2_NCL : P2_SHARED) * P2_DELTA);
                    if (ld) mbar_arrive(bar_xfull);
                    TR2P(n + 1, 3);
                }
                __syncwarp();
                o = on;
            }
            asm volatile("cp.async.bulk.wait_group 0;\n" ::: "memory");
            TR2P(30, 1);
        }
    } else {
        reg_inc<160>();
        if (small) {
            if (warp < 8) p1_compute<2, 2>(sbase, blockIdx.x * 2, warp, lane, zero);
            else p1_w2(w2, grn_b, warp & 3, lane);
            asm volatile("barrier.cluster.arrive.aligned;\nbarrier.cluster.wait.aligned;\n" ::: "memory");
            TSTAMP(0, 30);
            early();
        }
        const int wg = warp >> 2, w = warp & 3, g = lane >> 2, q = lane & 3;
        const uint32_t sx = sbase + P2_OFF_X + (g & 1) * P2_XHALF + (w * 8 + (g >> 1)) * P2_XROW + q * 16;
        const uint32_t af = bar_afull + wg * P2_NA * 8;
        const uint32_t s_a = sbase + P2_OFF_A + wg * P2_NA * P2_A + (lane >> 3) * 512 + (lane & 7) * 64 +
                             ((w ^ ((lane & 7) >> 1)) << 4);
        uint32_t acc0[48], acc1[48];
        uint32_t up;
        uint4 a0[2], a1[2];
        uint32_t st = 0, ph = 0;

        {
            float4* s_red = reinterpret_cast<float4*>(smem + P2_OFF_RED);
            const float* sums = g_sums[par & 1];
            float gx[4], part = 0.f, mx = 0.f;
            asm volatile("prefetch.global.L2 [%0];\n" ::"l"(sums + HID + tid * 2) : "memory");
            TSTAMP(1, 27);
            bar_sync(3, 416);
            gdc_wait();
            TSTAMP(1, 1);
#pragma unroll
            for (int i = 0; i < 4; i++) gx[i] = __ldcg(sums + tid + 384 * i);
            const float bias = __ldcg(sums + HID + tid), asum = __ldcg(sums + HID + C_DIM + tid);
            float z = __uint_as_float(__reduce_max_sync(0xffffffffu, __float_as_uint(asum)));
            uint32_t bm = __reduce_max_sync(0xffffffffu, __float_as_uint(fabsf(bias)));
#pragma unroll
            for (int i = 0; i < 4; i++) {
                asm("sqrt.approx.f32 %0, %1;\n" : "=f"(gx[i]) : "f"(fmaf(gx[i], HSCALE * HSCALE, 1e-6f)));
                part += gx[i];
                gx[i] *= bf_lo(gg[i]);
                mx = fmaxf(mx, fabsf(gx[i]));
            }
#pragma unroll
            for (int o = 16; o > 0; o >>= 1) part += __shfl_xor_sync(0xffffffffu, part, o);
            mx = __uint_as_float(__reduce_max_sync(0xffffffffu, __float_as_uint(mx)));
            TSTAMP(1, 26);
            if (lane == 0) s_red[warp] = make_float4(part, mx, z, __uint_as_float(bm));
            bar_sync(1, 384);
            float tot = 0.f;
            {
                const float4 t = s_red[min(lane & 15, 11)];
                tot = (lane & 15) < 12 ? t.x : 0.f;
#pragma unroll
                for (int o = 8; o > 0; o >>= 1) tot += __shfl_xor_sync(0xffffffffu, tot, o);
                mx = __uint_as_float(__reduce_max_sync(0xffffffffu, __float_as_uint(t.y)));
                z = __uint_as_float(__reduce_max_sync(0xffffffffu, __float_as_uint(t.z)));
                bm = __reduce_max_sync(0xffffffffu, __float_as_uint(t.w));
            }
            const float inv = __fdividef(1.0f, fmaf(tot, 1.0f / HID, 1e-6f));
            const uint32_t e0 = acc_exp(z) - 9u;
            const uint32_t j = min(max(max(__float_as_uint(fmaf(mx, inv, 1.0f) * 1.01f) >> 23, 130u) - 130u, max(bm >> 23, e0 + 12u) - (e0 + 12u)), 126u);
            const float dn = __uint_as_float((127u - j) << 23) * (HSCALE * 1.00235f);
#pragma unroll
            for (int i = 0; i < 4; i++)
                *reinterpret_cast<uint16_t*>(smem + P2_OFF_GRN + (tid + 384 * i) * 2) = pack_f16(fmaf(gx[i], inv, 1.0f) * dn, 0.f);
            const uint32_t e = min(e0 + j, 253u);
            up = e * 0x00800080u;
#pragma unroll
            for (int i = 0; i < 2; i++)
                *reinterpret_cast<uint16_t*>(smem + P2_OFF_BIAS + (tid >> 1) * 8 + i * 4 + (tid & 1) * 2) = pack_f16(bias * __uint_as_float((254u - e) << 23), 0.f);
            TSTAMP(1, 25);
            bar_sync(1, 384);
            if (wg == 1 && blockIdx.x < 96) {
                const uint4* src = g_w2img[0] + blockIdx.x * 768 + tid - 128;
                const uint4 fk = *reinterpret_cast<const uint4*>(smem + P2_OFF_GRN + blockIdx.x * 32 + (tid & 8) * 2);
                uint4 v[6];
#pragma unroll
                for (int i = 0; i < 6; i++) v[i] = __ldcg(src + i * 128);
                auto fold = [&](uint32_t b, uint32_t f) { return (h2_mul(b, f) + 0x00040004u) & 0xfff8fff8u; };
#pragma unroll
                for (int i = 0; i < 6; i++)
                    g_w2img[1][blockIdx.x * 768 + tid - 128 + i * 128] = make_uint4(fold(v[i].x, fk.x), fold(v[i].y, fk.y), fold(v[i].z, fk.z), fold(v[i].w, fk.w));
                asm volatile("fence.proxy.async.global;\n" ::: "memory");
                __threadfence();
                __syncwarp();
                if (lane == 0) asm volatile("red.release.gpu.global.add.u32 [%0], 1;\n" ::"l"(&g_img[1]) : "memory");
            }
        }
        TSTAMP(1, 28);
        int kt = k0, pos;
        const uint32_t be = lane < 2 ? mapa(bar_bempty, lane) : 0, be0 = mapa(bar_bempty, 0);
        uint32_t prev = 0, sa = 0, pa = 0;
        auto release_b = [&](uint32_t p, bool on) {
            asm volatile("{\n.reg .pred p, q;\nsetp.ne.u32 q, %2, 0;\nsetp.ne.and.u32 p, %1, 0, q;\n@p mbarrier.arrive.shared::cluster.b64 _, [%0];\n}\n"
                         ::"r"(be + p), "r"(be), "r"((uint32_t)on) : "memory");
        };
        auto arrive1 = [&](uint32_t bar) {
            asm volatile("{\n.reg .pred p;\nsetp.eq.u32 p, %1, %2;\n@p mbarrier.arrive.shared::cta.b64 _, [%0];\n}\n" ::"r"(bar), "r"(be), "r"(be0) : "memory");
        };
        auto seek = [&](int p) {
            pos = p;
            st = p % P2_NB * 8;
            ph = p / P2_NB & 1;
            int v;
            while (true) {
                asm volatile("ld.volatile.shared.u32 %0, [%1];\n" : "=r"(v) : "r"(s_pos) : "memory");
                if (__all_sync(0xffffffffu, v >= p)) break;
                __nanosleep(200);
                SAFE_BREAK
            }
        };
        bool ok_a = false;
        auto fetch = [&](uint4 (&a)[2], uint32_t done, bool rel, bool early, bool wait = true) {
            if (!ok_a) mbar_wait(af + sa, pa);
            uint32_t o[6];
            const uint32_t src = s_a + sa * (P2_A / 8);
            asm volatile("ldmatrix.sync.aligned.m8n8.x4.trans.shared.b16 {%0,%1,%2,%3}, [%4];\n"
                         : "=r"(o[0]), "=r"(o[1]), "=r"(o[2]), "=r"(o[3]) : "r"(src) : "memory");
            asm volatile("ldmatrix.sync.aligned.m8n8.x2.trans.shared.b16 {%0,%1}, [%2];\n"
                         : "=r"(o[4]), "=r"(o[5]) : "r"(src + 2048) : "memory");
            if ((sa += 8) == P2_NA * 8) { sa = 0; pa ^= 1; }
            if (wait) wg_wait<1>();
            asm volatile("" ::"r"(a[0].x), "r"(a[0].y), "r"(a[0].z), "r"(a[0].w), "r"(a[1].x), "r"(a[1].y), "r"(a[1].z), "r"(a[1].w));
            release_b(done, rel);
            ok_a = mbar_test(af + sa, pa);
            const bool ok_b = mbar_test(bar_bfull + st, ph);
            p2_unpack(a[0], o[0], o[1], o[2]);
            p2_unpack(a[1], o[3], o[4], o[5]);
            if (early) {
                const uint32_t* t = reinterpret_cast<const uint32_t*>(smem + P2_OFF_GRN) + kt * 16 + q;
#pragma unroll
                for (int i = 0; i < 2; i++)
                    a[i] = make_uint4(h2_mul(a[i].x, t[8 * i]), h2_mul(a[i].y, t[8 * i]), h2_mul(a[i].z, t[8 * i + 4]), h2_mul(a[i].w, t[8 * i + 4]));
                if (++kt == 48) kt = 0;
            }
            if (!ok_b) mbar_wait(bar_bfull + st, ph);
        };
        const uint64_t db0 = make_desc(sbase, 128, 256);
        auto step = [&](const uint4 (&a)[2], uint4 (&an)[2], bool cont, bool add, bool early) {
            TR2(0);
            const uint64_t db = db0 + st * (P2_B / 128);
            wg_fence();
            mma_rs_n192(acc0, a[0], db, add);
            mma_rs_n192(acc1, a[0], db + 384, add);
            mma_rs_n192(acc0, a[1], db + 768, 1);
            mma_rs_n192(acc1, a[1], db + 768 + 384, 1);
            wg_commit();
            arrive1(af + 3 * P2_NA * 8 - 8 + (sa ? sa : P2_NA * 8));
            const uint32_t done = prev;
            prev = st;
            if ((st += 8) == P2_NB * 8) { st = 0; ph ^= 1; }
            fetch(an, done, cont, early);
            pos++;
        };
        int n = wg == 2 && head ? -1 : wg;
#pragma unroll
        for (int c = 0; c < 12; c++) p2_init(c < 6 ? acc0 : acc1, c, sbase + P2_OFF_BIAS + q * 32);
        a0[0] = a0[1] = a1[0] = a1[1] = make_uint4(zero, zero, zero, zero);
        seek(p2_start(n));
        fetch(a0, 0, false, n <= 0, false);
#pragma unroll 1
        for (;; n += 3) {
            TSTAMP(1, 2 + n);
            const int p0 = n < 0 || n == P2_ITEMS ? 12 : 0, pe = n <= 0 ? p0 + P2_FOLD / 2 : 0;
            const bool more = n + 3 < P2_ITEMS + tail;
#pragma unroll 1
            for (int p = p0; p < 24; p++) {
                step(a0, a1, p != p0, p != p0 || n != P2_ITEMS, p < pe);
                step(a1, a0, true, true, p < pe);
            }
            if (n == P2_ITEMS) {
                flag_wait<true>(&g_half[pair][rank], 1);
                TR2(1);
                wg_wait<0>();
                TR2(2);
                release_b(prev, true);
                uint8_t* o = reinterpret_cast<uint8_t*>(out) + (size_t)((2 * p2_tile(cl, -1) + rank) * 64 + (g & 1) * 32 + w * 8 + (g >> 1)) * P2_XROW + q * 16;
                p2_epilogue_add(acc0, o, up, zero);
                p2_epilogue_add(acc1, o + 384, up, zero);
                TR2(3);
                break;
            }
            mbar_wait(bar_xfull, (n + head) & 1);
            TR2(1);
            wg_wait<0>();
            TR2(2);
            release_b(prev, true);
            p2_epilogue(acc0, acc1, sx, sbase + P2_OFF_BIAS + q * 32, up, zero);
            TR2(3);
            asm volatile("fence.proxy.async.shared::cta;\n" ::: "memory");
            __syncwarp();
            arrive1(bar_oready);
            if (!more) break;
            ok_a = false;
            seek(p2_start(n + 3));
            mbar_wait(bar_bfull + st, ph);
        }
        if (blockIdx.x == 120 && threadIdx.x < (LN_RING + 3 + NSMALL) * 2) (&g_flag[0][0][0])[threadIdx.x * 8] = 0;
        if (blockIdx.x == 121 && threadIdx.x == 0) atomicAdd(&g_epoch, 1u);
        TSTAMP(1, 30);
    }
}

}

extern "C" void kernel_launch(void* const* d_in, const int* in_sizes, int n_in, void* d_out, int out_size) {
    const __nv_bfloat16* x = (const __nv_bfloat16*)d_in[0];
    const __nv_bfloat16* dw = (const __nv_bfloat16*)d_in[1];
    const __nv_bfloat16* w1 = (const __nv_bfloat16*)d_in[2];
    const __nv_bfloat16* w2 = (const __nv_bfloat16*)d_in[3];
    const __nv_bfloat16* grn_g = (const __nv_bfloat16*)d_in[4];
    const __nv_bfloat16* grn_b = (const __nv_bfloat16*)d_in[5];
    __nv_bfloat16* out = (__nv_bfloat16*)d_out;

    cudaFuncSetAttribute(pass1_kernel<2>, cudaFuncAttributeMaxDynamicSharedMemorySize, P1_SMEM);
    cudaFuncSetAttribute(pass1_kernel<8>, cudaFuncAttributeMaxDynamicSharedMemorySize, P1_SMEM);
    cudaFuncSetAttribute(pass2_kernel, cudaFuncAttributeMaxDynamicSharedMemorySize, P2_SMEM);

    typedef CUresult (*EncodeFn)(CUtensorMap*, CUtensorMapDataType, cuuint32_t, void*, const cuuint64_t*, const cuuint64_t*,
                                 const cuuint32_t*, const cuuint32_t*, CUtensorMapInterleave, CUtensorMapSwizzle,
                                 CUtensorMapL2promotion, CUtensorMapFloatOOBfill);
    static EncodeFn encode = nullptr;
    if (!encode) {
        cudaDriverEntryPointQueryResult qres;
        cudaGetDriverEntryPoint("cuTensorMapEncodeTiled", (void**)&encode, cudaEnableDefault, &qres);
    }
    CUtensorMap wmap;
    const cuuint64_t gdim[2] = {HID, C_DIM};
    const cuuint64_t gstr[1] = {HID * 2};
    const cuuint32_t box[2] = {64, 192}, estr[2] = {1, 1};
    CUresult er = encode(&wmap, CU_TENSOR_MAP_DATA_TYPE_BFLOAT16, 2, (void*)w1, gdim, gstr, box, estr, CU_TENSOR_MAP_INTERLEAVE_NONE,
           CU_TENSOR_MAP_SWIZZLE_128B, CU_TENSOR_MAP_L2_PROMOTION_L2_128B, CU_TENSOR_MAP_FLOAT_OOB_FILL_NONE);
    if (er != CUDA_SUCCESS) printf("tensor map encode failed %d\n", (int)er);

    cudaLaunchAttribute attr[1];
    attr[0].id = cudaLaunchAttributeProgrammaticStreamSerialization;
    attr[0].val.programmaticStreamSerializationAllowed = 1;
    cudaLaunchConfig_t cfg = {};
    cfg.stream = 0;
    cfg.blockDim = dim3(512);
    cfg.dynamicSmemBytes = P1_SMEM;
    static int wide = -1;
    if (wide < 0) {
        int n = 0;
        cfg.gridDim = dim3(8 * NGRP);
        wide = cudaOccupancyMaxActiveClusters(&n, pass1_kernel<8>, &cfg) == cudaSuccess && n >= NGRP;
    }
    if (wide) pass1_kernel<8><<<8 * NGRP, 512, P1_SMEM>>>(wmap, x, dw, w1, 0);
    else pass1_kernel<2><<<8 * NGRP, 512, P1_SMEM>>>(wmap, x, dw, w1, 0);
    cfg.attrs = attr;
    cfg.numAttrs = 1;
    cfg.gridDim = dim3(NUM_CTAS);
    cfg.dynamicSmemBytes = P2_SMEM;
    cudaLaunchKernelEx(&cfg, pass2_kernel, wmap, x, w2, grn_g, grn_b, out, 0);
}
```

```cpp
#include <cuda.h>
#include <cuda_runtime.h>
#include <cuda_bf16.h>
#include <stdint.h>
#include <stdio.h>

namespace {

constexpr int M_TOTAL = 384 * 384;
constexpr int C_DIM   = 384;
constexpr int HID     = 1536;
constexpr int NT128   = M_TOTAL / 128;
constexpr int NUM_CTAS = 132;

constexpr int NGRP = 15, NSMALL = 100;
constexpr int LN_STEP = 2 * NGRP, LN_RING = 2 * LN_STEP;
__device__ __forceinline__ int p1_tile(int t) { return t < LN_STEP ? t : t + min((t - LN_STEP) / 10 + 1, NSMALL); }
__device__ __forceinline__ int p1_place(int tile, int slot) {
    const int i = (tile + 3) / 11;
    return i * 11 == tile + 3 && (unsigned)(i - 3) < NSMALL ? LN_RING + i : slot;
}
constexpr int LN_TILE = 128 * C_DIM * 2;
constexpr int H_TILE = 64 * HID * 3 / 2;
constexpr int H_HALF = 3072, H_STEP = 6144;

__device__ __align__(1024) uint4 g_h[(size_t)M_TOTAL * HID * 3 / 32];
__device__ __align__(1024) uint4 g_ln[(LN_RING + 3 + NSMALL) * LN_TILE / 16];
__device__ __align__(1024) uint4 g_w2img[2][HID * C_DIM * 2 / 16];
__device__ __align__(16) float g_sums[2][HID + 2 * C_DIM];
__device__ __align__(16) unsigned g_ex[HID];
__device__ unsigned g_epoch;
__device__ __align__(128) unsigned g_img[3];
__device__ __align__(128) unsigned g_prog;
__device__ __align__(128) unsigned g_half[32][2];
__device__ unsigned g_flag[LN_RING + 3 + NSMALL][2][8];
#define TSTAMP(k, i)
#define STAMPT(t, i)
#define TRACE(wg, pos, i)
#define TRACEW(pos, i)

#define TR2(i)
#define TR2P(pos, i)
__host__ __device__ __forceinline__ int perm32(int n) {
    return (n & ~31) | (((n >> 1) & 3) << 3) | (((n >> 3) & 3) << 1) | (n & 1);
}

__device__ __forceinline__ uint32_t smem_u32(const void* p) { return (uint32_t)__cvta_generic_to_shared(p); }

__device__ __forceinline__ void mbar_init(uint32_t bar, uint32_t count) {
    asm volatile("mbarrier.init.shared::cta.b64 [%0], %1;\n" ::"r"(bar), "r"(count) : "memory");
}
__device__ __forceinline__ void mbar_expect_tx(uint32_t bar, uint32_t bytes) {
    asm volatile("mbarrier.arrive.expect_tx.shared::cta.b64 _, [%0], %1;\n" ::"r"(bar), "r"(bytes) : "memory");
}
__device__ __forceinline__ void mbar_arrive(uint32_t bar) {
    asm volatile("mbarrier.arrive.shared::cta.b64 _, [%0];\n" ::"r"(bar) : "memory");
}
__device__ __forceinline__ void mbar_arrive_cluster(uint32_t bar_cluster_addr) {
    asm volatile("mbarrier.arrive.shared::cluster.b64 _, [%0];\n" ::"r"(bar_cluster_addr) : "memory");
}
#define SAFE_BREAK
__device__ __forceinline__ void mbar_wait(uint32_t bar, uint32_t parity) {
    asm volatile(
        "{\n"
        ".reg .pred p;\n"
        "LAB_WAIT:\n"
        "mbarrier.try_wait.parity.shared::cta.b64 p, [%0], %1;\n"
        "@!p bra LAB_WAIT;\n"
        "}\n" ::"r"(bar), "r"(parity) : "memory");
}
__device__ __forceinline__ bool mbar_test(uint32_t bar, uint32_t parity) {
    uint32_t ok;
    asm volatile("{\n.reg .pred p;\n"
                 "mbarrier.test_wait.parity.shared::cta.b64 p, [%1], %2;\n"
                 "selp.u32 %0, 1, 0, p;\n}\n" : "=r"(ok) : "r"(bar), "r"(parity) : "memory");
    return ok != 0;
}
__device__ __forceinline__ uint32_t mapa(uint32_t addr, uint32_t rank) {
    uint32_t r;
    asm volatile("mapa.shared::cluster.u32 %0, %1, %2;\n" : "=r"(r) : "r"(addr), "r"(rank));
    return r;
}
__device__ __forceinline__ void bulk_g2s(uint32_t dst, const void* src, uint32_t bytes, uint32_t bar) {
    asm volatile("cp.async.bulk.shared::cluster.global.mbarrier::complete_tx::bytes [%0], [%1], %2, [%3];\n"
                 ::"r"(dst), "l"(src), "r"(bytes), "r"(bar) : "memory");
}
__device__ __forceinline__ void bulk_g2s_mc(uint32_t dst, const void* src, uint32_t bytes, uint32_t bar, uint16_t mask) {
    asm volatile("cp.async.bulk.shared::cluster.global.mbarrier::complete_tx::bytes.multicast::cluster [%0], [%1], %2, [%3], %4;\n"
                 ::"r"(dst), "l"(src), "r"(bytes), "r"(bar), "h"(mask) : "memory");
}
__device__ __forceinline__ void tma2(uint32_t dst, const CUtensorMap* map, int c0, int c1, uint32_t bar) {
    asm volatile("cp.async.bulk.tensor.2d.shared::cluster.global.tile.mbarrier::complete_tx::bytes [%0], [%1, {%2, %3}], [%4];\n"
                 ::"r"(dst), "l"(map), "r"(c0), "r"(c1), "r"(bar) : "memory");
}
template <bool ACQ>
__device__ __forceinline__ uint32_t flag_wait(const unsigned* p, unsigned target) {
    unsigned v, n = 0;
    do {
        if (ACQ) asm volatile("ld.acquire.gpu.global.u32 %0, [%1];\n" : "=r"(v) : "l"(p) : "memory");
        else asm volatile("ld.relaxed.gpu.global.u32 %0, [%1];\n" : "=r"(v) : "l"(p) : "memory");
        n++;
    } while (v < target);
    return n == 1;
}
__device__ __forceinline__ void ldsm4t(uint32_t (&r)[4], uint32_t addr) {
    asm volatile("ldmatrix.sync.aligned.m8n8.x4.trans.shared.b16 {%0,%1,%2,%3}, [%4];\n"
                 : "=r"(r[0]), "=r"(r[1]), "=r"(r[2]), "=r"(r[3]) : "r"(addr) : "memory");
}
__device__ __forceinline__ void bulk_s2g(void* dst, uint32_t src, uint32_t bytes) {
    asm volatile("cp.async.bulk.global.shared::cta.bulk_group [%0], [%1], %2;\n" ::"l"(dst), "r"(src), "r"(bytes) : "memory");
}
__device__ __forceinline__ void cluster_sync_relaxed() {
    asm volatile("barrier.cluster.arrive.relaxed.aligned;\nbarrier.cluster.wait.aligned;\n" ::: "memory");
}
__device__ __forceinline__ void gdc_wait() { asm volatile("griddepcontrol.wait;\n" ::: "memory"); }
__device__ __forceinline__ void gdc_launch() { asm volatile("griddepcontrol.launch_dependents;\n" ::: "memory"); }
__device__ __forceinline__ uint32_t cluster_rank() {
    uint32_t r;
    asm volatile("mov.u32 %0, %%cluster_ctarank;\n" : "=r"(r));
    return r;
}
__device__ __forceinline__ bool elect_one() {
    uint32_t pred;
    asm volatile("{\n.reg .pred p;\nelect.sync _|p, 0xffffffff;\nselp.u32 %0, 1, 0, p;\n}\n" : "=r"(pred));
    return pred != 0;
}
__device__ __forceinline__ void wg_fence() { asm volatile("wgmma.fence.sync.aligned;\n" ::: "memory"); }
__device__ __forceinline__ void wg_commit() { asm volatile("wgmma.commit_group.sync.aligned;\n" ::: "memory"); }
template <int N> __device__ __forceinline__ void wg_wait() {
    asm volatile("wgmma.wait_group.sync.aligned %0;\n" ::"n"(N) : "memory");
}
template <int R> __device__ __forceinline__ void reg_inc() { asm volatile("setmaxnreg.inc.sync.aligned.u32 %0;\n" ::"n"(R)); }
template <int R> __device__ __forceinline__ void reg_dec() { asm volatile("setmaxnreg.dec.sync.aligned.u32 %0;\n" ::"n"(R)); }
__device__ __forceinline__ void bar_sync(int id, int n) { asm volatile("bar.sync %0, %1;\n" ::"r"(id), "r"(n) : "memory"); }
__device__ __forceinline__ void bar_arrive(int id, int n) { asm volatile("bar.arrive %0, %1;\n" ::"r"(id), "r"(n) : "memory"); }

__device__ __forceinline__ uint64_t make_desc(uint32_t saddr, uint32_t lbo, uint32_t sbo) {
    return (uint64_t)((saddr & 0x3FFFF) >> 4) | ((uint64_t)(lbo >> 4) << 16) | ((uint64_t)(sbo >> 4) << 32);
}

__device__ __forceinline__ void stg128_cs(void* p, uint32_t a, uint32_t b, uint32_t c, uint32_t d) {
    asm volatile("st.global.cs.v4.u32 [%0], {%1,%2,%3,%4};\n" ::"l"(p), "r"(a), "r"(b), "r"(c), "r"(d) : "memory");
}
__device__ __forceinline__ uint32_t pack_bf16(float lo, float hi) {
    uint32_t r;
    asm("cvt.rn.bf16x2.f32 %0, %1, %2;\n" : "=r"(r) : "f"(hi), "f"(lo));
    return r;
}
__device__ __forceinline__ float bf_lo(uint32_t v) { return __uint_as_float(v << 16); }
__device__ __forceinline__ float bf_hi(uint32_t v) { return __uint_as_float(v & 0xffff0000u); }
__device__ __forceinline__ uint32_t bf2_mul(uint32_t a, uint32_t b) {
    uint32_t r;
    asm("mul.rn.bf16x2 %0, %1, %2;\n" : "=r"(r) : "r"(a), "r"(b));
    return r;
}
__device__ __forceinline__ uint32_t bf2_fma(uint32_t a, uint32_t b, uint32_t c) {
    uint32_t r;
    asm("fma.rn.bf16x2 %0, %1, %2, %3;\n" : "=r"(r) : "r"(a), "r"(b), "r"(c));
    return r;
}
__device__ __forceinline__ uint32_t bf2_add(uint32_t a, uint32_t b) {
    uint32_t r;
    asm("add.rn.bf16x2 %0, %1, %2;\n" : "=r"(r) : "r"(a), "r"(b));
    return r;
}
constexpr float KAPPA = 0.3292034911525734f;
constexpr float GELU_C = 2.423681954311584f;
constexpr float HSCALE = 1.0f / (2.0f * KAPPA);
__device__ __forceinline__ uint32_t acc_exp(float z) { return max(__float_as_uint(z) >> 23, 10u); }
__device__ __forceinline__ void sched_break(int zero) {
    asm volatile("{\n.reg .pred p;\nsetp.ne.s32 p, %0, 0;\nSB_LOOP:\n@p nanosleep.u32 1;\n@p bra SB_LOOP;\n}\n" ::"r"(zero));
}

#define ACCR8(d, o) "+r"(d[o + 0]), "+r"(d[o + 1]), "+r"(d[o + 2]), "+r"(d[o + 3]), "+r"(d[o + 4]), "+r"(d[o + 5]), "+r"(d[o + 6]), "+r"(d[o + 7])
__device__ __forceinline__ void mma_rs_n128(uint32_t (&d)[32], const uint32_t (&a)[4], uint64_t desc, int scale_d) {
    asm volatile(
        "{\n.reg .pred p;\nsetp.ne.b32 p, %37, 0;\n"
        "wgmma.mma_async.sync.aligned.m64n128k16.f16.f16.f16 "
        "{%0,%1,%2,%3,%4,%5,%6,%7,%8,%9,%10,%11,%12,%13,%14,%15,"
        "%16,%17,%18,%19,%20,%21,%22,%23,%24,%25,%26,%27,%28,%29,%30,%31},"
        "{%32,%33,%34,%35}, %36, p, 1, 1, 0;\n}\n"
        : ACCR8(d, 0), ACCR8(d, 8), ACCR8(d, 16), ACCR8(d, 24)
        : "r"(a[0]), "r"(a[1]), "r"(a[2]), "r"(a[3]), "l"(desc), "r"(scale_d));
}
__device__ __forceinline__ void mma_ss_n128(uint32_t (&d)[32], uint64_t da, uint64_t db) {
    asm volatile(
        "{\n.reg .pred p;\nsetp.ne.b32 p, %34, 0;\n"
        "wgmma.mma_async.sync.aligned.m64n128k16.f16.f16.f16 "
        "{%0,%1,%2,%3,%4,%5,%6,%7,%8,%9,%10,%11,%12,%13,%14,%15,"
        "%16,%17,%18,%19,%20,%21,%22,%23,%24,%25,%26,%27,%28,%29,%30,%31},"
        "%32, %33, p, 1, 1, 0, 0;\n}\n"
        : ACCR8(d, 0), ACCR8(d, 8), ACCR8(d, 16), ACCR8(d, 24)
        : "l"(da), "l"(db), "r"(1));
}
__device__ __forceinline__ uint32_t bf2_as_h2(uint32_t v) { return (v & 0x0fff0fffu) * 7u + v; }
__device__ __forceinline__ float h_lo(uint32_t v) {
    float r;
    asm("{\n.reg .b16 l, h;\nmov.b32 {l, h}, %1;\ncvt.f32.f16 %0, l;\n}\n" : "=f"(r) : "r"(v));
    return r;
}
__device__ __forceinline__ float h_hi(uint32_t v) {
    float r;
    asm("{\n.reg .b16 l, h;\nmov.b32 {l, h}, %1;\ncvt.f32.f16 %0, h;\n}\n" : "=f"(r) : "r"(v));
    return r;
}

__device__ __forceinline__ void mma_rs_n192(uint32_t (&d)[48], const uint4& a, uint64_t db, int scale_d) {
    asm volatile(
        "{\n.reg .pred p;\nsetp.ne.b32 p, %53, 0;\n"
        "wgmma.mma_async.sync.aligned.m64n192k16.f16.f16.f16 "
        "{%0,%1,%2,%3,%4,%5,%6,%7,%8,%9,%10,%11,%12,%13,%14,%15,"
        "%16,%17,%18,%19,%20,%21,%22,%23,%24,%25,%26,%27,%28,%29,%30,%31,"
        "%32,%33,%34,%35,%36,%37,%38,%39,%40,%41,%42,%43,%44,%45,%46,%47},"
        "{%48,%49,%50,%51}, %52, p, 1, 1, 0;\n}\n"
        : ACCR8(d, 0), ACCR8(d, 8), ACCR8(d, 16), ACCR8(d, 24), ACCR8(d, 32), ACCR8(d, 40)
        : "r"(a.x), "r"(a.y), "r"(a.z), "r"(a.w), "l"(db), "r"(scale_d));
}

__device__ __forceinline__ uint32_t pack_f16(float lo, float hi) {
    uint32_t r;
    asm("cvt.rn.f16x2.f32 %0, %1, %2;\n" : "=r"(r) : "f"(hi), "f"(lo));
    return r;
}

constexpr int P1_IMG = 900;
constexpr int P1_SLOT = LN_TILE / 2, P1_NST = 4;
constexpr int P1_X = 16 * C_DIM * 2;
constexpr int P1_OFF_A = P1_SLOT * P1_NST;
constexpr int P1_OFF_DW = P1_OFF_A + 3 * 2048;
constexpr int P1_OFF_X = P1_OFF_DW + C_DIM * 2;
constexpr int P1_OFF_BAR = P1_OFF_X + 2 * P1_X;
constexpr int P1_OFF_TILE = P1_OFF_BAR + (2 * P1_NST + 3 + 2 + 3 + 2) * 8;
constexpr int P1_SMEM = P1_OFF_TILE + 64;

__device__ __forceinline__ float rsqrt_fast(float x) {
    float r;
    asm("rsqrt.approx.ftz.f32 %0, %1;\n" : "=f"(r) : "f"(x));
    return r;
}
__device__ __forceinline__ float sum8(const uint32_t (&c)[4]) {
    const uint32_t u = bf2_add(bf2_add(c[0], c[1]), bf2_add(c[2], c[3]));
    return bf_lo(u) + bf_hi(u);
}
__device__ __forceinline__ void lds128(uint32_t (&v)[4], uint32_t a) {
    asm volatile("ld.shared.v4.u32 {%0,%1,%2,%3}, [%4];\n" : "=r"(v[0]), "=r"(v[1]), "=r"(v[2]), "=r"(v[3]) : "r"(a) : "memory");
}
template <class F>
__device__ __forceinline__ void ln_row(uint32_t (&v)[6][4], uint32_t sdw, F after_loads) {
    uint32_t c[4], s[4], d[4], nm;
#pragma unroll
    for (int i = 0; i < 6; i++) {
        lds128(d, sdw + i * 128);
        if (i == 0) {
#pragma unroll
            for (int k = 0; k < 4; k++) c[k] = bf2_mul(v[0][k], d[k]);
            const float p = sum8(c) * -0.125f;
            nm = pack_bf16(p, p);
        }
#pragma unroll
        for (int k = 0; k < 4; k++) {
            v[i][k] = bf2_fma(v[i][k], d[k], nm);
            s[k] = i ? bf2_add(v[i][k], s[k]) : v[i][k];
            c[k] = i ? bf2_fma(v[i][k], v[i][k], c[k]) : bf2_mul(v[i][k], v[i][k]);
        }
    }
    after_loads(c[0]);
    float m = fmaf(sum8(s), 1.0f / 48, -bf_lo(nm));
    float q = fmaf(-bf_lo(nm), fmaf(2.f, m, bf_lo(nm)), sum8(c) * (1.0f / 48));
#pragma unroll
    for (int o = 1; o < 8; o <<= 1) {
        m += __shfl_xor_sync(0xffffffffu, m, o);
        q += __shfl_xor_sync(0xffffffffu, q, o);
    }
    m *= 0.125f;
    const float r = KAPPA * rsqrt_fast(fmaxf(fmaf(-m, m, q * 0.125f), 0.f) + 1e-5f);
    const float e = (-bf_lo(nm) - m) * r * 0x1p-112f;
    const bool two = __any_sync(0xffffffffu, r < 0x1p-14f);
    const float r1 = r * (two ? 0x1p-56f : 0x1p-112f);
    uint32_t mul = pack_bf16(r1, r1), add = two ? 0u : pack_bf16(e, e);
#pragma unroll 1
    for (int it = !two; it < 2; it++) {
#pragma unroll
        for (int i = 0; i < 6; i++)
#pragma unroll
            for (int k = 0; k < 4; k++) v[i][k] = bf2_fma(v[i][k], mul, add);
        mul = 0x23802380u;
        add = pack_bf16(e, e);
    }
#pragma unroll
    for (int i = 0; i < 6; i++)
#pragma unroll
        for (int k = 0; k < 4; k++) v[i][k] = bf2_as_h2(v[i][k]);
}

__device__ __forceinline__ float gelu_s(float y) {
    float u = y * fmaf(y, y, GELU_C);
    float t;
    asm volatile("tanh.approx.f32 %0, %1;\n" : "=f"(t) : "f"(u));
    return fmaf(y, t, y);
}
__device__ __forceinline__ void p1_pack(int c, uint32_t (&p)[4], uint32_t (&dd)[4]) {
#pragma unroll
    for (int u = 0; u < 4; u++) {
        if ((c & 3) == 0) dd[u] = p[u];
        else {
            uint32_t n = dd[u];
            if ((c & 3) == 1) n = __byte_perm(n, 0, 0x2301);
            if ((c & 3) == 2) {
                dd[u] = __byte_perm(n >> 3, n >> 1, 0x6341);
                n = __byte_perm(n >> 3, n >> 1, 0x7250);
            }
            asm("lop3.b32 %0, %0, %1, 0x40074007, 0xd8;\n" : "+r"(p[u]) : "r"(n));
        }
    }
}
__device__ __forceinline__ void p1_store(int c, const uint32_t (&p)[4], uint8_t* hptr) {
    if (c & 3) stg128_cs(hptr + (c >> 2) * H_HALF + ((c & 3) - 1) * 512, p[0], p[1], p[2], p[3]);
}

template <bool GEN>
__device__ __forceinline__ void p1_epilogue(uint32_t (&acc)[32], float (&ssq)[2], uint32_t sc2, uint8_t* hp, int zero) {
    uint32_t sq[2], dd[4];
#pragma unroll
    for (int c = 0; c < 8; c++) {
        if (GEN) sched_break(zero);
        uint32_t p[4];
#pragma unroll
        for (int u = 0; u < 4; u++) {
            const uint32_t y = acc[8 * (c >> 1) + 2 * u + (c & 1)];
            if (GEN) {
                const float sc = c & 1 ? bf_hi(sc2) : bf_lo(sc2), fs = __uint_as_float(0x78000000u - __float_as_uint(sc));
                const float g0 = gelu_s(h_lo(y) * fs), g1 = gelu_s(h_hi(y) * fs);
                ssq[c & 1] = fmaf(g1, g1, fmaf(g0, g0, ssq[c & 1]));
                p[u] = pack_f16(g0 * sc, g1 * sc);
            } else {
                uint32_t g;
                asm("{\n.reg .b32 w;\n"
                    "fma.rn.f16x2 w, %1, %1, %2;\n"
                    "mul.rn.f16x2 w, w, %1;\n"
                    "tanh.approx.f16x2 w, w;\n"
                    "fma.rn.f16x2 %0, %1, w, %1;\n}\n" : "=r"(g) : "r"(y), "r"(0x40d940d9u));
                acc[8 * (c >> 1) + 2 * u + (c & 1)] = g;
                if (c < 2 && u == 0) asm("mul.rn.f16x2 %0, %1, %1;\n" : "=r"(sq[c & 1]) : "r"(g));
                else asm("fma.rn.f16x2 %0, %1, %1, %0;\n" : "+r"(sq[c & 1]) : "r"(g));
                if (c & 1) asm("{\n.reg .b16 l, h;\n.reg .b32 f;\nmov.b32 {l, h}, %2;\nmov.b32 f, {h, h};\nmul.rn.f16x2 %0, %1, f;\n}\n" : "=r"(p[u]) : "r"(g), "r"(sc2));
                else asm("{\n.reg .b16 l, h;\n.reg .b32 f;\nmov.b32 {l, h}, %2;\nmov.b32 f, {l, l};\nmul.rn.f16x2 %0, %1, f;\n}\n" : "=r"(p[u]) : "r"(g), "r"(sc2));
            }
        }
        p1_pack(c, p, dd);
        if (c & 3) {
#pragma unroll
            for (int u = 0; u < 4; u++) acc[4 * (c - 1 - (c >> 2)) + u] = p[u];
        }
        p1_store(c, p, hp);
    }
    if (!GEN) {
#pragma unroll
        for (int r = 0; r < 2; r++) ssq[r] += h_lo(sq[r]) + h_hi(sq[r]);
    }
}
template <int CS, int NWG>
__device__ __forceinline__ void p1_compute(uint32_t sbase, int cb0, int warp, int lane, int zero) {
    const uint32_t bar_full = sbase + P1_OFF_BAR, bar_empty = bar_full + P1_NST * 8, bar_w = bar_empty + P1_NST * 8;
    const int wg = warp >> 2, w = warp & 3, cb = cb0 + wg;
    const uint32_t slot_free = mapa(bar_empty, lane & (CS - 1)) + (lane / CS) * 8;
    if (lane < 4 * CS && lane / CS != 1 + wg && (NWG == 2 || wg || lane >= CS)) mbar_arrive_cluster(slot_free);
    if (wg == 1) bar_arrive(1, 256);
    uint32_t a[24][4], ex[2], gen = 0;
    const uint32_t wsrc = sbase + (1 + wg) * P1_SLOT + ((lane >> 4) * 8 + (lane & 7)) * 128 + (((2 * w + ((lane >> 3) & 1)) ^ (lane & 7)) << 4);
#pragma unroll 1
    for (int it = 0; it < 2; it++) {
        if (it) mbar_wait(bar_w + wg * 8, 0);
        TRACEW(110 + warp, 5);
        if (it || wg == 0) {
#pragma unroll
        for (int k = 0; k < 24; k++) ldsm4t(a[k], wsrc + k * 2048);
#pragma unroll
        for (int r = 0; r < 2; r++) {
            float t = 0.f;
#pragma unroll
            for (int j = 0; j < 6; j++) {
                uint32_t c = bf2_mul(a[4 * j][r], a[4 * j][r]);
#pragma unroll
                for (int k = 1; k < 8; k++) c = bf2_fma(a[4 * j + k / 2][r + (k & 1) * 2], a[4 * j + k / 2][r + (k & 1) * 2], c);
                t += bf_lo(c) + bf_hi(c);
            }
            t += __shfl_xor_sync(0xffffffffu, t, 1);
            t += __shfl_xor_sync(0xffffffffu, t, 2);
            asm("sqrt.approx.f32 %0, %0;\n" : "+f"(t));
            ex[r] = min(max(__float_as_uint(13.9f * t) >> 23, 72u), 198u);
        }
        asm volatile("{\n.reg .pred p;\nsetp.gt.u32 p, %1, 7;\nbar.red.or.pred p, %2, 128, p;\nselp.u32 %0, 1, 0, p;\n}\n"
                     : "=r"(gen) : "r"(max(ex[0] - 125u, ex[1] - 125u)), "r"(5 + wg) : "memory");
        gen = __shfl_sync(0xffffffffu, gen, 0) & it;
        if (it) {
            if ((lane & 3) < 2) g_ex[cb * 64 + w * 16 + (lane & 1) * 8 + (lane >> 2)] = lane & 1 ? ex[1] : ex[0];
            if (lane / CS == 1 + wg) mbar_arrive_cluster(slot_free);
            __syncwarp();
        }
        }
        if (gen) {
#pragma unroll
            for (int k = 0; k < 24; k++)
#pragma unroll
                for (int j = 0; j < 4; j++) a[k][j] = bf2_mul(a[k][j], (268u - ex[j & 1]) * 0x00800080u);
        }
        if (it || wg == 1) {
#pragma unroll
            for (int k = 0; k < 24; k++)
#pragma unroll
                for (int j = 0; j < 4; j++) {
                    a[k][j] = bf2_as_h2(bf2_mul(a[k][j], 0x07800780u));
                    asm volatile("" : "+r"(a[k][j]));
                }
        }
        TRACEW(110 + warp, 6);
    }
#pragma unroll
    for (int j = 0; j < 4; j++)
        asm volatile("st.shared.u32 [%0], %1;\n" ::"r"(sbase + P1_OFF_A + warp * 512 + (j & 1) * 256 + (j >> 1) * 128 + lane * 4), "r"(a[23][j]) : "memory");
    asm volatile("fence.proxy.async.shared::cta;\n" ::: "memory");
    TRACEW(110 + warp, 7);
    const uint32_t ex2 = ex[0] | ex[1] << 16;
    const uint32_t sc2 = gen ? 0x7f007f00u - (ex2 << 7) : (0x008e008eu - ex2) << 10;
    const uint32_t empty_remote = mapa(bar_empty, lane & (CS - 1));
    const int g = lane >> 2, q = lane & 3, turn = wg + 1 == NWG ? 1 : wg + 2;
    float ssq[2] = {0.f, 0.f};
    uint32_t acc[32] = {};
    TSTAMP(0, 1);
    STAMPT(128, 4);
    STAMPT(256, 5);

    uint8_t* hp = reinterpret_cast<uint8_t*>(g_h) + ((cb * 2 + (w >> 1)) * H_STEP + (w & 1) * 1536) + g * 64 + (q ^ (g >> 1)) * 16;
    const uint64_t desc_base = make_desc(sbase, 16, 1024) | (1ull << 62);
    const uint64_t da = make_desc(sbase + P1_OFF_A + wg * 2048, 128, 256);
#pragma unroll 1
    for (int i = 0;; i++) {
        const int s0 = (i & 1) * 16, par = (i >> 1) & 1;
        const uint64_t d0 = desc_base + (uint64_t)((i & 1) * (LN_TILE / 16));
        TRACE(wg, i, 0);
        mbar_wait(bar_full + s0, par);
        bar_sync(1 + wg, 256);
        TRACE(wg, i, 1);
        uint32_t step, more;
        wg_fence();
#pragma unroll
        for (int k = 0; k < 24; k++) {
            if (k == 12) mbar_wait(bar_full + s0 + 8, par);
            const uint64_t db = d0 + (uint64_t)((k >> 2) * 1024 + (k & 3) * 2);
            if (k < 23) mma_rs_n128(acc, a[k], db, k ? 1 : zero);
            else mma_ss_n128(acc, da, db);
            if (k == 23) bar_arrive(turn, 256);
            if (k % 12 == 11) wg_commit();
        }
        if (NWG == 2) {
            step = (i ? 11 : LN_STEP) * (2 * H_TILE);
            more = i + 1 < NSMALL;
        } else asm volatile("ld.shared.v2.u32 {%0, %1}, [%2];\n" : "=r"(step), "=r"(more) : "r"(sbase + P1_OFF_TILE + (i & 3) * 16) : "memory");
        TRACE(wg, i, 2);
        wg_wait<1>();
        if (lane < CS) mbar_arrive_cluster(empty_remote + s0);
        hp += step;
        TRACE(wg, i, 3);
        wg_wait<0>();
        TRACE(wg, i, 4);
        if (lane < CS) mbar_arrive_cluster(empty_remote + s0 + 8);
        if (gen) p1_epilogue<true>(acc, ssq, sc2, hp, zero);
        else p1_epilogue<false>(acc, ssq, sc2, hp, zero);
        if (!more) break;
    }
    TSTAMP(0, 21);
    if (wg == 0) bar_sync(1, 256);
    uint32_t par;
    if (NWG == 2) par = __ldcg(&g_epoch) & 1;
    else asm volatile("ld.shared.u32 %0, [%1];\n" : "=r"(par) : "r"(sbase + P1_OFF_TILE - 4) : "memory");
    float* sums = g_sums[par];
#pragma unroll
    for (int r = 0; r < 2; r++) {
        ssq[r] += __shfl_xor_sync(0xffffffffu, ssq[r], 1);
        ssq[r] += __shfl_xor_sync(0xffffffffu, ssq[r], 2);
        if (q == 0) atomicAdd(sums + cb * 64 + w * 16 + r * 8 + g, ssq[r]);
    }
    if (NWG == 2) {
        asm volatile("fence.proxy.async.global;\nfence.acq_rel.gpu;\n" ::: "memory");
        __syncwarp();
        if (lane == 0) asm volatile("red.relaxed.gpu.global.add.u32 [%0], 1;\n" ::"l"(&g_img[2]) : "memory");
    }
}

__device__ __forceinline__ void p1_w2(const __nv_bfloat16* __restrict__ w2, const __nv_bfloat16* __restrict__ grn_b, int w, int lane) {
    const int gw = blockIdx.x * 4 + w;
    float* sums = g_sums[__ldcg(&g_epoch) & 1] + HID;
    flag_wait<true>(&g_flag[40][1][0], 12);
    {
        const int col = gw % 6 * 64 + lane * 2;
        float bsum[2] = {0.f, 0.f}, asum[2] = {0.f, 0.f};
#pragma unroll 4
        for (int kk = 0; kk < 192; kk++) {
            const int k = gw / 6 * 192 + kk;
            const uint32_t v = *reinterpret_cast<const uint32_t*>(w2 + k * C_DIM + col);
            const float b = __bfloat162float(grn_b[k]), f = __uint_as_float(__ldcg(&g_ex[k]) << 23);
            bsum[0] = fmaf(b, bf_lo(v), bsum[0]);
            bsum[1] = fmaf(b, bf_hi(v), bsum[1]);
            asum[0] = fmaf(f, fabsf(bf_lo(v)), asum[0]);
            asum[1] = fmaf(f, fabsf(bf_hi(v)), asum[1]);
        }
#pragma unroll
        for (int j = 0; j < 2; j++) {
            atomicAdd(sums + col + j, bsum[j]);
            atomicAdd(sums + C_DIM + col + j, asum[j]);
        }
        __threadfence();
        __syncwarp();
        if (lane == 0) asm volatile("red.relaxed.gpu.global.add.u32 [%0], 1;\n" ::"l"(&g_flag[LN_RING + 2][0][0]) : "memory");
    }
    while (*(volatile unsigned*)&g_flag[P1_IMG % LN_RING][1][0] < 12 * (P1_IMG / LN_RING + 1)) {
        __nanosleep(2000);
        SAFE_BREAK
    }
    flag_wait<true>(&g_flag[LN_RING + 2][0][0], 48);
    float z = 0.f;
#pragma unroll
    for (int j = 0; j < C_DIM / 32; j++) z = fmaxf(z, __ldcg(sums + C_DIM + j * 32 + lane));
    const float sc = __uint_as_float((263u - acc_exp(__uint_as_float(__reduce_max_sync(0xffffffffu, __float_as_uint(z))))) << 23);
    const int np = gw % 6 * 64 + lane * 2;
#pragma unroll 2
    for (int cc = 0; cc < 24; cc++) {
        const int c = gw / 6 * 24 + cc;
        uint32_t v[8], o[2][4];
#pragma unroll
        for (int e = 0; e < 8; e++) v[e] = *reinterpret_cast<const uint32_t*>(w2 + (c * 8 + e) * C_DIM + perm32(np));
#pragma unroll
        for (int e = 0; e < 4; e++) {
            const uint2 t = __ldcg(reinterpret_cast<const uint2*>(g_ex) + c * 4 + e);
            const float f0 = __uint_as_float(t.x << 23), f1 = __uint_as_float(t.y << 23);
            o[0][e] = pack_f16(bf_lo(v[2 * e]) * f0 * sc, bf_lo(v[2 * e + 1]) * f1 * sc);
            o[1][e] = pack_f16(bf_hi(v[2 * e]) * f0 * sc, bf_hi(v[2 * e + 1]) * f1 * sc);
        }
#pragma unroll
        for (int j = 0; j < 2; j++)
            g_w2img[0][(((c >> 1) * 48 + (np >> 3)) * 2 + (c & 1)) * 8 + (np & 7) + j] = make_uint4(o[j][0], o[j][1], o[j][2], o[j][3]);
    }
    asm volatile("fence.proxy.async.global;\n" ::: "memory");
    __threadfence();
    __syncwarp();
    if (lane < 2) asm volatile("red.relaxed.gpu.global.add.u32 [%0], 1;\n" ::"l"(&g_img[lane * 2]) : "memory");
}

__device__ __forceinline__ void p1_load_w1(uint32_t sbase, const CUtensorMap* wmap, int cb0, int nwg) {
    const uint32_t bar_w = sbase + P1_OFF_BAR + 2 * P1_NST * 8;
    for (int i = 0; i < nwg; i++) {
        mbar_expect_tx(bar_w + i * 8, P1_SLOT);
        tma2(sbase + (1 + i) * P1_SLOT, wmap, (cb0 + i) * 64, 0, bar_w + i * 8);
        tma2(sbase + (1 + i) * P1_SLOT + P1_SLOT / 2, wmap, (cb0 + i) * 64, 192, bar_w + i * 8);
    }
}

template <int CS>
__global__ void __cluster_dims__(CS, 1, 1) __launch_bounds__(512, 1)
pass1_kernel(const __grid_constant__ CUtensorMap wmap, const __nv_bfloat16* __restrict__ x, const __nv_bfloat16* __restrict__ dw,
             const __nv_bfloat16* __restrict__ w1, int zero) {
    extern __shared__ __align__(1024) uint8_t smem[];
    const uint32_t sbase = smem_u32(smem);
    const uint32_t bar_full = sbase + P1_OFF_BAR, bar_empty = bar_full + P1_NST * 8, bar_w = bar_empty + P1_NST * 8;
    const uint32_t bar_xfull = bar_w + 24, bar_raw = bar_xfull + 16, bar_done = bar_raw + 16;
    const int tid = threadIdx.x;
    const int warp = __shfl_sync(0xffffffffu, tid >> 5, 0), lane = tid & 31;
    const uint32_t rank = cluster_rank();
    const int bid = blockIdx.x, cl = bid >> 1;
    uint8_t* const ring = reinterpret_cast<uint8_t*>(g_ln);
    const int ln0 = bid >> 2, items = (NT128 - 1 - ln0) / LN_STEP + 1;

    TSTAMP(0, 0);
    TRACEW(110 + warp, 0);

    if (warp >= 12) {
        reg_dec<56>();
        asm volatile("barrier.cluster.arrive.relaxed.aligned;\n" ::: "memory");
        asm volatile("barrier.cluster.wait.aligned;\n" ::: "memory");
        {
            auto ring_row = [&](int p) {
                const int n = (p & 8) * 8 + (lane >> 3) * 8 + (p & 3) * 2 + (p >> 2 & 1);
                return n * 128 + (((lane ^ n) & 7) << 4);
            };
            const uint8_t* xsrc = reinterpret_cast<const uint8_t*>(x) + (size_t)(LN_STEP * 8 + bid * 2 + (warp & 1)) * P1_X;
            const uint32_t xbar = bar_xfull + (warp & 1) * 8, xdst = sbase + P1_OFF_X + (warp & 1) * P1_X;
            const uint32_t sdw = sbase + P1_OFF_DW + (lane & 7) * 16;
            uint32_t src = xdst - P1_OFF_X + (lane >> 3) * (C_DIM * 2) + (lane & 7) * 16;
            int row0 = ring_row((bid & 7) * 2 + (warp & 1)) ^ 288, slot = bid >> 3, used = 0;
            auto next = [&]() {
                xsrc += (size_t)LN_STEP * 8 * P1_X;
                if (elect_one()) {
                    mbar_expect_tx(xbar, P1_X);
                    bulk_g2s(xdst, xsrc, P1_X, xbar);
                }
                __syncwarp();
            };
#pragma unroll 1
            for (int i = -1; i < items; i++) {
                if (warp == 14) TRACEW(128 + i, 0);
                const int place = p1_place(ln0 + i * LN_STEP, slot);
                const int last = i > 0 ? 3 : i ? 2 + (warp >> 1 & 1) : 1;
#pragma unroll 1
                for (int ps = i < 0 ? last - 4 : 0; ps <= last; ps += i < 0 ? 4 : 1) {
                    if (i < 0 && ps > 0) STAMPT(416, 6);
                    if (i < 0 && ps > 0) mbar_wait(bar_raw, 0);
                    if (i < 0 && ps > 0) STAMPT(416, 7);
                    if (ps == 0) {
                        if (used) flag_wait<false>(&g_flag[slot][1][0], used);
                        if (i && i + 1 < items && elect_one())
                            asm volatile("cp.async.bulk.prefetch.L2.global [%0], %1;\n" ::"l"(xsrc + (size_t)LN_STEP * 8 * P1_X), "r"(P1_X) : "memory");
                        if (i) mbar_wait(xbar, ~i & 1);
                        else mbar_wait(bar_raw + 8, 0);
                        if (warp == 14) TRACEW(128 + i, 1);
                    }
                    uint32_t v[6][4];
#pragma unroll
                    for (int j = 0; j < 6; j++) lds128(v[j], src + (ps & 3) * (4 * C_DIM * 2) + j * 128);
                    ln_row(v, sdw, [&](uint32_t dep) {
                        if (i == 0 && ps == 1 && lane < CS) mbar_arrive_cluster(mapa(bar_empty, lane) + (dep & zero));
                        if (ps == 3 && i > 0 && i + 1 < items && !__any_sync(0xffffffffu, dep & zero)) next();
                    });
                    uint8_t* dst = ring + (place * LN_TILE + (ps & 1) * 4096 + (row0 ^ (ps & 2) * 144));
#pragma unroll
                    for (int j = 0; j < 6; j++)
                        asm volatile("{\n.reg .pred p;\nsetp.ge.s32 p, %5, 0;\n@p st.global.v4.u32 [%0], {%1,%2,%3,%4};\n}\n"
                                     ::"l"(dst + j * 16384), "r"(v[j][0]), "r"(v[j][1]), "r"(v[j][2]), "r"(v[j][3]), "r"(ps) : "memory");
                }
                if (warp == 14) TRACEW(128 + i, 2);
                asm volatile("fence.proxy.async.global;\nfence.acq_rel.cta;\n" ::: "memory");
                if (i < 0) {
                    bar_sync(4, 128);
                    if (warp < 14) break;
                    row0 ^= 288;
                    slot += NGRP;
                } else {
                    if (i) mbar_wait(bar_done, ~i & 1);
                    else {
                        src += P1_OFF_X;
                        slot = ln0;
                        row0 = ring_row((bid & 3) * 4 + (warp & 1) * 2);
                    }
                    __syncwarp();
                    if (lane == 0) mbar_arrive(bar_done);
                    if ((slot += LN_STEP) >= LN_RING) { slot -= LN_RING; used += 12; }
                }
            }
            if (warp < 14 && lane < CS) mbar_arrive_cluster(mapa(bar_empty, lane));
        }
        if (warp == 12) {
            int prev = 0, t = cl >> 2, next = t + NGRP;
            const uint32_t rbase = mapa(sbase, lane & (CS - 1));
            int i = 0;
#pragma unroll 1
            for (; t < NT128; i++) {
                const int s0 = (i & 1) * 2, par = (i >> 1) & 1;
                const int round = t / LN_RING, slot = t - round * LN_RING;
                const uint8_t* src = ring + slot * LN_TILE + rank * (P1_SLOT / CS);
                int draw = 0;
                if (rank == 0 && lane == 0) draw = 2 * NGRP + atomicAdd(&g_flag[LN_RING + ((cl >> 1) & 1)][cl & 1][0], 1u);
                flag_wait<true>(&g_flag[slot][0][0], 8 * round + 8);
                TRACEW(i, 2);
                if (i == 0) STAMPT(384, 10);
                if (i == 2) STAMPT(384, 13);
                if (i == 3) STAMPT(384, 14);
                asm volatile("fence.proxy.async.global;\n" ::: "memory");
                draw = p1_tile(__shfl_sync(0xffffffffu, draw, 0));
#pragma unroll
                for (int h = 0; h < 2; h++) {
                    mbar_wait(bar_empty + (s0 + h) * 8, par);
                    TRACEW(i, 4 + h);
                    if (i == 0 && h == 1) STAMPT(384, 11);
                    if (elect_one()) {
                        mbar_expect_tx(bar_full + (s0 + h) * 8, P1_SLOT + 16 - 16 * h);
                        bulk_g2s_mc(sbase + (s0 + h) * P1_SLOT + rank * (P1_SLOT / CS), src + h * P1_SLOT, P1_SLOT / CS, bar_full + (s0 + h) * 8, (uint16_t)((1 << CS) - 1));
                    }
                    __syncwarp();
                    if (h == 0 && rank == 0 && lane < CS)
                        asm volatile("st.async.shared::cluster.mbarrier::complete_tx::bytes.v4.u32 [%0], {%1, %2, %3, %3}, [%4];\n"
                                     ::"r"(rbase + P1_OFF_TILE + (i & 3) * 16), "r"((t - prev) * (2 * H_TILE)), "r"((int)(next < NT128)), "r"(draw),
                                       "r"(rbase + P1_OFF_BAR + s0 * 8) : "memory");
                }
                prev = t;
                t = next;
                next = draw;
                if (rank != 0) {
                    mbar_wait(bar_full + s0 * 8, (i >> 1) & 1);
                    mbar_wait(bar_full + s0 * 8 + 8, (i >> 1) & 1);
                    if (lane == 0 && rank == 1) asm volatile("red.relaxed.gpu.global.add.u32 [%0], %1;\n" ::"l"(&g_flag[slot][1][0]), "r"(CS * 3 / 2) : "memory");
                    asm volatile("ld.shared.u32 %0, [%1];\n" : "=r"(next) : "r"(sbase + P1_OFF_TILE + (i & 3) * 16 + 8) : "memory");
                    TRACEW(i, 3);
                }
            }
#pragma unroll 1
            for (int j = 2 * i; j < 2 * i + 4; j++) mbar_wait(bar_empty + (j & 3) * 8, (j >> 2) & 1);
        } else if (warp == 13) {
            STAMPT(416, 8);
            if (lane == 0) asm volatile("red.release.gpu.global.add.u32 [%0], 1;\n" ::"l"(&g_flag[bid >> 3][0][0]) : "memory");
            __syncwarp();
            STAMPT(416, 9);
            const uint32_t ep = g_epoch & 1;
            asm volatile("st.shared.u32 [%0], %1;\n" ::"r"(sbase + P1_OFF_TILE - 4), "r"(ep) : "memory");
            if (bid < 18) reinterpret_cast<float4*>(g_sums[ep ^ 1])[bid * 32 + lane] = make_float4(0.f, 0.f, 0.f, 0.f);
#pragma unroll 1
            for (int i = 0; i < items; i++) {
                mbar_wait(bar_done, i & 1);
                asm volatile("fence.proxy.async.global;\n" ::: "memory");
                if (lane == 0) {
                    const int slot = i ? ln0 + (i & 1) * LN_STEP : NGRP + (bid >> 3), place = p1_place(ln0 + i * LN_STEP, slot);
                    mbar_arrive(bar_done);
                    asm volatile("red.release.gpu.global.add.u32 [%0], %1;\n" ::"l"(&g_flag[place][0][0]), "r"(i ? 2 : 1) : "memory");
                    if (place != slot) {
                        atomicAdd(&g_flag[slot][0][0], 2u);
                        atomicAdd(&g_flag[slot][1][0], 3u);
                    }
                }
                __syncwarp();
                TRACEW(128 + i, 3);
            }
        }
    } else {
        if (tid == 0) {
            mbar_init(bar_raw, 1);
            mbar_init(bar_raw + 8, 1);
            mbar_init(bar_xfull, 1);
            mbar_init(bar_xfull + 8, 1);
            for (int i = 0; i < 3; i++) mbar_init(bar_w + i * 8, 1);
            asm volatile("fence.mbarrier_init.release.cluster;\n" ::: "memory");
            {
                mbar_expect_tx(bar_raw, P1_X + C_DIM * 2);
                bulk_g2s(sbase + P1_OFF_DW, dw, C_DIM * 2, bar_raw);
                for (int i = 0; i < 2; i++) bulk_g2s(sbase + i * P1_X + P1_X / 2, x + (size_t)(bid * 16 + i * 8) * C_DIM, P1_X / 2, bar_raw);
                if (bid < 96) asm volatile("cp.async.bulk.prefetch.L2.global [%0], 12288;\n" ::"l"(w1 + bid * 6144) : "memory");
                mbar_expect_tx(bar_raw + 8, P1_X);
                for (int i = 0; i < 2; i++) bulk_g2s(sbase + i * P1_X, x + (size_t)(NGRP * 128 + bid * 16 + i * 8) * C_DIM, P1_X / 2, bar_raw + 8);
            }
            p1_load_w1(sbase, &wmap, (bid & 7) * 3, 3);
            for (int i = 0; i < 2; i++) {
                mbar_expect_tx(bar_xfull + i * 8, P1_X);
                bulk_g2s(sbase + P1_OFF_X + i * P1_X, x + (size_t)(LN_STEP * 128 + bid * 32 + i * 16) * C_DIM, P1_X, bar_xfull + i * 8);
            }
        }
        if (tid == 32) {
            mbar_init(bar_done, 3);
            mbar_arrive(bar_done);
            asm volatile("fence.mbarrier_init.release.cluster;\n" ::: "memory");
        }
        if (tid == 64) {
            for (int i = 0; i < P1_NST; i++) {
                mbar_init(bar_full + i * 8, 1);
                mbar_init(bar_empty + i * 8, 12 * CS);
            }
            asm volatile("fence.mbarrier_init.release.cluster;\n" ::: "memory");
            if (bid < 64) (&g_half[0][0])[bid] = 0;
            else if (bid == 64) g_prog = 0;
            else if (bid < 68) g_img[bid - 65] = 0;
        }
        __syncwarp();
        asm volatile("barrier.cluster.arrive.relaxed.aligned;\n" ::: "memory");
        reg_inc<152>();
        TRACEW(110 + warp, 1);
        gdc_launch();
        asm volatile("barrier.cluster.wait.aligned;\n" ::: "memory");
        p1_compute<CS, 3>(sbase, (bid & 7) * 3, warp, lane, zero);
        TSTAMP(0, 30);
    }
}

constexpr int P2_B = 24576, P2_NB = 5;
constexpr int P2_A = 3072, P2_NA = 5;
constexpr int P2_XROW = C_DIM * 2;
constexpr int P2_OFF_A = P2_B * P2_NB;
constexpr int P2_OFF_X = P2_OFF_A + 3 * P2_NA * P2_A;
constexpr int P2_XHALF = 32 * P2_XROW + 64;
constexpr int P2_OFF_BIAS = P2_OFF_X + 64 * P2_XROW + 64;
constexpr int P2_OFF_GRN = P2_OFF_BIAS + C_DIM * 4;
constexpr int P2_OFF_RED = P2_OFF_GRN + HID * 2;
constexpr int P2_OFF_BAR = P2_OFF_RED + 192;
static_assert(P2_OFF_BAR >= P1_OFF_DW && P2_OFF_BAR + (2 * P2_NB + 6 * P2_NA + 3) * 8 <= P1_OFF_BAR, "");
constexpr int P2_SMEM = P1_SMEM;
constexpr int P2_LAG = 17;
constexpr int P2_NCL = NUM_CTAS / 2, P2_ITEMS = NT128 / P2_NCL, P2_SHARED = NT128 - P2_ITEMS * P2_NCL;
constexpr int P2_POS = P2_LAG * (P2_ITEMS - 1) + 48;
__device__ __forceinline__ int p2_start(int n) { return n < 0 ? 0 : n == P2_ITEMS ? P2_POS - 24 : P2_LAG * n; }
constexpr int P2_FOLD = 17;
constexpr int P2_XC = 8 * P2_XROW;
constexpr int P2_DELTA = 7;
__device__ __forceinline__ int p2_tile(int cl, int n) {
    return n == 0 ? NT128 - 1 - cl : n < 0 || n == P2_ITEMS ? NT128 - 1 - P2_NCL - (cl >> 1) : cl + P2_NCL * (n - 1);
}

constexpr int P2_EG = 2;
__device__ __forceinline__ void p2_init(uint32_t (&acc)[48], int c, uint32_t sb) {
#pragma unroll
    for (int i = 8 * (c % 6); i < 8 * (c % 6) + 8; i += 4)
        asm volatile("ld.shared.v4.u32 {%0,%1,%2,%3}, [%4];\n" : "=r"(acc[i]), "=r"(acc[i + 1]), "=r"(acc[i + 2]), "=r"(acc[i + 3])
                     : "r"(sb + c * 128 + i % 8 * 4) : "memory");
}
__device__ __forceinline__ void p2_epilogue(uint32_t (&acc0)[48], uint32_t (&acc1)[48], uint32_t sx, uint32_t sb, uint32_t up, int zero) {
    uint32_t v[2][P2_EG][4];
    auto load = [&](int c, uint32_t a) {
#pragma unroll
        for (int j = 0; j < P2_EG; j++) {
            const int u = c * P2_EG + j;
            asm volatile("ld.shared.v4.u32 {%0,%1,%2,%3}, [%4];\n" : "=r"(v[c & 1][j][0]), "=r"(v[c & 1][j][1]), "=r"(v[c & 1][j][2]), "=r"(v[c & 1][j][3])
                         : "r"(a + (u >> 1) * 64 + (u & 1) * 4 * P2_XROW) : "memory");
        }
    };
    load(0, sx);
#pragma unroll
    for (int c = 0; c < 24 / P2_EG; c++) {
        if (c + 1 < 24 / P2_EG) load(c + 1, sx + (v[c & 1][P2_EG - 1][0] & zero));
#pragma unroll
        for (int j = 0; j < P2_EG; j++) {
            const int u = c * P2_EG + j, i = 8 * ((u >> 1) % 6) + (u & 1);
            const uint32_t (&acc)[48] = u < 12 ? acc0 : acc1;
            uint32_t (&w)[4] = v[c & 1][j];
#pragma unroll
            for (int e = 0; e < 4; e++)
                w[e] = bf2_fma(pack_bf16(h_lo(acc[i + 2 * e]), h_hi(acc[i + 2 * e])), up, w[e]);
            asm volatile("st.shared.v4.u32 [%4], {%0,%1,%2,%3};\n" ::"r"(w[0]), "r"(w[1]), "r"(w[2]), "r"(w[3]),
                         "r"(sx + (u >> 1) * 64 + (u & 1) * 4 * P2_XROW) : "memory");
        }
        p2_init(c < 6 ? acc0 : acc1, c, sb + (v[c & 1][1][0] & zero));
    }
}

__device__ __forceinline__ void p2_unpack(uint4& u, uint32_t o1, uint32_t o2, uint32_t o3) {
    u.z = o1 & 0xbff8bff8u;
    u.y = o2 & 0xbff8bff8u;
    u.w = o3 & 0xbff8bff8u;
    u.x = (__byte_perm(o1, 0, 0x2301) & 0x07400740u) | ((__byte_perm(o2, o3, 0x6240) << 3) & 0x38383838u) | ((__byte_perm(o2, o3, 0x3715) << 1) & 0x80808080u);
}
__device__ __forceinline__ uint32_t h2_mul(uint32_t a, uint32_t b) {
    uint32_t r;
    asm("mul.rn.f16x2 %0, %1, %2;\n" : "=r"(r) : "r"(a), "r"(b));
    return r;
}
__device__ __forceinline__ void p2_epilogue_add(const uint32_t (&acc)[48], uint8_t* o, uint32_t up, int zero) {
#pragma unroll
    for (int t = 0; t < 12; t++) {
        uint32_t v[4];
#pragma unroll
        for (int e = 0; e < 4; e++) {
            v[e] = acc[8 * (t >> 1) + (t & 1) + 2 * e];
            asm volatile("" : "+r"(v[e]));
            v[e] = bf2_mul(pack_bf16(h_lo(v[e]), h_hi(v[e])), up);
        }
        asm volatile("red.global.add.noftz.v4.bf16x2 [%0], {%1,%2,%3,%4};\n" ::"l"(o + (t >> 1) * 64 + (t & 1) * 4 * P2_XROW),
                     "r"(v[0]), "r"(v[1]), "r"(v[2]), "r"(v[3]) : "memory");
        if (t % 3 == 2) sched_break(zero);
    }
}

__global__ void __cluster_dims__(2, 1, 1) __launch_bounds__(512, 1)
pass2_kernel(const __grid_constant__ CUtensorMap wmap, const __nv_bfloat16* __restrict__ x, const __nv_bfloat16* __restrict__ w2,
             const __nv_bfloat16* __restrict__ grn_g, const __nv_bfloat16* __restrict__ grn_b, __nv_bfloat16* __restrict__ out, int zero) {
    extern __shared__ __align__(1024) uint8_t smem[];
    const uint32_t sbase = smem_u32(smem);
    const uint32_t bar_bfull = sbase + P2_OFF_BAR, bar_bempty = bar_bfull + P2_NB * 8;
    const uint32_t bar_afull = bar_bempty + P2_NB * 8, bar_aempty = bar_afull + 3 * P2_NA * 8;
    const uint32_t bar_xfull = bar_aempty + 3 * P2_NA * 8, bar_oready = bar_xfull + 8, s_pos = bar_xfull + 16;
    int tid;
    asm volatile("mov.u32 %0, %%tid.x;\n" : "=r"(tid));
    const int warp = __shfl_sync(0xffffffffu, tid >> 5, 0), lane = tid & 31;
    const uint32_t rank = cluster_rank();
    const int cl = blockIdx.x >> 1, pair = cl >> 1;
    const int k0 = (4 * pair + (cl & 1) * (48 - P2_POS % 48)) % 48;
    const int head = pair < P2_SHARED && !(cl & 1), tail = pair < P2_SHARED && (cl & 1);

    const bool small = blockIdx.x < NUM_CTAS - 8 * NGRP;
    uint32_t par, gg[4];
    auto early = [&]() {
        asm volatile("ld.global.cg.u32 %0, [%1];\n" : "=r"(par) : "l"(&g_epoch) : "memory");
#pragma unroll
        for (int i = 0; i < 4; i++) asm volatile("ld.global.nc.u16 %0, [%1];\n" : "=r"(gg[i]) : "l"(grn_g + tid + 384 * i) : "memory");
    };
    if (warp < 12) early();
    else if (small) par = 0;
    else asm volatile("ld.acquire.gpu.global.u32 %0, [%1];\n" : "=r"(par) : "l"(&g_img[(warp & 1) * 2]) : "memory");
    if (small && tid == 0) {
        for (int i = 0; i < 2 * P1_NST + 2; i++) mbar_init(sbase + P1_OFF_BAR + i * 8, (i & 12) == 4 ? 16 : 1);
        asm volatile("fence.mbarrier_init.release.cluster;\n" ::: "memory");
        p1_load_w1(sbase, &wmap, blockIdx.x * 2, 2);
    }
    if (small) TSTAMP(0, 0);
    TSTAMP(1, 0);
    if (tid == 384) {
        for (int i = 0; i < P2_NB; i++) {
            mbar_init(bar_bfull + i * 8, 1);
            mbar_init(bar_bempty + i * 8, 24);
        }
        for (int i = 0; i < 3 * P2_NA; i++) {
            mbar_init(bar_afull + i * 8, 1);
            mbar_init(bar_aempty + i * 8, 4);
        }
        mbar_init(bar_xfull, 2);
        mbar_init(bar_oready, 4);
        asm volatile("st.shared.u32 [%0], 0;\n" ::"r"(s_pos) : "memory");
        asm volatile("fence.mbarrier_init.release.cluster;\n" ::: "memory");
    }
    __syncthreads();
    cluster_sync_relaxed();

    if (warp >= 12) {
        reg_dec<32>();
        if (small) {
#pragma unroll 1
            for (int j = 0; warp == 12 && j < 2 * NSMALL; j++) {
                const uint32_t bar = sbase + P1_OFF_BAR + (j & 3) * 8;
                if (!(j & 1)) {
                    flag_wait<true>(&g_flag[LN_RING + 3 + (j >> 1)][0][0], 8);
                    asm volatile("fence.proxy.async.global;\n" ::: "memory");
                }
                mbar_wait(bar + P1_NST * 8, (j >> 2) & 1);
                if (elect_one()) {
                    mbar_expect_tx(bar, P1_SLOT);
                    bulk_g2s_mc(sbase + (j & 3) * P1_SLOT + rank * (P1_SLOT / 2),
                                reinterpret_cast<const uint8_t*>(g_ln) + (size_t)(2 * (LN_RING + 3) + j) * P1_SLOT + rank * (P1_SLOT / 2), P1_SLOT / 2, bar, (uint16_t)3);
                }
                __syncwarp();
            }
            asm volatile("barrier.cluster.arrive.aligned;\nbarrier.cluster.wait.aligned;\n" ::: "memory");
        }
        if (warp == 12) {
            const uint8_t* wsrc = reinterpret_cast<const uint8_t*>(g_w2img) + rank * (P2_B / 2);
            int st = 0, ph = 1, kb = k0, m = 0, r = 0;
            const int busy = head ? 0 : tail ? P2_POS - 24 : P2_POS;
#pragma unroll 1
            for (int p = 0; p < P2_POS; p++) {
                if (p == 0 || p == P2_FOLD) {
                    if (p || par < 48) flag_wait<true>(&g_img[p != 0], p ? 96 * 4 : 48);
                    asm volatile("fence.proxy.async.global;\n" ::: "memory");
                    if (p) wsrc += sizeof(g_w2img[0]);
                }
                mbar_wait(bar_bempty + st * 8, ph);
                TR2P(p, 0);
                if (elect_one()) {
                    mbar_expect_tx(bar_bfull + st * 8, P2_B);
                    bulk_g2s_mc(sbase + st * P2_B + rank * (P2_B / 2), wsrc + kb * P2_B, P2_B / 2, bar_bfull + st * 8, (uint16_t)3);
                    asm volatile("st.volatile.shared.u32 [%0], %1;\n" ::"r"(s_pos), "r"(p) : "memory");
                    const int idle = 2 - min(m, P2_ITEMS - 1) + max(m - 2 + (r >= 48 - 2 * P2_LAG), 0) - ((unsigned)(p - busy) < 24);
                    if (idle) asm volatile("mbarrier.arrive.shared::cta.b64 _, [%0], %1;\n" ::"r"(bar_bempty + st * 8), "r"(idle * 8) : "memory");
                    if (rank == 0) asm volatile("red.relaxed.gpu.global.add.u32 [%0], 1;\n" ::"l"(&g_prog) : "memory");
                }
                __syncwarp();
                if (++st == P2_NB) { st = 0; ph ^= 1; }
                if (++kb == 48) kb = 0;
                if (++r == P2_LAG) { r = 0; m++; }
            }
            mbar_wait(bar_bempty + st * 8, ph);
            if (lane == 0) mbar_arrive(bar_bfull + st * 8);
#pragma unroll 1
            for (int p = 1; p < P2_NB; p++) {
                if (++st == P2_NB) { st = 0; ph ^= 1; }
                mbar_wait(bar_bempty + st * 8, ph);
            }
        } else if (warp == 13) {
            const uint8_t* src[3];
            int n[3], left[3], wrap[3];
            uint32_t st[3];
            auto item = [&](int w) {
                const int u = (k0 + p2_start(n[w])) % 48;
                left[w] = n[w] < 0 || n[w] == P2_ITEMS ? 24 : 48;
                wrap[w] = left[w] - (48 - u);
                src[w] = reinterpret_cast<const uint8_t*>(g_h) + (size_t)p2_tile(cl, n[w]) * (2 * H_TILE) + rank * H_HALF + u * H_STEP;
            };
#pragma unroll
            for (int w = 0; w < 3; w++) {
                n[w] = w == 2 && head ? -1 : w;
                st[w] = 0x80000000u;
                item(w);
            }
            if (par < (NUM_CTAS - 8 * NGRP) * 12) flag_wait<true>(&g_img[2], (NUM_CTAS - 8 * NGRP) * 12);
            bar_arrive(3, 416);
            gdc_wait();
            asm volatile("fence.proxy.async.global;\n" ::: "memory");
#pragma unroll 1
            for (int fin = 0; fin < 3;) {
                bool idle = true;
#pragma unroll
                for (int w = 0; w < 3; w++) {
                    const uint32_t o = (st[w] & 0xff) + w * P2_NA * 8;
                    if (left[w] >= 0 && mbar_test(bar_aempty + o, st[w] >> 31)) {
                        idle = false;
                        if (left[w] == 0) {
                            if (lane == 0) mbar_arrive(bar_afull + o);
                            left[w] = -1;
                            fin++;
                        } else {
                            if (elect_one()) {
                                mbar_expect_tx(bar_afull + o, P2_A);
                                bulk_g2s(sbase + P2_OFF_A + o * (P2_A / 8), src[w], P2_A, bar_afull + o);
                            }
                            __syncwarp();
                            src[w] += H_STEP;
                            st[w] += 8;
                            if ((st[w] & 0xff) == P2_NA * 8) st[w] ^= 0x80000000u | (P2_NA * 8);
                            if (--left[w] == wrap[w]) src[w] -= 48 * H_STEP;
                            if (left[w] == 0 && (n[w] += 3) < P2_ITEMS + tail) item(w);
                        }
                    }
                }
                if (idle) __nanosleep(64);
                SAFE_BREAK
            }
        } else if (warp == 14) {
            const uint32_t sx = sbase + P2_OFF_X;
            size_t o = 0;
            auto pace = [&](int target) {
                int v;
                while (true) {
                    asm volatile("ld.volatile.shared.u32 %0, [%1];\n" : "=r"(v) : "r"(s_pos) : "memory");
                    if (v * 16 >= target) break;
                    __nanosleep(100);
                    SAFE_BREAK
                }
            };
#pragma unroll 1
            for (int n = -head; n <= P2_ITEMS; n++) {
                const size_t on = (size_t)(2 * p2_tile(cl, n) + rank) * (64 * C_DIM * 2);
                const bool st = n + head > 0, ld = n < P2_ITEMS;
                if (st) mbar_wait(bar_oready, (n - 1 + head) & 1);
                TR2P(n + 1, 1);
                if (lane == 0) {
                    if (n == 1 && head) {
                        asm volatile("cp.async.bulk.wait_group 0;\nfence.proxy.async.global;\n" ::: "memory");
                        asm volatile("st.release.gpu.global.u32 [%0], 1;\n" ::"l"(&g_half[pair][rank]) : "memory");
                    }
                    if (ld) mbar_expect_tx(bar_xfull, 64 * C_DIM * 2);
                    const bool paced = st && n < P2_ITEMS - 1;
                    int t = (P2_LAG * (n - 1) + 52) * 16;
#pragma unroll 1
                    for (int c = 0; st && c < 64 * P2_XROW; c += P2_XC) {
                        if (paced) pace(t += 11);
                        bulk_s2g(reinterpret_cast<uint8_t*>(out) + o + c, sx + c + (c >= 32 * P2_XROW ? 64 : 0), P2_XC);
                        asm volatile("cp.async.bulk.commit_group;\n" ::: "memory");
                    }
#pragma unroll 1
                    for (int c = 0; ld && c < 64 * P2_XROW; c += P2_XC) {
                        if (c == 0) asm volatile("cp.async.bulk.wait_group.read 4;\n" ::: "memory");
                        if (c == 32 * P2_XROW) asm volatile("cp.async.bulk.wait_group.read 0;\n" ::: "memory");
                        if (paced) pace(t += 11);
                        bulk_g2s(sx + c + (c >= 32 * P2_XROW ? 64 : 0), reinterpret_cast<const uint8_t*>(x) + on + c, P2_XC, bar_xfull);
                    }
                    TR2P(n + 1, 2);
                    if (rank == 0 && n > 0 && n < P2_ITEMS - 2)
                        flag_wait<false>(&g_prog, P2_NCL * (P2_LAG * n + 48) + (tail ? P2_SHARED - P2_NCL : P2_SHARED) * P2_DELTA);
                    if (ld) mbar_arrive(bar_xfull);
                    TR2P(n + 1, 3);
                }
                __syncwarp();
                o = on;
            }
            asm volatile("cp.async.bulk.wait_group 0;\n" ::: "memory");
            TR2P(30, 1);
        }
    } else {
        reg_inc<160>();
        if (small) {
            if (warp < 8) p1_compute<2, 2>(sbase, blockIdx.x * 2, warp, lane, zero);
            else p1_w2(w2, grn_b, warp & 3, lane);
            asm volatile("barrier.cluster.arrive.aligned;\nbarrier.cluster.wait.aligned;\n" ::: "memory");
            TSTAMP(0, 30);
            early();
        }
        const int wg = warp >> 2, w = warp & 3, g = lane >> 2, q = lane & 3;
        const uint32_t sx = sbase + P2_OFF_X + (g & 1) * P2_XHALF + (w * 8 + (g >> 1)) * P2_XROW + q * 16;
        const uint32_t af = bar_afull + wg * P2_NA * 8;
        const uint32_t s_a = sbase + P2_OFF_A + wg * P2_NA * P2_A + (lane >> 3) * 512 + (lane & 7) * 64 +
                             ((w ^ ((lane & 7) >> 1)) << 4);
        uint32_t acc0[48], acc1[48];
        uint32_t up;
        uint4 a0[2], a1[2];
        uint32_t st = 0, ph = 0;

        {
            float4* s_red = reinterpret_cast<float4*>(smem + P2_OFF_RED);
            const float* sums = g_sums[par & 1];
            float gx[4], part = 0.f, mx = 0.f;
            asm volatile("prefetch.global.L2 [%0];\n" ::"l"(sums + HID + tid * 2) : "memory");
            TSTAMP(1, 27);
            bar_sync(3, 416);
            gdc_wait();
            TSTAMP(1, 1);
#pragma unroll
            for (int i = 0; i < 4; i++) gx[i] = __ldcg(sums + tid + 384 * i);
            const float bias = __ldcg(sums + HID + tid), asum = __ldcg(sums + HID + C_DIM + tid);
            float z = __uint_as_float(__reduce_max_sync(0xffffffffu, __float_as_uint(asum)));
            uint32_t bm = __reduce_max_sync(0xffffffffu, __float_as_uint(fabsf(bias)));
#pragma unroll
            for (int i = 0; i < 4; i++) {
                asm("sqrt.approx.f32 %0, %1;\n" : "=f"(gx[i]) : "f"(fmaf(gx[i], HSCALE * HSCALE, 1e-6f)));
                part += gx[i];
                gx[i] *= bf_lo(gg[i]);
                mx = fmaxf(mx, fabsf(gx[i]));
            }
#pragma unroll
            for (int o = 16; o > 0; o >>= 1) part += __shfl_xor_sync(0xffffffffu, part, o);
            mx = __uint_as_float(__reduce_max_sync(0xffffffffu, __float_as_uint(mx)));
            TSTAMP(1, 26);
            if (lane == 0) s_red[warp] = make_float4(part, mx, z, __uint_as_float(bm));
            bar_sync(1, 384);
            float tot = 0.f;
            {
                const float4 t = s_red[min(lane & 15, 11)];
                tot = (lane & 15) < 12 ? t.x : 0.f;
#pragma unroll
                for (int o = 8; o > 0; o >>= 1) tot += __shfl_xor_sync(0xffffffffu, tot, o);
                mx = __uint_as_float(__reduce_max_sync(0xffffffffu, __float_as_uint(t.y)));
                z = __uint_as_float(__reduce_max_sync(0xffffffffu, __float_as_uint(t.z)));
                bm = __reduce_max_sync(0xffffffffu, __float_as_uint(t.w));
            }
            const float inv = __fdividef(1.0f, fmaf(tot, 1.0f / HID, 1e-6f));
            const uint32_t e0 = acc_exp(z) - 9u;
            const uint32_t j = min(max(max(__float_as_uint(fmaf(mx, inv, 1.0f) * 1.01f) >> 23, 130u) - 130u, max(bm >> 23, e0 + 12u) - (e0 + 12u)), 126u);
            const float dn = __uint_as_float((127u - j) << 23) * (HSCALE * 1.00235f);
#pragma unroll
            for (int i = 0; i < 4; i++)
                *reinterpret_cast<uint16_t*>(smem + P2_OFF_GRN + (tid + 384 * i) * 2) = pack_f16(fmaf(gx[i], inv, 1.0f) * dn, 0.f);
            const uint32_t e = min(e0 + j, 253u);
            up = e * 0x00800080u;
#pragma unroll
            for (int i = 0; i < 2; i++)
                *reinterpret_cast<uint16_t*>(smem + P2_OFF_BIAS + (tid >> 1) * 8 + i * 4 + (tid & 1) * 2) = pack_f16(bias * __uint_as_float((254u - e) << 23), 0.f);
            TSTAMP(1, 25);
            bar_sync(1, 384);
            if (wg == 1 && blockIdx.x < 96) {
                const uint4* src = g_w2img[0] + blockIdx.x * 768 + tid - 128;
                const uint4 fk = *reinterpret_cast<const uint4*>(smem + P2_OFF_GRN + blockIdx.x * 32 + (tid & 8) * 2);
                uint4 v[6];
#pragma unroll
                for (int i = 0; i < 6; i++) v[i] = __ldcg(src + i * 128);
                auto fold = [&](uint32_t b, uint32_t f) { return (h2_mul(b, f) + 0x00040004u) & 0xfff8fff8u; };
#pragma unroll
                for (int i = 0; i < 6; i++)
                    g_w2img[1][blockIdx.x * 768 + tid - 128 + i * 128] = make_uint4(fold(v[i].x, fk.x), fold(v[i].y, fk.y), fold(v[i].z, fk.z), fold(v[i].w, fk.w));
                asm volatile("fence.proxy.async.global;\n" ::: "memory");
                __threadfence();
                __syncwarp();
                if (lane == 0) asm volatile("red.release.gpu.global.add.u32 [%0], 1;\n" ::"l"(&g_img[1]) : "memory");
            }
        }
        TSTAMP(1, 28);
        int kt = k0, pos;
        const uint32_t be = lane < 2 ? mapa(bar_bempty, lane) : 0, be0 = mapa(bar_bempty, 0);
        uint32_t prev = 0, sa = 0, pa = 0;
        auto release_b = [&](uint32_t p, bool on) {
            asm volatile("{\n.reg .pred p, q;\nsetp.ne.u32 q, %2, 0;\nsetp.ne.and.u32 p, %1, 0, q;\n@p mbarrier.arrive.shared::cluster.b64 _, [%0];\n}\n"
                         ::"r"(be + p), "r"(be), "r"((uint32_t)on) : "memory");
        };
        auto arrive1 = [&](uint32_t bar) {
            asm volatile("{\n.reg .pred p;\nsetp.eq.u32 p, %1, %2;\n@p mbarrier.arrive.shared::cta.b64 _, [%0];\n}\n" ::"r"(bar), "r"(be), "r"(be0) : "memory");
        };
        auto seek = [&](int p) {
            pos = p;
            st = p % P2_NB * 8;
            ph = p / P2_NB & 1;
            int v;
            while (true) {
                asm volatile("ld.volatile.shared.u32 %0, [%1];\n" : "=r"(v) : "r"(s_pos) : "memory");
                if (__all_sync(0xffffffffu, v >= p)) break;
                __nanosleep(200);
                SAFE_BREAK
            }
        };
        bool ok_a = false;
        auto fetch = [&](uint4 (&a)[2], uint32_t done, bool rel, bool early, bool wait = true) {
            if (!ok_a) mbar_wait(af + sa, pa);
            uint32_t o[6];
            const uint32_t src = s_a + sa * (P2_A / 8);
            asm volatile("ldmatrix.sync.aligned.m8n8.x4.trans.shared.b16 {%0,%1,%2,%3}, [%4];\n"
                         : "=r"(o[0]), "=r"(o[1]), "=r"(o[2]), "=r"(o[3]) : "r"(src) : "memory");
            asm volatile("ldmatrix.sync.aligned.m8n8.x2.trans.shared.b16 {%0,%1}, [%2];\n"
                         : "=r"(o[4]), "=r"(o[5]) : "r"(src + 2048) : "memory");
            if ((sa += 8) == P2_NA * 8) { sa = 0; pa ^= 1; }
            if (wait) wg_wait<1>();
            asm volatile("" ::"r"(a[0].x), "r"(a[0].y), "r"(a[0].z), "r"(a[0].w), "r"(a[1].x), "r"(a[1].y), "r"(a[1].z), "r"(a[1].w));
            release_b(done, rel);
            ok_a = mbar_test(af + sa, pa);
            const bool ok_b = mbar_test(bar_bfull + st, ph);
            p2_unpack(a[0], o[0], o[1], o[2]);
            p2_unpack(a[1], o[3], o[4], o[5]);
            if (early) {
                const uint32_t* t = reinterpret_cast<const uint32_t*>(smem + P2_OFF_GRN) + kt * 16 + q;
#pragma unroll
                for (int i = 0; i < 2; i++)
                    a[i] = make_uint4(h2_mul(a[i].x, t[8 * i]), h2_mul(a[i].y, t[8 * i]), h2_mul(a[i].z, t[8 * i + 4]), h2_mul(a[i].w, t[8 * i + 4]));
                if (++kt == 48) kt = 0;
            }
            if (!ok_b) mbar_wait(bar_bfull + st, ph);
        };
        const uint64_t db0 = make_desc(sbase, 128, 256);
        auto step = [&](const uint4 (&a)[2], uint4 (&an)[2], bool cont, bool add, bool early) {
            TR2(0);
            const uint64_t db = db0 + st * (P2_B / 128);
            wg_fence();
            mma_rs_n192(acc0, a[0], db, add);
            mma_rs_n192(acc1, a[0], db + 384, add);
            mma_rs_n192(acc0, a[1], db + 768, 1);
            mma_rs_n192(acc1, a[1], db + 768 + 384, 1);
            wg_commit();
            arrive1(af + 3 * P2_NA * 8 - 8 + (sa ? sa : P2_NA * 8));
            const uint32_t done = prev;
            prev = st;
            if ((st += 8) == P2_NB * 8) { st = 0; ph ^= 1; }
            fetch(an, done, cont, early);
            pos++;
        };
        int n = wg == 2 && head ? -1 : wg;
#pragma unroll
        for (int c = 0; c < 12; c++) p2_init(c < 6 ? acc0 : acc1, c, sbase + P2_OFF_BIAS + q * 32);
        a0[0] = a0[1] = a1[0] = a1[1] = make_uint4(zero, zero, zero, zero);
        seek(p2_start(n));
        fetch(a0, 0, false, n <= 0, false);
#pragma unroll 1
        for (;; n += 3) {
            TSTAMP(1, 2 + n);
            const int p0 = n < 0 || n == P2_ITEMS ? 12 : 0, pe = n <= 0 ? p0 + P2_FOLD / 2 : 0;
            const bool more = n + 3 < P2_ITEMS + tail;
#pragma unroll 1
            for (int p = p0; p < 24; p++) {
                step(a0, a1, p != p0, p != p0 || n != P2_ITEMS, p < pe);
                step(a1, a0, true, true, p < pe);
            }
            if (n == P2_ITEMS) {
                flag_wait<true>(&g_half[pair][rank], 1);
                TR2(1);
                wg_wait<0>();
                TR2(2);
                release_b(prev, true);
                uint8_t* o = reinterpret_cast<uint8_t*>(out) + (size_t)((2 * p2_tile(cl, -1) + rank) * 64 + (g & 1) * 32 + w * 8 + (g >> 1)) * P2_XROW + q * 16;
                p2_epilogue_add(acc0, o, up, zero);
                p2_epilogue_add(acc1, o + 384, up, zero);
                TR2(3);
                break;
            }
            mbar_wait(bar_xfull, (n + head) & 1);
            TR2(1);
            wg_wait<0>();
            TR2(2);
            release_b(prev, true);
            p2_epilogue(acc0, acc1, sx, sbase + P2_OFF_BIAS + q * 32, up, zero);
            TR2(3);
            asm volatile("fence.proxy.async.shared::cta;\n" ::: "memory");
            __syncwarp();
            arrive1(bar_oready);
            if (!more) break;
            ok_a = false;
            seek(p2_start(n + 3));
            mbar_wait(bar_bfull + st, ph);
        }
        if (blockIdx.x == 120 && threadIdx.x < (LN_RING + 3 + NSMALL) * 2) (&g_flag[0][0][0])[threadIdx.x * 8] = 0;
        if (blockIdx.x == 121 && threadIdx.x == 0) atomicAdd(&g_epoch, 1u);
        TSTAMP(1, 30);
    }
}

}

extern "C" void kernel_launch(void* const* d_in, const int* in_sizes, int n_in, void* d_out, int out_size) {
    const __nv_bfloat16* x = (const __nv_bfloat16*)d_in[0];
    const __nv_bfloat16* dw = (const __nv_bfloat16*)d_in[1];
    const __nv_bfloat16* w1 = (const __nv_bfloat16*)d_in[2];
    const __nv_bfloat16* w2 = (const __nv_bfloat16*)d_in[3];
    const __nv_bfloat16* grn_g = (const __nv_bfloat16*)d_in[4];
    const __nv_bfloat16* grn_b = (const __nv_bfloat16*)d_in[5];
    __nv_bfloat16* out = (__nv_bfloat16*)d_out;

    cudaFuncSetAttribute(pass1_kernel<2>, cudaFuncAttributeMaxDynamicSharedMemorySize, P1_SMEM);
    cudaFuncSetAttribute(pass1_kernel<8>, cudaFuncAttributeMaxDynamicSharedMemorySize, P1_SMEM);
    cudaFuncSetAttribute(pass2_kernel, cudaFuncAttributeMaxDynamicSharedMemorySize, P2_SMEM);

    typedef CUresult (*EncodeFn)(CUtensorMap*, CUtensorMapDataType, cuuint32_t, void*, const cuuint64_t*, const cuuint64_t*,
                                 const cuuint32_t*, const cuuint32_t*, CUtensorMapInterleave, CUtensorMapSwizzle,
                                 CUtensorMapL2promotion, CUtensorMapFloatOOBfill);
    static EncodeFn encode = nullptr;
    if (!encode) {
        cudaDriverEntryPointQueryResult qres;
        cudaGetDriverEntryPoint("cuTensorMapEncodeTiled", (void**)&encode, cudaEnableDefault, &qres);
    }
    CUtensorMap wmap;
    const cuuint64_t gdim[2] = {HID, C_DIM};
    const cuuint64_t gstr[1] = {HID * 2};
    const cuuint32_t box[2] = {64, 192}, estr[2] = {1, 1};
    CUresult er = encode(&wmap, CU_TENSOR_MAP_DATA_TYPE_BFLOAT16, 2, (void*)w1, gdim, gstr, box, estr, CU_TENSOR_MAP_INTERLEAVE_NONE,
           CU_TENSOR_MAP_SWIZZLE_128B, CU_TENSOR_MAP_L2_PROMOTION_L2_128B, CU_TENSOR_MAP_FLOAT_OOB_FILL_NONE);
    if (er != CUDA_SUCCESS) printf("tensor map encode failed %d\n", (int)er);

    cudaLaunchAttribute attr[1];
    attr[0].id = cudaLaunchAttributeProgrammaticStreamSerialization;
    attr[0].val.programmaticStreamSerializationAllowed = 1;
    cudaLaunchConfig_t cfg = {};
    cfg.stream = 0;
    cfg.blockDim = dim3(512);
    cfg.dynamicSmemBytes = P1_SMEM;
    static int wide = -1;
    if (wide < 0) {
        int n = 0;
        cfg.gridDim = dim3(8 * NGRP);
        wide = cudaOccupancyMaxActiveClusters(&n, pass1_kernel<8>, &cfg) == cudaSuccess && n >= NGRP;
    }
    if (wide) pass1_kernel<8><<<8 * NGRP, 512, P1_SMEM>>>(wmap, x, dw, w1, 0);
    else pass1_kernel<2><<<8 * NGRP, 512, P1_SMEM>>>(wmap, x, dw, w1, 0);
    cfg.attrs = attr;
    cfg.numAttrs = 1;
    cfg.gridDim = dim3(NUM_CTAS);
    cfg.dynamicSmemBytes = P2_SMEM;
    cudaLaunchKernelEx(&cfg, pass2_kernel, wmap, x, w2, grn_g, grn_b, out, 0);
}
```

```cpp
#include <cuda.h>
#include <cuda_runtime.h>
#include <cuda_bf16.h>
#include <stdint.h>
#include <stdio.h>

namespace {

constexpr int M_TOTAL = 384 * 384;
constexpr int C_DIM   = 384;
constexpr int HID     = 1536;
constexpr int NT128   = M_TOTAL / 128;
constexpr int NUM_CTAS = 132;

constexpr int NGRP = 15, NSMALL = 100;
constexpr int LN_STEP = 2 * NGRP, LN_RING = 2 * LN_STEP;
__device__ __forceinline__ int p1_tile(int t) { return t < LN_STEP ? t : t + min((t - LN_STEP) / 10 + 1, NSMALL); }
__device__ __forceinline__ int p1_place(int tile, int slot) {
    const int i = (tile + 3) / 11;
    return i * 11 == tile + 3 && (unsigned)(i - 3) < NSMALL ? LN_RING + i : slot;
}
constexpr int LN_TILE = 128 * C_DIM * 2;
constexpr int H_TILE = 64 * HID * 3 / 2;
constexpr int H_HALF = 3072, H_STEP = 6144;

__device__ __align__(1024) uint4 g_h[(size_t)M_TOTAL * HID * 3 / 32];
__device__ __align__(1024) uint4 g_ln[(LN_RING + 3 + NSMALL) * LN_TILE / 16];
__device__ __align__(1024) uint4 g_w2img[2][HID * C_DIM * 2 / 16];
__device__ __align__(16) float g_sums[2][HID + 2 * C_DIM];
__device__ __align__(16) unsigned g_ex[HID];
__device__ unsigned g_epoch;
__device__ __align__(128) unsigned g_img[3];
__device__ __align__(128) unsigned g_prog;
__device__ __align__(128) unsigned g_half[32][2];
__device__ unsigned g_flag[LN_RING + 3 + NSMALL][2][8];
#define TSTAMP(k, i)
#define STAMPT(t, i)
#define TRACE(wg, pos, i)
#define TRACEW(pos, i)

#define TR2(i)
#define TR2P(pos, i)
__host__ __device__ __forceinline__ int perm32(int n) {
    return (n & ~31) | (((n >> 1) & 3) << 3) | (((n >> 3) & 3) << 1) | (n & 1);
}

__device__ __forceinline__ uint32_t smem_u32(const void* p) { return (uint32_t)__cvta_generic_to_shared(p); }

__device__ __forceinline__ void mbar_init(uint32_t bar, uint32_t count) {
    asm volatile("mbarrier.init.shared::cta.b64 [%0], %1;\n" ::"r"(bar), "r"(count) : "memory");
}
__device__ __forceinline__ void mbar_expect_tx(uint32_t bar, uint32_t bytes) {
    asm volatile("mbarrier.arrive.expect_tx.shared::cta.b64 _, [%0], %1;\n" ::"r"(bar), "r"(bytes) : "memory");
}
__device__ __forceinline__ void mbar_arrive(uint32_t bar) {
    asm volatile("mbarrier.arrive.shared::cta.b64 _, [%0];\n" ::"r"(bar) : "memory");
}
__device__ __forceinline__ void mbar_arrive_cluster(uint32_t bar_cluster_addr) {
    asm volatile("mbarrier.arrive.shared::cluster.b64 _, [%0];\n" ::"r"(bar_cluster_addr) : "memory");
}
#define SAFE_BREAK
__device__ __forceinline__ void mbar_wait(uint32_t bar, uint32_t parity) {
    asm volatile(
        "{\n"
        ".reg .pred p;\n"
        "LAB_WAIT:\n"
        "mbarrier.try_wait.parity.shared::cta.b64 p, [%0], %1;\n"
        "@!p bra LAB_WAIT;\n"
        "}\n" ::"r"(bar), "r"(parity) : "memory");
}
__device__ __forceinline__ bool mbar_test(uint32_t bar, uint32_t parity) {
    uint32_t ok;
    asm volatile("{\n.reg .pred p;\n"
                 "mbarrier.test_wait.parity.shared::cta.b64 p, [%1], %2;\n"
                 "selp.u32 %0, 1, 0, p;\n}\n" : "=r"(ok) : "r"(bar), "r"(parity) : "memory");
    return ok != 0;
}
__device__ __forceinline__ uint32_t mapa(uint32_t addr, uint32_t rank) {
    uint32_t r;
    asm volatile("mapa.shared::cluster.u32 %0, %1, %2;\n" : "=r"(r) : "r"(addr), "r"(rank));
    return r;
}
__device__ __forceinline__ void bulk_g2s(uint32_t dst, const void* src, uint32_t bytes, uint32_t bar) {
    asm volatile("cp.async.bulk.shared::cluster.global.mbarrier::complete_tx::bytes [%0], [%1], %2, [%3];\n"
                 ::"r"(dst), "l"(src), "r"(bytes), "r"(bar) : "memory");
}
__device__ __forceinline__ void bulk_g2s_mc(uint32_t dst, const void* src, uint32_t bytes, uint32_t bar, uint16_t mask) {
    asm volatile("cp.async.bulk.shared::cluster.global.mbarrier::complete_tx::bytes.multicast::cluster [%0], [%1], %2, [%3], %4;\n"
                 ::"r"(dst), "l"(src), "r"(bytes), "r"(bar), "h"(mask) : "memory");
}
__device__ __forceinline__ void tma2(uint32_t dst, const CUtensorMap* map, int c0, int c1, uint32_t bar) {
    asm volatile("cp.async.bulk.tensor.2d.shared::cluster.global.tile.mbarrier::complete_tx::bytes [%0], [%1, {%2, %3}], [%4];\n"
                 ::"r"(dst), "l"(map), "r"(c0), "r"(c1), "r"(bar) : "memory");
}
template <bool ACQ>
__device__ __forceinline__ uint32_t flag_wait(const unsigned* p, unsigned target) {
    unsigned v, n = 0;
    do {
        if (ACQ) asm volatile("ld.acquire.gpu.global.u32 %0, [%1];\n" : "=r"(v) : "l"(p) : "memory");
        else asm volatile("ld.relaxed.gpu.global.u32 %0, [%1];\n" : "=r"(v) : "l"(p) : "memory");
        n++;
    } while (v < target);
    return n == 1;
}
__device__ __forceinline__ void ldsm4t(uint32_t (&r)[4], uint32_t addr) {
    asm volatile("ldmatrix.sync.aligned.m8n8.x4.trans.shared.b16 {%0,%1,%2,%3}, [%4];\n"
                 : "=r"(r[0]), "=r"(r[1]), "=r"(r[2]), "=r"(r[3]) : "r"(addr) : "memory");
}
__device__ __forceinline__ void bulk_s2g(void* dst, uint32_t src, uint32_t bytes) {
    asm volatile("cp.async.bulk.global.shared::cta.bulk_group [%0], [%1], %2;\n" ::"l"(dst), "r"(src), "r"(bytes) : "memory");
}
__device__ __forceinline__ void gdc_wait() { asm volatile("griddepcontrol.wait;\n" ::: "memory"); }
__device__ __forceinline__ void gdc_launch() { asm volatile("griddepcontrol.launch_dependents;\n" ::: "memory"); }
__device__ __forceinline__ uint32_t cluster_rank() {
    uint32_t r;
    asm volatile("mov.u32 %0, %%cluster_ctarank;\n" : "=r"(r));
    return r;
}
__device__ __forceinline__ bool elect_one() {
    uint32_t pred;
    asm volatile("{\n.reg .pred p;\nelect.sync _|p, 0xffffffff;\nselp.u32 %0, 1, 0, p;\n}\n" : "=r"(pred));
    return pred != 0;
}
__device__ __forceinline__ void wg_fence() { asm volatile("wgmma.fence.sync.aligned;\n" ::: "memory"); }
__device__ __forceinline__ void wg_commit() { asm volatile("wgmma.commit_group.sync.aligned;\n" ::: "memory"); }
template <int N> __device__ __forceinline__ void wg_wait() {
    asm volatile("wgmma.wait_group.sync.aligned %0;\n" ::"n"(N) : "memory");
}
template <int R> __device__ __forceinline__ void reg_inc() { asm volatile("setmaxnreg.inc.sync.aligned.u32 %0;\n" ::"n"(R)); }
template <int R> __device__ __forceinline__ void reg_dec() { asm volatile("setmaxnreg.dec.sync.aligned.u32 %0;\n" ::"n"(R)); }
__device__ __forceinline__ void bar_sync(int id, int n) { asm volatile("bar.sync %0, %1;\n" ::"r"(id), "r"(n) : "memory"); }
__device__ __forceinline__ void bar_arrive(int id, int n) { asm volatile("bar.arrive %0, %1;\n" ::"r"(id), "r"(n) : "memory"); }

__device__ __forceinline__ uint64_t make_desc(uint32_t saddr, uint32_t lbo, uint32_t sbo) {
    return (uint64_t)((saddr & 0x3FFFF) >> 4) | ((uint64_t)(lbo >> 4) << 16) | ((uint64_t)(sbo >> 4) << 32);
}

__device__ __forceinline__ void stg128_cs(void* p, uint32_t a, uint32_t b, uint32_t c, uint32_t d) {
    asm volatile("st.global.cs.v4.u32 [%0], {%1,%2,%3,%4};\n" ::"l"(p), "r"(a), "r"(b), "r"(c), "r"(d) : "memory");
}
__device__ __forceinline__ uint32_t pack_bf16(float lo, float hi) {
    uint32_t r;
    asm("cvt.rn.bf16x2.f32 %0, %1, %2;\n" : "=r"(r) : "f"(hi), "f"(lo));
    return r;
}
__device__ __forceinline__ float bf_lo(uint32_t v) { return __uint_as_float(v << 16); }
__device__ __forceinline__ float bf_hi(uint32_t v) { return __uint_as_float(v & 0xffff0000u); }
__device__ __forceinline__ uint32_t bf2_mul(uint32_t a, uint32_t b) {
    uint32_t r;
    asm("mul.rn.bf16x2 %0, %1, %2;\n" : "=r"(r) : "r"(a), "r"(b));
    return r;
}
__device__ __forceinline__ uint32_t bf2_fma(uint32_t a, uint32_t b, uint32_t c) {
    uint32_t r;
    asm("fma.rn.bf16x2 %0, %1, %2, %3;\n" : "=r"(r) : "r"(a), "r"(b), "r"(c));
    return r;
}
__device__ __forceinline__ uint32_t bf2_add(uint32_t a, uint32_t b) {
    uint32_t r;
    asm("add.rn.bf16x2 %0, %1, %2;\n" : "=r"(r) : "r"(a), "r"(b));
    return r;
}
constexpr float KAPPA = 0.3292034911525734f;
constexpr float GELU_C = 2.423681954311584f;
constexpr float HSCALE = 1.0f / (2.0f * KAPPA);
__device__ __forceinline__ uint32_t acc_exp(float z) { return max(__float_as_uint(z) >> 23, 10u); }
__device__ __forceinline__ void sched_break(int zero) {
    asm volatile("{\n.reg .pred p;\nsetp.ne.s32 p, %0, 0;\nSB_LOOP:\n@p nanosleep.u32 1;\n@p bra SB_LOOP;\n}\n" ::"r"(zero));
}

#define ACCR8(d, o) "+r"(d[o + 0]), "+r"(d[o + 1]), "+r"(d[o + 2]), "+r"(d[o + 3]), "+r"(d[o + 4]), "+r"(d[o + 5]), "+r"(d[o + 6]), "+r"(d[o + 7])
__device__ __forceinline__ void mma_rs_n128(uint32_t (&d)[32], const uint32_t (&a)[4], uint64_t desc, int scale_d) {
    asm volatile(
        "{\n.reg .pred p;\nsetp.ne.b32 p, %37, 0;\n"
        "wgmma.mma_async.sync.aligned.m64n128k16.f16.f16.f16 "
        "{%0,%1,%2,%3,%4,%5,%6,%7,%8,%9,%10,%11,%12,%13,%14,%15,"
        "%16,%17,%18,%19,%20,%21,%22,%23,%24,%25,%26,%27,%28,%29,%30,%31},"
        "{%32,%33,%34,%35}, %36, p, 1, 1, 0;\n}\n"
        : ACCR8(d, 0), ACCR8(d, 8), ACCR8(d, 16), ACCR8(d, 24)
        : "r"(a[0]), "r"(a[1]), "r"(a[2]), "r"(a[3]), "l"(desc), "r"(scale_d));
}
__device__ __forceinline__ void mma_ss_n128(uint32_t (&d)[32], uint64_t da, uint64_t db) {
    asm volatile(
        "{\n.reg .pred p;\nsetp.ne.b32 p, %34, 0;\n"
        "wgmma.mma_async.sync.aligned.m64n128k16.f16.f16.f16 "
        "{%0,%1,%2,%3,%4,%5,%6,%7,%8,%9,%10,%11,%12,%13,%14,%15,"
        "%16,%17,%18,%19,%20,%21,%22,%23,%24,%25,%26,%27,%28,%29,%30,%31},"
        "%32, %33, p, 1, 1, 0, 0;\n}\n"
        : ACCR8(d, 0), ACCR8(d, 8), ACCR8(d, 16), ACCR8(d, 24)
        : "l"(da), "l"(db), "r"(1));
}
__device__ __forceinline__ uint32_t bf2_as_h2(uint32_t v) { return (v & 0x0fff0fffu) * 7u + v; }
__device__ __forceinline__ float h_lo(uint32_t v) {
    float r;
    asm("{\n.reg .b16 l, h;\nmov.b32 {l, h}, %1;\ncvt.f32.f16 %0, l;\n}\n" : "=f"(r) : "r"(v));
    return r;
}
__device__ __forceinline__ float h_hi(uint32_t v) {
    float r;
    asm("{\n.reg .b16 l, h;\nmov.b32 {l, h}, %1;\ncvt.f32.f16 %0, h;\n}\n" : "=f"(r) : "r"(v));
    return r;
}

__device__ __forceinline__ void mma_rs_n192(uint32_t (&d)[48], const uint4& a, uint64_t db, int scale_d) {
    asm volatile(
        "{\n.reg .pred p;\nsetp.ne.b32 p, %53, 0;\n"
        "wgmma.mma_async.sync.aligned.m64n192k16.f16.f16.f16 "
        "{%0,%1,%2,%3,%4,%5,%6,%7,%8,%9,%10,%11,%12,%13,%14,%15,"
        "%16,%17,%18,%19,%20,%21,%22,%23,%24,%25,%26,%27,%28,%29,%30,%31,"
        "%32,%33,%34,%35,%36,%37,%38,%39,%40,%41,%42,%43,%44,%45,%46,%47},"
        "{%48,%49,%50,%51}, %52, p, 1, 1, 0;\n}\n"
        : ACCR8(d, 0), ACCR8(d, 8), ACCR8(d, 16), ACCR8(d, 24), ACCR8(d, 32), ACCR8(d, 40)
        : "r"(a.x), "r"(a.y), "r"(a.z), "r"(a.w), "l"(db), "r"(scale_d));
}

__device__ __forceinline__ uint32_t pack_f16(float lo, float hi) {
    uint32_t r;
    asm("cvt.rn.f16x2.f32 %0, %1, %2;\n" : "=r"(r) : "f"(hi), "f"(lo));
    return r;
}

constexpr int P1_IMG = 900;
constexpr int P1_SLOT = LN_TILE / 2, P1_NST = 4;
constexpr int P1_X = 16 * C_DIM * 2;
constexpr int P1_OFF_A = P1_SLOT * P1_NST;
constexpr int P1_OFF_DW = P1_OFF_A + 3 * 2048;
constexpr int P1_OFF_X = P1_OFF_DW + C_DIM * 2;
constexpr int P1_OFF_BAR = P1_OFF_X + 2 * P1_X;
constexpr int P1_OFF_TILE = P1_OFF_BAR + (2 * P1_NST + 3 + 2 + 3 + 2) * 8;
constexpr int P1_SMEM = P1_OFF_TILE + 64;

__device__ __forceinline__ float rsqrt_fast(float x) {
    float r;
    asm("rsqrt.approx.ftz.f32 %0, %1;\n" : "=f"(r) : "f"(x));
    return r;
}
__device__ __forceinline__ float sum8(const uint32_t (&c)[4]) {
    const uint32_t u = bf2_add(bf2_add(c[0], c[1]), bf2_add(c[2], c[3]));
    return bf_lo(u) + bf_hi(u);
}
__device__ __forceinline__ void lds128(uint32_t (&v)[4], uint32_t a) {
    asm volatile("ld.shared.v4.u32 {%0,%1,%2,%3}, [%4];\n" : "=r"(v[0]), "=r"(v[1]), "=r"(v[2]), "=r"(v[3]) : "r"(a) : "memory");
}
template <class F>
__device__ __forceinline__ void ln_row(uint32_t (&v)[6][4], uint32_t sdw, F after_loads) {
    uint32_t c[4], s[4], d[4], nm;
#pragma unroll
    for (int i = 0; i < 6; i++) {
        lds128(d, sdw + i * 128);
        if (i == 0) {
#pragma unroll
            for (int k = 0; k < 4; k++) c[k] = bf2_mul(v[0][k], d[k]);
            const float p = sum8(c) * -0.125f;
            nm = pack_bf16(p, p);
        }
#pragma unroll
        for (int k = 0; k < 4; k++) {
            v[i][k] = bf2_fma(v[i][k], d[k], nm);
            s[k] = i ? bf2_add(v[i][k], s[k]) : v[i][k];
            c[k] = i ? bf2_fma(v[i][k], v[i][k], c[k]) : bf2_mul(v[i][k], v[i][k]);
        }
    }
    after_loads(c[0]);
    float m = fmaf(sum8(s), 1.0f / 48, -bf_lo(nm));
    float q = fmaf(-bf_lo(nm), fmaf(2.f, m, bf_lo(nm)), sum8(c) * (1.0f / 48));
#pragma unroll
    for (int o = 1; o < 8; o <<= 1) {
        m += __shfl_xor_sync(0xffffffffu, m, o);
        q += __shfl_xor_sync(0xffffffffu, q, o);
    }
    m *= 0.125f;
    const float r = KAPPA * rsqrt_fast(fmaxf(fmaf(-m, m, q * 0.125f), 0.f) + 1e-5f);
    const float e = (-bf_lo(nm) - m) * r * 0x1p-112f;
    const bool two = __any_sync(0xffffffffu, r < 0x1p-14f);
    const float r1 = r * (two ? 0x1p-56f : 0x1p-112f);
    uint32_t mul = pack_bf16(r1, r1), add = two ? 0u : pack_bf16(e, e);
#pragma unroll 1
    for (int it = !two; it < 2; it++) {
#pragma unroll
        for (int i = 0; i < 6; i++)
#pragma unroll
            for (int k = 0; k < 4; k++) v[i][k] = bf2_fma(v[i][k], mul, add);
        mul = 0x23802380u;
        add = pack_bf16(e, e);
    }
#pragma unroll
    for (int i = 0; i < 6; i++)
#pragma unroll
        for (int k = 0; k < 4; k++) v[i][k] = bf2_as_h2(v[i][k]);
}

__device__ __forceinline__ float gelu_s(float y) {
    float u = y * fmaf(y, y, GELU_C);
    float t;
    asm volatile("tanh.approx.f32 %0, %1;\n" : "=f"(t) : "f"(u));
    return fmaf(y, t, y);
}
__device__ __forceinline__ void p1_pack(int c, uint32_t (&p)[4], uint32_t (&dd)[4]) {
#pragma unroll
    for (int u = 0; u < 4; u++) {
        if ((c & 3) == 0) dd[u] = p[u];
        else {
            uint32_t n = dd[u];
            if ((c & 3) == 1) n = __byte_perm(n, 0, 0x2301);
            if ((c & 3) == 2) {
                dd[u] = __byte_perm(n >> 3, n >> 1, 0x6341);
                n = __byte_perm(n >> 3, n >> 1, 0x7250);
            }
            asm("lop3.b32 %0, %0, %1, 0x40074007, 0xd8;\n" : "+r"(p[u]) : "r"(n));
        }
    }
}
__device__ __forceinline__ void p1_store(int c, const uint32_t (&p)[4], uint8_t* hptr) {
    if (c & 3) stg128_cs(hptr + (c >> 2) * H_HALF + ((c & 3) - 1) * 512, p[0], p[1], p[2], p[3]);
}

template <bool GEN>
__device__ __forceinline__ void p1_epilogue(uint32_t (&acc)[32], float (&ssq)[2], uint32_t sc2, uint8_t* hp, int zero) {
    uint32_t sq[2], dd[4];
#pragma unroll
    for (int c = 0; c < 8; c++) {
        if (GEN) sched_break(zero);
        uint32_t p[4];
#pragma unroll
        for (int u = 0; u < 4; u++) {
            const uint32_t y = acc[8 * (c >> 1) + 2 * u + (c & 1)];
            if (GEN) {
                const float sc = c & 1 ? bf_hi(sc2) : bf_lo(sc2), fs = __uint_as_float(0x78000000u - __float_as_uint(sc));
                const float g0 = gelu_s(h_lo(y) * fs), g1 = gelu_s(h_hi(y) * fs);
                ssq[c & 1] = fmaf(g1, g1, fmaf(g0, g0, ssq[c & 1]));
                p[u] = pack_f16(g0 * sc, g1 * sc);
            } else {
                uint32_t g;
                asm("{\n.reg .b32 w;\n"
                    "fma.rn.f16x2 w, %1, %1, %2;\n"
                    "mul.rn.f16x2 w, w, %1;\n"
                    "tanh.approx.f16x2 w, w;\n"
                    "fma.rn.f16x2 %0, %1, w, %1;\n}\n" : "=r"(g) : "r"(y), "r"(0x40d940d9u));
                acc[8 * (c >> 1) + 2 * u + (c & 1)] = g;
                if (c < 2 && u == 0) asm("mul.rn.f16x2 %0, %1, %1;\n" : "=r"(sq[c & 1]) : "r"(g));
                else asm("fma.rn.f16x2 %0, %1, %1, %0;\n" : "+r"(sq[c & 1]) : "r"(g));
                if (c & 1) asm("{\n.reg .b16 l, h;\n.reg .b32 f;\nmov.b32 {l, h}, %2;\nmov.b32 f, {h, h};\nmul.rn.f16x2 %0, %1, f;\n}\n" : "=r"(p[u]) : "r"(g), "r"(sc2));
                else asm("{\n.reg .b16 l, h;\n.reg .b32 f;\nmov.b32 {l, h}, %2;\nmov.b32 f, {l, l};\nmul.rn.f16x2 %0, %1, f;\n}\n" : "=r"(p[u]) : "r"(g), "r"(sc2));
            }
        }
        p1_pack(c, p, dd);
        if (c & 3) {
#pragma unroll
            for (int u = 0; u < 4; u++) acc[4 * (c - 1 - (c >> 2)) + u] = p[u];
        }
        p1_store(c, p, hp);
    }
    if (!GEN) {
#pragma unroll
        for (int r = 0; r < 2; r++) ssq[r] += h_lo(sq[r]) + h_hi(sq[r]);
    }
}
template <int CS, int NWG>
__device__ __forceinline__ void p1_compute(uint32_t sbase, int cb0, int warp, int lane, int zero) {
    const uint32_t bar_full = sbase + P1_OFF_BAR, bar_empty = bar_full + P1_NST * 8, bar_w = bar_empty + P1_NST * 8;
    const int wg = warp >> 2, w = warp & 3, cb = cb0 + wg;
    const uint32_t slot_free = mapa(bar_empty, lane & (CS - 1)) + (lane / CS) * 8;
    if (lane < 4 * CS && lane / CS != 1 + wg && (NWG == 2 || wg || lane >= CS)) mbar_arrive_cluster(slot_free);
    if (wg == 1) bar_arrive(1, 256);
    uint32_t a[24][4], ex[2], gen = 0;
    const uint32_t wsrc = sbase + (1 + wg) * P1_SLOT + ((lane >> 4) * 8 + (lane & 7)) * 128 + (((2 * w + ((lane >> 3) & 1)) ^ (lane & 7)) << 4);
#pragma unroll 1
    for (int it = 0; it < 2; it++) {
        if (it) mbar_wait(bar_w + wg * 8, 0);
        TRACEW(110 + warp, 5);
        if (it || wg == 0) {
#pragma unroll
        for (int k = 0; k < 24; k++) ldsm4t(a[k], wsrc + k * 2048);
#pragma unroll
        for (int r = 0; r < 2; r++) {
            float t = 0.f;
#pragma unroll
            for (int j = 0; j < 6; j++) {
                uint32_t c = bf2_mul(a[4 * j][r], a[4 * j][r]);
#pragma unroll
                for (int k = 1; k < 8; k++) c = bf2_fma(a[4 * j + k / 2][r + (k & 1) * 2], a[4 * j + k / 2][r + (k & 1) * 2], c);
                t += bf_lo(c) + bf_hi(c);
            }
            t += __shfl_xor_sync(0xffffffffu, t, 1);
            t += __shfl_xor_sync(0xffffffffu, t, 2);
            asm("sqrt.approx.f32 %0, %0;\n" : "+f"(t));
            ex[r] = min(max(__float_as_uint(13.9f * t) >> 23, 72u), 198u);
        }
        asm volatile("{\n.reg .pred p;\nsetp.gt.u32 p, %1, 7;\nbar.red.or.pred p, %2, 128, p;\nselp.u32 %0, 1, 0, p;\n}\n"
                     : "=r"(gen) : "r"(max(ex[0] - 125u, ex[1] - 125u)), "r"(5 + wg) : "memory");
        gen = __shfl_sync(0xffffffffu, gen, 0) & it;
        if (it) {
            if ((lane & 3) < 2) g_ex[cb * 64 + w * 16 + (lane & 1) * 8 + (lane >> 2)] = lane & 1 ? ex[1] : ex[0];
            if (lane / CS == 1 + wg) mbar_arrive_cluster(slot_free);
            __syncwarp();
        }
        }
        if (gen) {
#pragma unroll
            for (int k = 0; k < 24; k++)
#pragma unroll
                for (int j = 0; j < 4; j++) a[k][j] = bf2_mul(a[k][j], (268u - ex[j & 1]) * 0x00800080u);
        }
        if (it || wg == 1) {
#pragma unroll
            for (int k = 0; k < 24; k++)
#pragma unroll
                for (int j = 0; j < 4; j++) {
                    a[k][j] = bf2_as_h2(bf2_mul(a[k][j], 0x07800780u));
                    asm volatile("" : "+r"(a[k][j]));
                }
        }
        TRACEW(110 + warp, 6);
    }
#pragma unroll
    for (int j = 0; j < 4; j++)
        asm volatile("st.shared.u32 [%0], %1;\n" ::"r"(sbase + P1_OFF_A + warp * 512 + (j & 1) * 256 + (j >> 1) * 128 + lane * 4), "r"(a[23][j]) : "memory");
    asm volatile("fence.proxy.async.shared::cta;\n" ::: "memory");
    TRACEW(110 + warp, 7);
    const uint32_t ex2 = ex[0] | ex[1] << 16;
    const uint32_t sc2 = gen ? 0x7f007f00u - (ex2 << 7) : (0x008e008eu - ex2) << 10;
    const uint32_t empty_remote = mapa(bar_empty, lane & (CS - 1));
    const int g = lane >> 2, q = lane & 3, turn = wg + 1 == NWG ? 1 : wg + 2;
    float ssq[2] = {0.f, 0.f};
    uint32_t acc[32] = {};
    TSTAMP(0, 1);
    STAMPT(128, 4);
    STAMPT(256, 5);

    uint8_t* hp = reinterpret_cast<uint8_t*>(g_h) + ((cb * 2 + (w >> 1)) * H_STEP + (w & 1) * 1536) + g * 64 + (q ^ (g >> 1)) * 16;
    const uint64_t desc_base = make_desc(sbase, 16, 1024) | (1ull << 62);
    const uint64_t da = make_desc(sbase + P1_OFF_A + wg * 2048, 128, 256);
#pragma unroll 1
    for (int i = 0;; i++) {
        const int s0 = (i & 1) * 16, par = (i >> 1) & 1;
        const uint64_t d0 = desc_base + (uint64_t)((i & 1) * (LN_TILE / 16));
        TRACE(wg, i, 0);
        mbar_wait(bar_full + s0, par);
        bar_sync(1 + wg, 256);
        TRACE(wg, i, 1);
        uint32_t step, more;
        wg_fence();
#pragma unroll
        for (int k = 0; k < 24; k++) {
            if (k == 12) mbar_wait(bar_full + s0 + 8, par);
            const uint64_t db = d0 + (uint64_t)((k >> 2) * 1024 + (k & 3) * 2);
            if (k < 23) mma_rs_n128(acc, a[k], db, k ? 1 : zero);
            else mma_ss_n128(acc, da, db);
            if (k == 23) bar_arrive(turn, 256);
            if (k % 12 == 11) wg_commit();
        }
        if (NWG == 2) {
            step = (i ? 11 : LN_STEP) * (2 * H_TILE);
            more = i + 1 < NSMALL;
        } else asm volatile("ld.shared.v2.u32 {%0, %1}, [%2];\n" : "=r"(step), "=r"(more) : "r"(sbase + P1_OFF_TILE + (i & 3) * 16) : "memory");
        TRACE(wg, i, 2);
        wg_wait<1>();
        if (lane < CS) mbar_arrive_cluster(empty_remote + s0);
        hp += step;
        TRACE(wg, i, 3);
        wg_wait<0>();
        TRACE(wg, i, 4);
        if (lane < CS) mbar_arrive_cluster(empty_remote + s0 + 8);
        if (gen) p1_epilogue<true>(acc, ssq, sc2, hp, zero);
        else p1_epilogue<false>(acc, ssq, sc2, hp, zero);
        if (!more) break;
    }
    TSTAMP(0, 21);
    if (wg == 0) bar_sync(1, 256);
    uint32_t par;
    if (NWG == 2) par = __ldcg(&g_epoch) & 1;
    else asm volatile("ld.shared.u32 %0, [%1];\n" : "=r"(par) : "r"(sbase + P1_OFF_TILE - 4) : "memory");
    float* sums = g_sums[par];
#pragma unroll
    for (int r = 0; r < 2; r++) {
        ssq[r] += __shfl_xor_sync(0xffffffffu, ssq[r], 1);
        ssq[r] += __shfl_xor_sync(0xffffffffu, ssq[r], 2);
        if (q == 0) atomicAdd(sums + cb * 64 + w * 16 + r * 8 + g, ssq[r]);
    }
    if (NWG == 2) {
        asm volatile("fence.proxy.async.global;\nfence.acq_rel.gpu;\n" ::: "memory");
        __syncwarp();
        if (lane == 0) asm volatile("red.relaxed.gpu.global.add.u32 [%0], 1;\n" ::"l"(&g_img[2]) : "memory");
    }
}

__device__ __forceinline__ void p1_w2(const __nv_bfloat16* __restrict__ w2, const __nv_bfloat16* __restrict__ grn_b, int w, int lane) {
    const int gw = blockIdx.x * 4 + w;
    float* sums = g_sums[__ldcg(&g_epoch) & 1] + HID;
    flag_wait<true>(&g_flag[40][1][0], 12);
    {
        const int col = gw % 6 * 64 + lane * 2;
        float bsum[2] = {0.f, 0.f}, asum[2] = {0.f, 0.f};
#pragma unroll 4
        for (int kk = 0; kk < 192; kk++) {
            const int k = gw / 6 * 192 + kk;
            const uint32_t v = *reinterpret_cast<const uint32_t*>(w2 + k * C_DIM + col);
            const float b = __bfloat162float(grn_b[k]), f = __uint_as_float(__ldcg(&g_ex[k]) << 23);
            bsum[0] = fmaf(b, bf_lo(v), bsum[0]);
            bsum[1] = fmaf(b, bf_hi(v), bsum[1]);
            asum[0] = fmaf(f, fabsf(bf_lo(v)), asum[0]);
            asum[1] = fmaf(f, fabsf(bf_hi(v)), asum[1]);
        }
#pragma unroll
        for (int j = 0; j < 2; j++) {
            atomicAdd(sums + col + j, bsum[j]);
            atomicAdd(sums + C_DIM + col + j, asum[j]);
        }
        __threadfence();
        __syncwarp();
        if (lane == 0) asm volatile("red.relaxed.gpu.global.add.u32 [%0], 1;\n" ::"l"(&g_flag[LN_RING + 2][0][0]) : "memory");
    }
    while (*(volatile unsigned*)&g_flag[P1_IMG % LN_RING][1][0] < 12 * (P1_IMG / LN_RING + 1)) {
        __nanosleep(2000);
        SAFE_BREAK
    }
    flag_wait<true>(&g_flag[LN_RING + 2][0][0], 48);
    float z = 0.f;
#pragma unroll
    for (int j = 0; j < C_DIM / 32; j++) z = fmaxf(z, __ldcg(sums + C_DIM + j * 32 + lane));
    const float sc = __uint_as_float((263u - acc_exp(__uint_as_float(__reduce_max_sync(0xffffffffu, __float_as_uint(z))))) << 23);
    const int np = gw % 6 * 64 + lane * 2;
#pragma unroll 2
    for (int cc = 0; cc < 24; cc++) {
        const int c = gw / 6 * 24 + cc;
        uint32_t v[8], o[2][4];
#pragma unroll
        for (int e = 0; e < 8; e++) v[e] = *reinterpret_cast<const uint32_t*>(w2 + (c * 8 + e) * C_DIM + perm32(np));
#pragma unroll
        for (int e = 0; e < 4; e++) {
            const uint2 t = __ldcg(reinterpret_cast<const uint2*>(g_ex) + c * 4 + e);
            const float f0 = __uint_as_float(t.x << 23), f1 = __uint_as_float(t.y << 23);
            o[0][e] = pack_f16(bf_lo(v[2 * e]) * f0 * sc, bf_lo(v[2 * e + 1]) * f1 * sc);
            o[1][e] = pack_f16(bf_hi(v[2 * e]) * f0 * sc, bf_hi(v[2 * e + 1]) * f1 * sc);
        }
#pragma unroll
        for (int j = 0; j < 2; j++)
            g_w2img[0][(((c >> 1) * 48 + (np >> 3)) * 2 + (c & 1)) * 8 + (np & 7) + j] = make_uint4(o[j][0], o[j][1], o[j][2], o[j][3]);
    }
    asm volatile("fence.proxy.async.global;\n" ::: "memory");
    __threadfence();
    __syncwarp();
    if (lane < 2) asm volatile("red.relaxed.gpu.global.add.u32 [%0], 1;\n" ::"l"(&g_img[lane * 2]) : "memory");
}

__device__ __forceinline__ void p1_load_w1(uint32_t sbase, const CUtensorMap* wmap, int cb0, int nwg) {
    const uint32_t bar_w = sbase + P1_OFF_BAR + 2 * P1_NST * 8;
    for (int i = 0; i < nwg; i++) {
        mbar_expect_tx(bar_w + i * 8, P1_SLOT);
        tma2(sbase + (1 + i) * P1_SLOT, wmap, (cb0 + i) * 64, 0, bar_w + i * 8);
        tma2(sbase + (1 + i) * P1_SLOT + P1_SLOT / 2, wmap, (cb0 + i) * 64, 192, bar_w + i * 8);
    }
}

template <int CS>
__global__ void __cluster_dims__(CS, 1, 1) __launch_bounds__(512, 1)
pass1_kernel(const __grid_constant__ CUtensorMap wmap, const __nv_bfloat16* __restrict__ x, const __nv_bfloat16* __restrict__ dw,
             const __nv_bfloat16* __restrict__ w1, int zero) {
    extern __shared__ __align__(1024) uint8_t smem[];
    const uint32_t sbase = smem_u32(smem);
    const uint32_t bar_full = sbase + P1_OFF_BAR, bar_empty = bar_full + P1_NST * 8, bar_w = bar_empty + P1_NST * 8;
    const uint32_t bar_xfull = bar_w + 24, bar_raw = bar_xfull + 16, bar_done = bar_raw + 16;
    const int tid = threadIdx.x;
    const int warp = __shfl_sync(0xffffffffu, tid >> 5, 0), lane = tid & 31;
    const uint32_t rank = cluster_rank();
    const int bid = blockIdx.x, cl = bid >> 1;
    uint8_t* const ring = reinterpret_cast<uint8_t*>(g_ln);
    const int ln0 = bid >> 2, items = (NT128 - 1 - ln0) / LN_STEP + 1;

    TSTAMP(0, 0);
    TRACEW(110 + warp, 0);

    if (warp >= 12) {
        reg_dec<56>();
        asm volatile("barrier.cluster.arrive.relaxed.aligned;\n" ::: "memory");
        asm volatile("barrier.cluster.wait.aligned;\n" ::: "memory");
        {
            auto ring_row = [&](int p) {
                const int n = (p & 8) * 8 + (lane >> 3) * 8 + (p & 3) * 2 + (p >> 2 & 1);
                return n * 128 + (((lane ^ n) & 7) << 4);
            };
            const uint8_t* xsrc = reinterpret_cast<const uint8_t*>(x) + (size_t)(LN_STEP * 8 + bid * 2 + (warp & 1)) * P1_X;
            const uint32_t xbar = bar_xfull + (warp & 1) * 8, xdst = sbase + P1_OFF_X + (warp & 1) * P1_X;
            const uint32_t sdw = sbase + P1_OFF_DW + (lane & 7) * 16;
            uint32_t src = xdst - P1_OFF_X + (lane >> 3) * (C_DIM * 2) + (lane & 7) * 16;
            int row0 = ring_row((bid & 7) * 2 + (warp & 1)) ^ 288, slot = bid >> 3, used = 0;
            auto next = [&]() {
                xsrc += (size_t)LN_STEP * 8 * P1_X;
                if (elect_one()) {
                    mbar_expect_tx(xbar, P1_X);
                    bulk_g2s(xdst, xsrc, P1_X, xbar);
                }
                __syncwarp();
            };
#pragma unroll 1
            for (int i = -1; i < items; i++) {
                if (warp == 14) TRACEW(128 + i, 0);
                const int place = p1_place(ln0 + i * LN_STEP, slot);
                const int last = i > 0 ? 3 : i ? 2 + (warp >> 1 & 1) : 1;
#pragma unroll 1
                for (int ps = i < 0 ? last - 4 : 0; ps <= last; ps += i < 0 ? 4 : 1) {
                    if (i < 0 && ps > 0) STAMPT(416, 6);
                    if (i < 0 && ps > 0) mbar_wait(bar_raw, 0);
                    if (i < 0 && ps > 0) STAMPT(416, 7);
                    if (ps == 0) {
                        if (used) flag_wait<false>(&g_flag[slot][1][0], used);
                        if (i && i + 1 < items && elect_one())
                            asm volatile("cp.async.bulk.prefetch.L2.global [%0], %1;\n" ::"l"(xsrc + (size_t)LN_STEP * 8 * P1_X), "r"(P1_X) : "memory");
                        if (i) mbar_wait(xbar, ~i & 1);
                        else mbar_wait(bar_raw + 8, 0);
                        if (warp == 14) TRACEW(128 + i, 1);
                    }
                    uint32_t v[6][4];
#pragma unroll
                    for (int j = 0; j < 6; j++) lds128(v[j], src + (ps & 3) * (4 * C_DIM * 2) + j * 128);
                    ln_row(v, sdw, [&](uint32_t dep) {
                        if (i == 0 && ps == 1 && lane < CS) mbar_arrive_cluster(mapa(bar_empty, lane) + (dep & zero));
                        if (ps == 3 && i > 0 && i + 1 < items && !__any_sync(0xffffffffu, dep & zero)) next();
                    });
                    uint8_t* dst = ring + (place * LN_TILE + (ps & 1) * 4096 + (row0 ^ (ps & 2) * 144));
#pragma unroll
                    for (int j = 0; j < 6; j++)
                        asm volatile("{\n.reg .pred p;\nsetp.ge.s32 p, %5, 0;\n@p st.global.v4.u32 [%0], {%1,%2,%3,%4};\n}\n"
                                     ::"l"(dst + j * 16384), "r"(v[j][0]), "r"(v[j][1]), "r"(v[j][2]), "r"(v[j][3]), "r"(ps) : "memory");
                }
                if (warp == 14) TRACEW(128 + i, 2);
                asm volatile("fence.proxy.async.global;\nfence.acq_rel.cta;\n" ::: "memory");
                if (i < 0) {
                    bar_sync(4, 128);
                    if (warp < 14) break;
                    row0 ^= 288;
                    slot += NGRP;
                } else {
                    if (i) mbar_wait(bar_done, ~i & 1);
                    else {
                        src += P1_OFF_X;
                        slot = ln0;
                        row0 = ring_row((bid & 3) * 4 + (warp & 1) * 2);
                    }
                    __syncwarp();
                    if (lane == 0) mbar_arrive(bar_done);
                    if ((slot += LN_STEP) >= LN_RING) { slot -= LN_RING; used += 12; }
                }
            }
            if (warp < 14 && lane < CS) mbar_arrive_cluster(mapa(bar_empty, lane));
        }
        if (warp == 12) {
            int prev = 0, t = cl >> 2, next = t + NGRP;
            const uint32_t rbase = mapa(sbase, lane & (CS - 1));
            int i = 0;
#pragma unroll 1
            for (; t < NT128; i++) {
                const int s0 = (i & 1) * 2, par = (i >> 1) & 1;
                const int round = t / LN_RING, slot = t - round * LN_RING;
                const uint8_t* src = ring + slot * LN_TILE + rank * (P1_SLOT / CS);
                int draw = 0;
                if (rank == 0 && lane == 0) draw = 2 * NGRP + atomicAdd(&g_flag[LN_RING + ((cl >> 1) & 1)][cl & 1][0], 1u);
                flag_wait<true>(&g_flag[slot][0][0], 8 * round + 8);
                TRACEW(i, 2);
                if (i == 0) STAMPT(384, 10);
                if (i == 2) STAMPT(384, 13);
                if (i == 3) STAMPT(384, 14);
                asm volatile("fence.proxy.async.global;\n" ::: "memory");
                draw = p1_tile(__shfl_sync(0xffffffffu, draw, 0));
#pragma unroll
                for (int h = 0; h < 2; h++) {
                    mbar_wait(bar_empty + (s0 + h) * 8, par);
                    TRACEW(i, 4 + h);
                    if (i == 0 && h == 1) STAMPT(384, 11);
                    if (elect_one()) {
                        mbar_expect_tx(bar_full + (s0 + h) * 8, P1_SLOT + 16 - 16 * h);
                        bulk_g2s_mc(sbase + (s0 + h) * P1_SLOT + rank * (P1_SLOT / CS), src + h * P1_SLOT, P1_SLOT / CS, bar_full + (s0 + h) * 8, (uint16_t)((1 << CS) - 1));
                    }
                    __syncwarp();
                    if (h == 0 && rank == 0 && lane < CS)
                        asm volatile("st.async.shared::cluster.mbarrier::complete_tx::bytes.v4.u32 [%0], {%1, %2, %3, %3}, [%4];\n"
                                     ::"r"(rbase + P1_OFF_TILE + (i & 3) * 16), "r"((t - prev) * (2 * H_TILE)), "r"((int)(next < NT128)), "r"(draw),
                                       "r"(rbase + P1_OFF_BAR + s0 * 8) : "memory");
                }
                prev = t;
                t = next;
                next = draw;
                if (rank != 0) {
                    mbar_wait(bar_full + s0 * 8, (i >> 1) & 1);
                    mbar_wait(bar_full + s0 * 8 + 8, (i >> 1) & 1);
                    if (lane == 0 && rank == 1) asm volatile("red.relaxed.gpu.global.add.u32 [%0], %1;\n" ::"l"(&g_flag[slot][1][0]), "r"(CS * 3 / 2) : "memory");
                    asm volatile("ld.shared.u32 %0, [%1];\n" : "=r"(next) : "r"(sbase + P1_OFF_TILE + (i & 3) * 16 + 8) : "memory");
                    TRACEW(i, 3);
                }
            }
#pragma unroll 1
            for (int j = 2 * i; j < 2 * i + 4; j++) mbar_wait(bar_empty + (j & 3) * 8, (j >> 2) & 1);
        } else if (warp == 13) {
            STAMPT(416, 8);
            if (lane == 0) asm volatile("red.release.gpu.global.add.u32 [%0], 1;\n" ::"l"(&g_flag[bid >> 3][0][0]) : "memory");
            __syncwarp();
            STAMPT(416, 9);
            const uint32_t ep = g_epoch & 1;
            asm volatile("st.shared.u32 [%0], %1;\n" ::"r"(sbase + P1_OFF_TILE - 4), "r"(ep) : "memory");
            if (bid < 18) reinterpret_cast<float4*>(g_sums[ep ^ 1])[bid * 32 + lane] = make_float4(0.f, 0.f, 0.f, 0.f);
#pragma unroll 1
            for (int i = 0; i < items; i++) {
                mbar_wait(bar_done, i & 1);
                asm volatile("fence.proxy.async.global;\n" ::: "memory");
                if (lane == 0) {
                    const int slot = i ? ln0 + (i & 1) * LN_STEP : NGRP + (bid >> 3), place = p1_place(ln0 + i * LN_STEP, slot);
                    mbar_arrive(bar_done);
                    asm volatile("red.release.gpu.global.add.u32 [%0], %1;\n" ::"l"(&g_flag[place][0][0]), "r"(i ? 2 : 1) : "memory");
                    if (place != slot) {
                        atomicAdd(&g_flag[slot][0][0], 2u);
                        atomicAdd(&g_flag[slot][1][0], 3u);
                    }
                }
                __syncwarp();
                TRACEW(128 + i, 3);
            }
        }
    } else {
        if (tid == 0) {
            mbar_init(bar_raw, 1);
            mbar_init(bar_raw + 8, 1);
            mbar_init(bar_xfull, 1);
            mbar_init(bar_xfull + 8, 1);
            for (int i = 0; i < 3; i++) mbar_init(bar_w + i * 8, 1);
            asm volatile("fence.mbarrier_init.release.cluster;\n" ::: "memory");
            {
                mbar_expect_tx(bar_raw, P1_X + C_DIM * 2);
                bulk_g2s(sbase + P1_OFF_DW, dw, C_DIM * 2, bar_raw);
                for (int i = 0; i < 2; i++) bulk_g2s(sbase + i * P1_X + P1_X / 2, x + (size_t)(bid * 16 + i * 8) * C_DIM, P1_X / 2, bar_raw);
                if (bid < 96) asm volatile("cp.async.bulk.prefetch.L2.global [%0], 12288;\n" ::"l"(w1 + bid * 6144) : "memory");
                mbar_expect_tx(bar_raw + 8, P1_X);
                for (int i = 0; i < 2; i++) bulk_g2s(sbase + i * P1_X, x + (size_t)(NGRP * 128 + bid * 16 + i * 8) * C_DIM, P1_X / 2, bar_raw + 8);
            }
            p1_load_w1(sbase, &wmap, (bid & 7) * 3, 3);
            for (int i = 0; i < 2; i++) {
                mbar_expect_tx(bar_xfull + i * 8, P1_X);
                bulk_g2s(sbase + P1_OFF_X + i * P1_X, x + (size_t)(LN_STEP * 128 + bid * 32 + i * 16) * C_DIM, P1_X, bar_xfull + i * 8);
            }
        }
        if (tid == 32) {
            mbar_init(bar_done, 3);
            mbar_arrive(bar_done);
            asm volatile("fence.mbarrier_init.release.cluster;\n" ::: "memory");
        }
        if (tid == 64) {
            for (int i = 0; i < P1_NST; i++) {
                mbar_init(bar_full + i * 8, 1);
                mbar_init(bar_empty + i * 8, 12 * CS);
            }
            asm volatile("fence.mbarrier_init.release.cluster;\n" ::: "memory");
            if (bid < 64) (&g_half[0][0])[bid] = 0;
            else if (bid == 64) g_prog = 0;
            else if (bid < 68) g_img[bid - 65] = 0;
        }
        __syncwarp();
        asm volatile("barrier.cluster.arrive.relaxed.aligned;\n" ::: "memory");
        reg_inc<152>();
        TRACEW(110 + warp, 1);
        gdc_launch();
        asm volatile("barrier.cluster.wait.aligned;\n" ::: "memory");
        p1_compute<CS, 3>(sbase, (bid & 7) * 3, warp, lane, zero);
        TSTAMP(0, 30);
    }
}

constexpr int P2_B = 24576, P2_NB = 5;
constexpr int P2_A = 3072, P2_NA = 5;
constexpr int P2_XROW = C_DIM * 2;
constexpr int P2_OFF_A = P2_B * P2_NB;
constexpr int P2_OFF_X = P2_OFF_A + 3 * P2_NA * P2_A;
constexpr int P2_XHALF = 32 * P2_XROW + 64;
constexpr int P2_OFF_BIAS = P2_OFF_X + 64 * P2_XROW + 64;
constexpr int P2_OFF_GRN = P2_OFF_BIAS + C_DIM * 4;
constexpr int P2_OFF_RED = P2_OFF_GRN + HID * 2;
constexpr int P2_OFF_BAR = P2_OFF_RED + 192;
static_assert(P2_OFF_BAR >= P1_OFF_DW && P2_OFF_BAR + (2 * P2_NB + 6 * P2_NA + 3) * 8 <= P1_OFF_BAR, "");
constexpr int P2_SMEM = P1_SMEM;
constexpr int P2_LAG = 17;
constexpr int P2_NCL = NUM_CTAS / 2, P2_ITEMS = NT128 / P2_NCL, P2_SHARED = NT128 - P2_ITEMS * P2_NCL;
constexpr int P2_POS = P2_LAG * (P2_ITEMS - 1) + 48;
__device__ __forceinline__ int p2_start(int n) { return n < 0 ? 0 : n == P2_ITEMS ? P2_POS - 24 : P2_LAG * n; }
constexpr int P2_FOLD = 17;
constexpr int P2_XC = 8 * P2_XROW;
constexpr int P2_DELTA = 7;
__device__ __forceinline__ int p2_tile(int cl, int n) {
    return n == 0 ? NT128 - 1 - cl : n < 0 || n == P2_ITEMS ? NT128 - 1 - P2_NCL - (cl >> 1) : cl + P2_NCL * (n - 1);
}

constexpr int P2_EG = 2;
__device__ __forceinline__ void p2_init(uint32_t (&acc)[48], int c, uint32_t sb) {
#pragma unroll
    for (int i = 8 * (c % 6); i < 8 * (c % 6) + 8; i += 4)
        asm volatile("ld.shared.v4.u32 {%0,%1,%2,%3}, [%4];\n" : "=r"(acc[i]), "=r"(acc[i + 1]), "=r"(acc[i + 2]), "=r"(acc[i + 3])
                     : "r"(sb + c * 128 + i % 8 * 4) : "memory");
}
__device__ __forceinline__ void p2_epilogue(uint32_t (&acc0)[48], uint32_t (&acc1)[48], uint32_t sx, uint32_t sb, uint32_t up, int zero) {
    uint32_t v[2][P2_EG][4];
    auto load = [&](int c, uint32_t a) {
#pragma unroll
        for (int j = 0; j < P2_EG; j++) {
            const int u = c * P2_EG + j;
            asm volatile("ld.shared.v4.u32 {%0,%1,%2,%3}, [%4];\n" : "=r"(v[c & 1][j][0]), "=r"(v[c & 1][j][1]), "=r"(v[c & 1][j][2]), "=r"(v[c & 1][j][3])
                         : "r"(a + (u >> 1) * 64 + (u & 1) * 4 * P2_XROW) : "memory");
        }
    };
    load(0, sx);
#pragma unroll
    for (int c = 0; c < 24 / P2_EG; c++) {
        if (c + 1 < 24 / P2_EG) load(c + 1, sx + (v[c & 1][P2_EG - 1][0] & zero));
#pragma unroll
        for (int j = 0; j < P2_EG; j++) {
            const int u = c * P2_EG + j, i = 8 * ((u >> 1) % 6) + (u & 1);
            const uint32_t (&acc)[48] = u < 12 ? acc0 : acc1;
            uint32_t (&w)[4] = v[c & 1][j];
#pragma unroll
            for (int e = 0; e < 4; e++)
                w[e] = bf2_fma(pack_bf16(h_lo(acc[i + 2 * e]), h_hi(acc[i + 2 * e])), up, w[e]);
            asm volatile("st.shared.v4.u32 [%4], {%0,%1,%2,%3};\n" ::"r"(w[0]), "r"(w[1]), "r"(w[2]), "r"(w[3]),
                         "r"(sx + (u >> 1) * 64 + (u & 1) * 4 * P2_XROW) : "memory");
        }
        p2_init(c < 6 ? acc0 : acc1, c, sb + (v[c & 1][1][0] & zero));
    }
}

__device__ __forceinline__ void p2_unpack(uint4& u, uint32_t o1, uint32_t o2, uint32_t o3) {
    u.z = o1 & 0xbff8bff8u;
    u.y = o2 & 0xbff8bff8u;
    u.w = o3 & 0xbff8bff8u;
    u.x = (__byte_perm(o1, 0, 0x2301) & 0x07400740u) | ((__byte_perm(o2, o3, 0x6240) << 3) & 0x38383838u) | ((__byte_perm(o2, o3, 0x3715) << 1) & 0x80808080u);
}
__device__ __forceinline__ uint32_t h2_mul(uint32_t a, uint32_t b) {
    uint32_t r;
    asm("mul.rn.f16x2 %0, %1, %2;\n" : "=r"(r) : "r"(a), "r"(b));
    return r;
}
__device__ __forceinline__ void p2_epilogue_add(const uint32_t (&acc)[48], uint8_t* o, uint32_t up, int zero) {
#pragma unroll
    for (int t = 0; t < 12; t++) {
        uint32_t v[4];
#pragma unroll
        for (int e = 0; e < 4; e++) {
            v[e] = acc[8 * (t >> 1) + (t & 1) + 2 * e];
            asm volatile("" : "+r"(v[e]));
            v[e] = bf2_mul(pack_bf16(h_lo(v[e]), h_hi(v[e])), up);
        }
        asm volatile("red.global.add.noftz.v4.bf16x2 [%0], {%1,%2,%3,%4};\n" ::"l"(o + (t >> 1) * 64 + (t & 1) * 4 * P2_XROW),
                     "r"(v[0]), "r"(v[1]), "r"(v[2]), "r"(v[3]) : "memory");
        if (t % 3 == 2) sched_break(zero);
    }
}

__global__ void __cluster_dims__(2, 1, 1) __launch_bounds__(512, 1)
pass2_kernel(const __grid_constant__ CUtensorMap wmap, const __nv_bfloat16* __restrict__ x, const __nv_bfloat16* __restrict__ w2,
             const __nv_bfloat16* __restrict__ grn_g, const __nv_bfloat16* __restrict__ grn_b, __nv_bfloat16* __restrict__ out, int zero) {
    extern __shared__ __align__(1024) uint8_t smem[];
    const uint32_t sbase = smem_u32(smem);
    const uint32_t bar_bfull = sbase + P2_OFF_BAR, bar_bempty = bar_bfull + P2_NB * 8;
    const uint32_t bar_afull = bar_bempty + P2_NB * 8, bar_aempty = bar_afull + 3 * P2_NA * 8;
    const uint32_t bar_xfull = bar_aempty + 3 * P2_NA * 8, bar_oready = bar_xfull + 8, s_pos = bar_xfull + 16;
    int tid;
    asm volatile("mov.u32 %0, %%tid.x;\n" : "=r"(tid));
    const int warp = __shfl_sync(0xffffffffu, tid >> 5, 0), lane = tid & 31;
    const uint32_t rank = cluster_rank();
    const int cl = blockIdx.x >> 1, pair = cl >> 1;
    const int k0 = (4 * pair + (cl & 1) * (48 - P2_POS % 48)) % 48;
    const int head = pair < P2_SHARED && !(cl & 1), tail = pair < P2_SHARED && (cl & 1);

    const bool small = blockIdx.x < NUM_CTAS - 8 * NGRP;
    uint32_t par, gg[4];
    auto early = [&]() {
        asm volatile("ld.global.cg.u32 %0, [%1];\n" : "=r"(par) : "l"(&g_epoch) : "memory");
#pragma unroll
        for (int i = 0; i < 4; i++) asm volatile("ld.global.nc.u16 %0, [%1];\n" : "=r"(gg[i]) : "l"(grn_g + tid + 384 * i) : "memory");
    };
    if (warp < 12) early();
    if (small && tid == 0) {
        for (int i = 0; i < 2 * P1_NST + 2; i++) mbar_init(sbase + P1_OFF_BAR + i * 8, (i & 12) == 4 ? 16 : 1);
        asm volatile("fence.mbarrier_init.release.cluster;\n" ::: "memory");
        p1_load_w1(sbase, &wmap, blockIdx.x * 2, 2);
    }
    if (small) TSTAMP(0, 0);
    TSTAMP(1, 0);
    if (tid == 384) {
        for (int i = 0; i < P2_NB; i++) {
            mbar_init(bar_bfull + i * 8, 1);
            mbar_init(bar_bempty + i * 8, 24);
        }
        mbar_init(bar_xfull, 2);
        mbar_init(bar_oready, 4);
        asm volatile("st.shared.u32 [%0], 0;\nfence.mbarrier_init.release.cluster;\nfence.acq_rel.cta;\n" ::"r"(s_pos) : "memory");
    }
    if (warp > 12 && lane == 0) {
        for (int i = 0; i < P2_NA; i++) {
            mbar_init(bar_afull + ((warp - 13) * P2_NA + i) * 8, 1);
            mbar_init(bar_aempty + ((warp - 13) * P2_NA + i) * 8, 4);
        }
        asm volatile("fence.mbarrier_init.release.cluster;\n" ::: "memory");
    }
    __syncwarp();
    asm volatile("barrier.cluster.arrive.relaxed.aligned;\n" ::: "memory");

    if (warp >= 12) {
        reg_dec<32>();
        if (small) par = 0;
        else asm volatile("ld.acquire.gpu.global.u32 %0, [%1];\n" : "=r"(par) : "l"(&g_img[(warp & 1) * 2]) : "memory");
        asm volatile("barrier.cluster.wait.aligned;\n" ::: "memory");
        if (small) {
#pragma unroll 1
            for (int j = 0; warp == 12 && j < 2 * NSMALL; j++) {
                const uint32_t bar = sbase + P1_OFF_BAR + (j & 3) * 8;
                if (!(j & 1)) {
                    flag_wait<true>(&g_flag[LN_RING + 3 + (j >> 1)][0][0], 8);
                    asm volatile("fence.proxy.async.global;\n" ::: "memory");
                }
                mbar_wait(bar + P1_NST * 8, (j >> 2) & 1);
                if (elect_one()) {
                    mbar_expect_tx(bar, P1_SLOT);
                    bulk_g2s_mc(sbase + (j & 3) * P1_SLOT + rank * (P1_SLOT / 2),
                                reinterpret_cast<const uint8_t*>(g_ln) + (size_t)(2 * (LN_RING + 3) + j) * P1_SLOT + rank * (P1_SLOT / 2), P1_SLOT / 2, bar, (uint16_t)3);
                }
                __syncwarp();
            }
            asm volatile("barrier.cluster.arrive.aligned;\nbarrier.cluster.wait.aligned;\n" ::: "memory");
        }
        if (warp == 12) {
            const uint8_t* wsrc = reinterpret_cast<const uint8_t*>(g_w2img) + rank * (P2_B / 2);
            int st = 0, ph = 1, kb = k0, m = 0, r = 0;
            const int busy = head ? 0 : tail ? P2_POS - 24 : P2_POS;
#pragma unroll 1
            for (int p = 0; p < P2_POS; p++) {
                if (p == 0 || p == P2_FOLD) {
                    if (p || par < 48) flag_wait<true>(&g_img[p != 0], p ? 96 * 4 : 48);
                    asm volatile("fence.proxy.async.global;\n" ::: "memory");
                    if (p) wsrc += sizeof(g_w2img[0]);
                }
                mbar_wait(bar_bempty + st * 8, ph);
                TR2P(p, 0);
                if (elect_one()) {
                    mbar_expect_tx(bar_bfull + st * 8, P2_B);
                    bulk_g2s_mc(sbase + st * P2_B + rank * (P2_B / 2), wsrc + kb * P2_B, P2_B / 2, bar_bfull + st * 8, (uint16_t)3);
                    asm volatile("st.volatile.shared.u32 [%0], %1;\n" ::"r"(s_pos), "r"(p) : "memory");
                    const int idle = 2 - min(m, P2_ITEMS - 1) + max(m - 2 + (r >= 48 - 2 * P2_LAG), 0) - ((unsigned)(p - busy) < 24);
                    if (idle) asm volatile("mbarrier.arrive.shared::cta.b64 _, [%0], %1;\n" ::"r"(bar_bempty + st * 8), "r"(idle * 8) : "memory");
                    if (rank == 0) asm volatile("red.relaxed.gpu.global.add.u32 [%0], 1;\n" ::"l"(&g_prog) : "memory");
                }
                __syncwarp();
                if (++st == P2_NB) { st = 0; ph ^= 1; }
                if (++kb == 48) kb = 0;
                if (++r == P2_LAG) { r = 0; m++; }
            }
            mbar_wait(bar_bempty + st * 8, ph);
            if (lane == 0) mbar_arrive(bar_bfull + st * 8);
#pragma unroll 1
            for (int p = 1; p < P2_NB; p++) {
                if (++st == P2_NB) { st = 0; ph ^= 1; }
                mbar_wait(bar_bempty + st * 8, ph);
            }
        } else if (warp == 13) {
            const uint8_t* src[3];
            int n[3], left[3], wrap[3];
            uint32_t st[3];
            auto item = [&](int w) {
                const int u = (k0 + p2_start(n[w])) % 48;
                left[w] = n[w] < 0 || n[w] == P2_ITEMS ? 24 : 48;
                wrap[w] = left[w] - (48 - u);
                src[w] = reinterpret_cast<const uint8_t*>(g_h) + (size_t)p2_tile(cl, n[w]) * (2 * H_TILE) + rank * H_HALF + u * H_STEP;
            };
#pragma unroll
            for (int w = 0; w < 3; w++) {
                n[w] = w == 2 && head ? -1 : w;
                st[w] = 0x80000000u;
                item(w);
            }
            if (par < (NUM_CTAS - 8 * NGRP) * 12) flag_wait<true>(&g_img[2], (NUM_CTAS - 8 * NGRP) * 12);
            bar_arrive(3, 416);
            gdc_wait();
            asm volatile("fence.proxy.async.global;\n" ::: "memory");
#pragma unroll 1
            for (int fin = 0; fin < 3;) {
                bool idle = true;
#pragma unroll
                for (int w = 0; w < 3; w++) {
                    const uint32_t o = (st[w] & 0xff) + w * P2_NA * 8;
                    if (left[w] >= 0 && mbar_test(bar_aempty + o, st[w] >> 31)) {
                        idle = false;
                        if (left[w] == 0) {
                            if (lane == 0) mbar_arrive(bar_afull + o);
                            left[w] = -1;
                            fin++;
                        } else {
                            if (elect_one()) {
                                mbar_expect_tx(bar_afull + o, P2_A);
                                bulk_g2s(sbase + P2_OFF_A + o * (P2_A / 8), src[w], P2_A, bar_afull + o);
                            }
                            __syncwarp();
                            src[w] += H_STEP;
                            st[w] += 8;
                            if ((st[w] & 0xff) == P2_NA * 8) st[w] ^= 0x80000000u | (P2_NA * 8);
                            if (--left[w] == wrap[w]) src[w] -= 48 * H_STEP;
                            if (left[w] == 0 && (n[w] += 3) < P2_ITEMS + tail) item(w);
                        }
                    }
                }
                if (idle) __nanosleep(64);
                SAFE_BREAK
            }
        } else if (warp == 14) {
            const uint32_t sx = sbase + P2_OFF_X;
            size_t o = 0;
            auto pace = [&](int target) {
                int v;
                while (true) {
                    asm volatile("ld.volatile.shared.u32 %0, [%1];\n" : "=r"(v) : "r"(s_pos) : "memory");
                    if (v * 16 >= target) break;
                    __nanosleep(100);
                    SAFE_BREAK
                }
            };
#pragma unroll 1
            for (int n = -head; n <= P2_ITEMS; n++) {
                const size_t on = (size_t)(2 * p2_tile(cl, n) + rank) * (64 * C_DIM * 2);
                const bool st = n + head > 0, ld = n < P2_ITEMS;
                if (st) mbar_wait(bar_oready, (n - 1 + head) & 1);
                TR2P(n + 1, 1);
                if (lane == 0) {
                    if (n == 1 && head) {
                        asm volatile("cp.async.bulk.wait_group 0;\nfence.proxy.async.global;\n" ::: "memory");
                        asm volatile("st.release.gpu.global.u32 [%0], 1;\n" ::"l"(&g_half[pair][rank]) : "memory");
                    }
                    if (ld) mbar_expect_tx(bar_xfull, 64 * C_DIM * 2);
                    const bool paced = st && n < P2_ITEMS - 1;
                    int t = (P2_LAG * (n - 1) + 52) * 16;
#pragma unroll 1
                    for (int c = 0; st && c < 64 * P2_XROW; c += P2_XC) {
                        if (paced) pace(t += 11);
                        bulk_s2g(reinterpret_cast<uint8_t*>(out) + o + c, sx + c + (c >= 32 * P2_XROW ? 64 : 0), P2_XC);
                        asm volatile("cp.async.bulk.commit_group;\n" ::: "memory");
                    }
#pragma unroll 1
                    for (int c = 0; ld && c < 64 * P2_XROW; c += P2_XC) {
                        if (c == 0) asm volatile("cp.async.bulk.wait_group.read 4;\n" ::: "memory");
                        if (c == 32 * P2_XROW) asm volatile("cp.async.bulk.wait_group.read 0;\n" ::: "memory");
                        if (paced) pace(t += 11);
                        bulk_g2s(sx + c + (c >= 32 * P2_XROW ? 64 : 0), reinterpret_cast<const uint8_t*>(x) + on + c, P2_XC, bar_xfull);
                    }
                    TR2P(n + 1, 2);
                    if (rank == 0 && n > 0 && n < P2_ITEMS - 2)
                        flag_wait<false>(&g_prog, P2_NCL * (P2_LAG * n + 48) + (tail ? P2_SHARED - P2_NCL : P2_SHARED) * P2_DELTA);
                    if (ld) mbar_arrive(bar_xfull);
                    TR2P(n + 1, 3);
                }
                __syncwarp();
                o = on;
            }
            asm volatile("cp.async.bulk.wait_group 0;\n" ::: "memory");
            TR2P(30, 1);
        }
    } else {
        reg_inc<160>();
        asm volatile("barrier.cluster.wait.aligned;\n" ::: "memory");
        if (small) {
            if (warp < 8) p1_compute<2, 2>(sbase, blockIdx.x * 2, warp, lane, zero);
            else p1_w2(w2, grn_b, warp & 3, lane);
            asm volatile("barrier.cluster.arrive.aligned;\nbarrier.cluster.wait.aligned;\n" ::: "memory");
            TSTAMP(0, 30);
            early();
        }
        const int wg = warp >> 2, w = warp & 3, g = lane >> 2, q = lane & 3;
        const uint32_t sx = sbase + P2_OFF_X + (g & 1) * P2_XHALF + (w * 8 + (g >> 1)) * P2_XROW + q * 16;
        const uint32_t af = bar_afull + wg * P2_NA * 8;
        const uint32_t s_a = sbase + P2_OFF_A + wg * P2_NA * P2_A + (lane >> 3) * 512 + (lane & 7) * 64 +
                             ((w ^ ((lane & 7) >> 1)) << 4);
        uint32_t acc0[48], acc1[48];
        uint32_t up;
        uint4 a0[2], a1[2];
        uint32_t st = 0, ph = 0;

        {
            float4* s_red = reinterpret_cast<float4*>(smem + P2_OFF_RED);
            const float* sums = g_sums[par & 1];
            float gx[4], part = 0.f, mx = 0.f;
            asm volatile("prefetch.global.L2 [%0];\n" ::"l"(sums + HID + tid * 2) : "memory");
            TSTAMP(1, 27);
            bar_sync(3, 416);
            gdc_wait();
            TSTAMP(1, 1);
#pragma unroll
            for (int i = 0; i < 4; i++) gx[i] = __ldcg(sums + tid + 384 * i);
            const float bias = __ldcg(sums + HID + tid), asum = __ldcg(sums + HID + C_DIM + tid);
            float z = __uint_as_float(__reduce_max_sync(0xffffffffu, __float_as_uint(asum)));
            uint32_t bm = __reduce_max_sync(0xffffffffu, __float_as_uint(fabsf(bias)));
#pragma unroll
            for (int i = 0; i < 4; i++) {
                asm("sqrt.approx.f32 %0, %1;\n" : "=f"(gx[i]) : "f"(fmaf(gx[i], HSCALE * HSCALE, 1e-6f)));
                part += gx[i];
                gx[i] *= bf_lo(gg[i]);
                mx = fmaxf(mx, fabsf(gx[i]));
            }
#pragma unroll
            for (int o = 16; o > 0; o >>= 1) part += __shfl_xor_sync(0xffffffffu, part, o);
            mx = __uint_as_float(__reduce_max_sync(0xffffffffu, __float_as_uint(mx)));
            TSTAMP(1, 26);
            if (lane == 0) s_red[warp] = make_float4(part, mx, z, __uint_as_float(bm));
            bar_sync(1, 384);
            float tot = 0.f;
            {
                const float4 t = s_red[min(lane & 15, 11)];
                tot = (lane & 15) < 12 ? t.x : 0.f;
#pragma unroll
                for (int o = 8; o > 0; o >>= 1) tot += __shfl_xor_sync(0xffffffffu, tot, o);
                mx = __uint_as_float(__reduce_max_sync(0xffffffffu, __float_as_uint(t.y)));
                z = __uint_as_float(__reduce_max_sync(0xffffffffu, __float_as_uint(t.z)));
                bm = __reduce_max_sync(0xffffffffu, __float_as_uint(t.w));
            }
            const float inv = __fdividef(1.0f, fmaf(tot, 1.0f / HID, 1e-6f));
            const uint32_t e0 = acc_exp(z) - 9u;
            const uint32_t j = min(max(max(__float_as_uint(fmaf(mx, inv, 1.0f) * 1.01f) >> 23, 130u) - 130u, max(bm >> 23, e0 + 12u) - (e0 + 12u)), 126u);
            const float dn = __uint_as_float((127u - j) << 23) * (HSCALE * 1.00235f);
#pragma unroll
            for (int i = 0; i < 4; i++)
                *reinterpret_cast<uint16_t*>(smem + P2_OFF_GRN + (tid + 384 * i) * 2) = pack_f16(fmaf(gx[i], inv, 1.0f) * dn, 0.f);
            const uint32_t e = min(e0 + j, 253u);
            up = e * 0x00800080u;
#pragma unroll
            for (int i = 0; i < 2; i++)
                *reinterpret_cast<uint16_t*>(smem + P2_OFF_BIAS + (tid >> 1) * 8 + i * 4 + (tid & 1) * 2) = pack_f16(bias * __uint_as_float((254u - e) << 23), 0.f);
            TSTAMP(1, 25);
            bar_sync(1, 384);
            if (wg == 1 && blockIdx.x < 96) {
                const uint4* src = g_w2img[0] + blockIdx.x * 768 + tid - 128;
                const uint4 fk = *reinterpret_cast<const uint4*>(smem + P2_OFF_GRN + blockIdx.x * 32 + (tid & 8) * 2);
                uint4 v[6];
#pragma unroll
                for (int i = 0; i < 6; i++) v[i] = __ldcg(src + i * 128);
                auto fold = [&](uint32_t b, uint32_t f) { return (h2_mul(b, f) + 0x00040004u) & 0xfff8fff8u; };
#pragma unroll
                for (int i = 0; i < 6; i++)
                    g_w2img[1][blockIdx.x * 768 + tid - 128 + i * 128] = make_uint4(fold(v[i].x, fk.x), fold(v[i].y, fk.y), fold(v[i].z, fk.z), fold(v[i].w, fk.w));
                asm volatile("fence.proxy.async.global;\n" ::: "memory");
                __threadfence();
                __syncwarp();
                if (lane == 0) asm volatile("red.release.gpu.global.add.u32 [%0], 1;\n" ::"l"(&g_img[1]) : "memory");
            }
        }
        TSTAMP(1, 28);
        int kt = k0, pos;
        const uint32_t be = lane < 2 ? mapa(bar_bempty, lane) : 0, be0 = mapa(bar_bempty, 0);
        uint32_t prev = 0, sa = 0, pa = 0;
        auto release_b = [&](uint32_t p, bool on) {
            asm volatile("{\n.reg .pred p, q;\nsetp.ne.u32 q, %2, 0;\nsetp.ne.and.u32 p, %1, 0, q;\n@p mbarrier.arrive.shared::cluster.b64 _, [%0];\n}\n"
                         ::"r"(be + p), "r"(be), "r"((uint32_t)on) : "memory");
        };
        auto arrive1 = [&](uint32_t bar) {
            asm volatile("{\n.reg .pred p;\nsetp.eq.u32 p, %1, %2;\n@p mbarrier.arrive.shared::cta.b64 _, [%0];\n}\n" ::"r"(bar), "r"(be), "r"(be0) : "memory");
        };
        auto seek = [&](int p) {
            pos = p;
            st = p % P2_NB * 8;
            ph = p / P2_NB & 1;
            int v;
            while (true) {
                asm volatile("ld.volatile.shared.u32 %0, [%1];\n" : "=r"(v) : "r"(s_pos) : "memory");
                if (__all_sync(0xffffffffu, v >= p)) break;
                __nanosleep(200);
                SAFE_BREAK
            }
        };
        bool ok_a = false;
        auto fetch = [&](uint4 (&a)[2], uint32_t done, bool rel, bool early, bool wait = true) {
            if (!ok_a) mbar_wait(af + sa, pa);
            uint32_t o[6];
            const uint32_t src = s_a + sa * (P2_A / 8);
            asm volatile("ldmatrix.sync.aligned.m8n8.x4.trans.shared.b16 {%0,%1,%2,%3}, [%4];\n"
                         : "=r"(o[0]), "=r"(o[1]), "=r"(o[2]), "=r"(o[3]) : "r"(src) : "memory");
            asm volatile("ldmatrix.sync.aligned.m8n8.x2.trans.shared.b16 {%0,%1}, [%2];\n"
                         : "=r"(o[4]), "=r"(o[5]) : "r"(src + 2048) : "memory");
            if ((sa += 8) == P2_NA * 8) { sa = 0; pa ^= 1; }
            if (wait) wg_wait<1>();
            asm volatile("" ::"r"(a[0].x), "r"(a[0].y), "r"(a[0].z), "r"(a[0].w), "r"(a[1].x), "r"(a[1].y), "r"(a[1].z), "r"(a[1].w));
            release_b(done, rel);
            ok_a = mbar_test(af + sa, pa);
            const bool ok_b = mbar_test(bar_bfull + st, ph);
            p2_unpack(a[0], o[0], o[1], o[2]);
            p2_unpack(a[1], o[3], o[4], o[5]);
            if (early) {
                const uint32_t* t = reinterpret_cast<const uint32_t*>(smem + P2_OFF_GRN) + kt * 16 + q;
#pragma unroll
                for (int i = 0; i < 2; i++)
                    a[i] = make_uint4(h2_mul(a[i].x, t[8 * i]), h2_mul(a[i].y, t[8 * i]), h2_mul(a[i].z, t[8 * i + 4]), h2_mul(a[i].w, t[8 * i + 4]));
                if (++kt == 48) kt = 0;
            }
            if (!ok_b) mbar_wait(bar_bfull + st, ph);
        };
        const uint64_t db0 = make_desc(sbase, 128, 256);
        auto step = [&](const uint4 (&a)[2], uint4 (&an)[2], bool cont, bool add, bool early) {
            TR2(0);
            const uint64_t db = db0 + st * (P2_B / 128);
            wg_fence();
            mma_rs_n192(acc0, a[0], db, add);
            mma_rs_n192(acc1, a[0], db + 384, add);
            mma_rs_n192(acc0, a[1], db + 768, 1);
            mma_rs_n192(acc1, a[1], db + 768 + 384, 1);
            wg_commit();
            arrive1(af + 3 * P2_NA * 8 - 8 + (sa ? sa : P2_NA * 8));
            const uint32_t done = prev;
            prev = st;
            if ((st += 8) == P2_NB * 8) { st = 0; ph ^= 1; }
            fetch(an, done, cont, early);
            pos++;
        };
        int n = wg == 2 && head ? -1 : wg;
#pragma unroll
        for (int c = 0; c < 12; c++) p2_init(c < 6 ? acc0 : acc1, c, sbase + P2_OFF_BIAS + q * 32);
        a0[0] = a0[1] = a1[0] = a1[1] = make_uint4(zero, zero, zero, zero);
        seek(p2_start(n));
        fetch(a0, 0, false, n <= 0, false);
#pragma unroll 1
        for (;; n += 3) {
            TSTAMP(1, 2 + n);
            const int p0 = n < 0 || n == P2_ITEMS ? 12 : 0, pe = n <= 0 ? p0 + P2_FOLD / 2 : 0;
            const bool more = n + 3 < P2_ITEMS + tail;
#pragma unroll 1
            for (int p = p0; p < 24; p++) {
                step(a0, a1, p != p0, p != p0 || n != P2_ITEMS, p < pe);
                step(a1, a0, true, true, p < pe);
            }
            if (n == P2_ITEMS) {
                flag_wait<true>(&g_half[pair][rank], 1);
                TR2(1);
                wg_wait<0>();
                TR2(2);
                release_b(prev, true);
                uint8_t* o = reinterpret_cast<uint8_t*>(out) + (size_t)((2 * p2_tile(cl, -1) + rank) * 64 + (g & 1) * 32 + w * 8 + (g >> 1)) * P2_XROW + q * 16;
                p2_epilogue_add(acc0, o, up, zero);
                p2_epilogue_add(acc1, o + 384, up, zero);
                TR2(3);
                break;
            }
            mbar_wait(bar_xfull, (n + head) & 1);
            TR2(1);
            wg_wait<0>();
            TR2(2);
            release_b(prev, true);
            p2_epilogue(acc0, acc1, sx, sbase + P2_OFF_BIAS + q * 32, up, zero);
            TR2(3);
            asm volatile("fence.proxy.async.shared::cta;\n" ::: "memory");
            __syncwarp();
            arrive1(bar_oready);
            if (!more) break;
            ok_a = false;
            seek(p2_start(n + 3));
            mbar_wait(bar_bfull + st, ph);
        }
        if (blockIdx.x == 120 && threadIdx.x < (LN_RING + 3 + NSMALL) * 2) (&g_flag[0][0][0])[threadIdx.x * 8] = 0;
        if (blockIdx.x == 121 && threadIdx.x == 0) atomicAdd(&g_epoch, 1u);
        TSTAMP(1, 30);
    }
}

}

extern "C" void kernel_launch(void* const* d_in, const int* in_sizes, int n_in, void* d_out, int out_size) {
    const __nv_bfloat16* x = (const __nv_bfloat16*)d_in[0];
    const __nv_bfloat16* dw = (const __nv_bfloat16*)d_in[1];
    const __nv_bfloat16* w1 = (const __nv_bfloat16*)d_in[2];
    const __nv_bfloat16* w2 = (const __nv_bfloat16*)d_in[3];
    const __nv_bfloat16* grn_g = (const __nv_bfloat16*)d_in[4];
    const __nv_bfloat16* grn_b = (const __nv_bfloat16*)d_in[5];
    __nv_bfloat16* out = (__nv_bfloat16*)d_out;

    cudaFuncSetAttribute(pass1_kernel<2>, cudaFuncAttributeMaxDynamicSharedMemorySize, P1_SMEM);
    cudaFuncSetAttribute(pass1_kernel<8>, cudaFuncAttributeMaxDynamicSharedMemorySize, P1_SMEM);
    cudaFuncSetAttribute(pass2_kernel, cudaFuncAttributeMaxDynamicSharedMemorySize, P2_SMEM);

    typedef CUresult (*EncodeFn)(CUtensorMap*, CUtensorMapDataType, cuuint32_t, void*, const cuuint64_t*, const cuuint64_t*,
                                 const cuuint32_t*, const cuuint32_t*, CUtensorMapInterleave, CUtensorMapSwizzle,
                                 CUtensorMapL2promotion, CUtensorMapFloatOOBfill);
    static EncodeFn encode = nullptr;
    if (!encode) {
        cudaDriverEntryPointQueryResult qres;
        cudaGetDriverEntryPoint("cuTensorMapEncodeTiled", (void**)&encode, cudaEnableDefault, &qres);
    }
    CUtensorMap wmap;
    const cuuint64_t gdim[2] = {HID, C_DIM};
    const cuuint64_t gstr[1] = {HID * 2};
    const cuuint32_t box[2] = {64, 192}, estr[2] = {1, 1};
    CUresult er = encode(&wmap, CU_TENSOR_MAP_DATA_TYPE_BFLOAT16, 2, (void*)w1, gdim, gstr, box, estr, CU_TENSOR_MAP_INTERLEAVE_NONE,
           CU_TENSOR_MAP_SWIZZLE_128B, CU_TENSOR_MAP_L2_PROMOTION_L2_128B, CU_TENSOR_MAP_FLOAT_OOB_FILL_NONE);
    if (er != CUDA_SUCCESS) printf("tensor map encode failed %d\n", (int)er);

    cudaLaunchAttribute attr[1];
    attr[0].id = cudaLaunchAttributeProgrammaticStreamSerialization;
    attr[0].val.programmaticStreamSerializationAllowed = 1;
    cudaLaunchConfig_t cfg = {};
    cfg.stream = 0;
    cfg.blockDim = dim3(512);
    cfg.dynamicSmemBytes = P1_SMEM;
    static int wide = -1;
    if (wide < 0) {
        int n = 0;
        cfg.gridDim = dim3(8 * NGRP);
        wide = cudaOccupancyMaxActiveClusters(&n, pass1_kernel<8>, &cfg) == cudaSuccess && n >= NGRP;
    }
    if (wide) pass1_kernel<8><<<8 * NGRP, 512, P1_SMEM>>>(wmap, x, dw, w1, 0);
    else pass1_kernel<2><<<8 * NGRP, 512, P1_SMEM>>>(wmap, x, dw, w1, 0);
    cfg.attrs = attr;
    cfg.numAttrs = 1;
    cfg.gridDim = dim3(NUM_CTAS);
    cfg.dynamicSmemBytes = P2_SMEM;
    cudaLaunchKernelEx(&cfg, pass2_kernel, wmap, x, w2, grn_g, grn_b, out, 0);
}
```

```cpp
#include <cuda.h>
#include <cuda_runtime.h>
#include <cuda_bf16.h>
#include <stdint.h>
#include <stdio.h>

namespace {

constexpr int M_TOTAL = 384 * 384;
constexpr int C_DIM   = 384;
constexpr int HID     = 1536;
constexpr int NT128   = M_TOTAL / 128;
constexpr int NUM_CTAS = 132;

constexpr int NGRP = 15, NSMALL = 100;
constexpr int LN_STEP = 2 * NGRP, LN_RING = 2 * LN_STEP;
__device__ __forceinline__ int p1_tile(int t) { return t < LN_STEP ? t : t + min((t - LN_STEP) / 10 + 1, NSMALL); }
__device__ __forceinline__ int p1_place(int tile, int slot) {
    const int i = (tile + 3) / 11;
    return i * 11 == tile + 3 && (unsigned)(i - 3) < NSMALL ? LN_RING + i : slot;
}
constexpr int LN_TILE = 128 * C_DIM * 2;
constexpr int H_TILE = 64 * HID * 3 / 2;
constexpr int H_HALF = 3072, H_STEP = 6144;

__device__ __align__(1024) uint4 g_h[(size_t)M_TOTAL * HID * 3 / 32];
__device__ __align__(1024) uint4 g_ln[(LN_RING + 3 + NSMALL) * LN_TILE / 16];
__device__ __align__(1024) uint4 g_w2img[2][HID * C_DIM * 2 / 16];
__device__ __align__(16) float g_sums[2][HID + 2 * C_DIM];
__device__ __align__(16) unsigned g_ex[HID];
__device__ unsigned g_epoch;
__device__ __align__(128) unsigned g_img[3];
__device__ __align__(128) unsigned g_half[32][2];
__device__ unsigned g_flag[LN_RING + 3 + NSMALL][2][8];
#define TSTAMP(k, i)
#define STAMPT(t, i)
#define TRACE(wg, pos, i)
#define TRACEW(pos, i)

#define TR2(i)
#define TR2P(pos, i)
__host__ __device__ __forceinline__ int perm32(int n) {
    return (n & ~31) | (((n >> 1) & 3) << 3) | (((n >> 3) & 3) << 1) | (n & 1);
}

__device__ __forceinline__ uint32_t smem_u32(const void* p) { return (uint32_t)__cvta_generic_to_shared(p); }

__device__ __forceinline__ void mbar_init(uint32_t bar, uint32_t count) {
    asm volatile("mbarrier.init.shared::cta.b64 [%0], %1;\n" ::"r"(bar), "r"(count) : "memory");
}
__device__ __forceinline__ void mbar_expect_tx(uint32_t bar, uint32_t bytes) {
    asm volatile("mbarrier.arrive.expect_tx.shared::cta.b64 _, [%0], %1;\n" ::"r"(bar), "r"(bytes) : "memory");
}
__device__ __forceinline__ void mbar_arrive(uint32_t bar) {
    asm volatile("mbarrier.arrive.shared::cta.b64 _, [%0];\n" ::"r"(bar) : "memory");
}
__device__ __forceinline__ void mbar_arrive_cluster(uint32_t bar_cluster_addr) {
    asm volatile("mbarrier.arrive.shared::cluster.b64 _, [%0];\n" ::"r"(bar_cluster_addr) : "memory");
}
#define SAFE_BREAK
__device__ __forceinline__ void mbar_wait(uint32_t bar, uint32_t parity) {
    asm volatile(
        "{\n"
        ".reg .pred p;\n"
        "LAB_WAIT:\n"
        "mbarrier.try_wait.parity.shared::cta.b64 p, [%0], %1;\n"
        "@!p bra LAB_WAIT;\n"
        "}\n" ::"r"(bar), "r"(parity) : "memory");
}
__device__ __forceinline__ bool mbar_test(uint32_t bar, uint32_t parity) {
    uint32_t ok;
    asm volatile("{\n.reg .pred p;\n"
                 "mbarrier.test_wait.parity.shared::cta.b64 p, [%1], %2;\n"
                 "selp.u32 %0, 1, 0, p;\n}\n" : "=r"(ok) : "r"(bar), "r"(parity) : "memory");
    return ok != 0;
}
__device__ __forceinline__ uint32_t mapa(uint32_t addr, uint32_t rank) {
    uint32_t r;
    asm volatile("mapa.shared::cluster.u32 %0, %1, %2;\n" : "=r"(r) : "r"(addr), "r"(rank));
    return r;
}
__device__ __forceinline__ void bulk_g2s(uint32_t dst, const void* src, uint32_t bytes, uint32_t bar) {
    asm volatile("cp.async.bulk.shared::cluster.global.mbarrier::complete_tx::bytes [%0], [%1], %2, [%3];\n"
                 ::"r"(dst), "l"(src), "r"(bytes), "r"(bar) : "memory");
}
__device__ __forceinline__ void bulk_g2s_mc(uint32_t dst, const void* src, uint32_t bytes, uint32_t bar, uint16_t mask) {
    asm volatile("cp.async.bulk.shared::cluster.global.mbarrier::complete_tx::bytes.multicast::cluster [%0], [%1], %2, [%3], %4;\n"
                 ::"r"(dst), "l"(src), "r"(bytes), "r"(bar), "h"(mask) : "memory");
}
__device__ __forceinline__ void tma2(uint32_t dst, const CUtensorMap* map, int c0, int c1, uint32_t bar) {
    asm volatile("cp.async.bulk.tensor.2d.shared::cluster.global.tile.mbarrier::complete_tx::bytes [%0], [%1, {%2, %3}], [%4];\n"
                 ::"r"(dst), "l"(map), "r"(c0), "r"(c1), "r"(bar) : "memory");
}
template <bool ACQ>
__device__ __forceinline__ uint32_t flag_wait(const unsigned* p, unsigned target) {
    unsigned v, n = 0;
    do {
        if (ACQ) asm volatile("ld.acquire.gpu.global.u32 %0, [%1];\n" : "=r"(v) : "l"(p) : "memory");
        else asm volatile("ld.relaxed.gpu.global.u32 %0, [%1];\n" : "=r"(v) : "l"(p) : "memory");
        n++;
    } while (v < target);
    return n == 1;
}
__device__ __forceinline__ void ldsm4t(uint32_t (&r)[4], uint32_t addr) {
    asm volatile("ldmatrix.sync.aligned.m8n8.x4.trans.shared.b16 {%0,%1,%2,%3}, [%4];\n"
                 : "=r"(r[0]), "=r"(r[1]), "=r"(r[2]), "=r"(r[3]) : "r"(addr) : "memory");
}
__device__ __forceinline__ void bulk_s2g(void* dst, uint32_t src, uint32_t bytes) {
    asm volatile("cp.async.bulk.global.shared::cta.bulk_group [%0], [%1], %2;\n" ::"l"(dst), "r"(src), "r"(bytes) : "memory");
}
__device__ __forceinline__ void gdc_wait() { asm volatile("griddepcontrol.wait;\n" ::: "memory"); }
__device__ __forceinline__ void gdc_launch() { asm volatile("griddepcontrol.launch_dependents;\n" ::: "memory"); }
__device__ __forceinline__ uint32_t cluster_rank() {
    uint32_t r;
    asm volatile("mov.u32 %0, %%cluster_ctarank;\n" : "=r"(r));
    return r;
}
__device__ __forceinline__ bool elect_one() {
    uint32_t pred;
    asm volatile("{\n.reg .pred p;\nelect.sync _|p, 0xffffffff;\nselp.u32 %0, 1, 0, p;\n}\n" : "=r"(pred));
    return pred != 0;
}
__device__ __forceinline__ void wg_fence() { asm volatile("wgmma.fence.sync.aligned;\n" ::: "memory"); }
__device__ __forceinline__ void wg_commit() { asm volatile("wgmma.commit_group.sync.aligned;\n" ::: "memory"); }
template <int N> __device__ __forceinline__ void wg_wait() {
    asm volatile("wgmma.wait_group.sync.aligned %0;\n" ::"n"(N) : "memory");
}
template <int R> __device__ __forceinline__ void reg_inc() { asm volatile("setmaxnreg.inc.sync.aligned.u32 %0;\n" ::"n"(R)); }
template <int R> __device__ __forceinline__ void reg_dec() { asm volatile("setmaxnreg.dec.sync.aligned.u32 %0;\n" ::"n"(R)); }
__device__ __forceinline__ void bar_sync(int id, int n) { asm volatile("bar.sync %0, %1;\n" ::"r"(id), "r"(n) : "memory"); }
__device__ __forceinline__ void bar_arrive(int id, int n) { asm volatile("bar.arrive %0, %1;\n" ::"r"(id), "r"(n) : "memory"); }

__device__ __forceinline__ uint64_t make_desc(uint32_t saddr, uint32_t lbo, uint32_t sbo) {
    return (uint64_t)((saddr & 0x3FFFF) >> 4) | ((uint64_t)(lbo >> 4) << 16) | ((uint64_t)(sbo >> 4) << 32);
}

__device__ __forceinline__ void stg128_cs(void* p, uint32_t a, uint32_t b, uint32_t c, uint32_t d) {
    asm volatile("st.global.cs.v4.u32 [%0], {%1,%2,%3,%4};\n" ::"l"(p), "r"(a), "r"(b), "r"(c), "r"(d) : "memory");
}
__device__ __forceinline__ uint32_t pack_bf16(float lo, float hi) {
    uint32_t r;
    asm("cvt.rn.bf16x2.f32 %0, %1, %2;\n" : "=r"(r) : "f"(hi), "f"(lo));
    return r;
}
__device__ __forceinline__ float bf_lo(uint32_t v) { return __uint_as_float(v << 16); }
__device__ __forceinline__ float bf_hi(uint32_t v) { return __uint_as_float(v & 0xffff0000u); }
__device__ __forceinline__ uint32_t bf2_mul(uint32_t a, uint32_t b) {
    uint32_t r;
    asm("mul.rn.bf16x2 %0, %1, %2;\n" : "=r"(r) : "r"(a), "r"(b));
    return r;
}
__device__ __forceinline__ uint32_t bf2_fma(uint32_t a, uint32_t b, uint32_t c) {
    uint32_t r;
    asm("fma.rn.bf16x2 %0, %1, %2, %3;\n" : "=r"(r) : "r"(a), "r"(b), "r"(c));
    return r;
}
__device__ __forceinline__ uint32_t bf2_add(uint32_t a, uint32_t b) {
    uint32_t r;
    asm("add.rn.bf16x2 %0, %1, %2;\n" : "=r"(r) : "r"(a), "r"(b));
    return r;
}
constexpr float KAPPA = 0.3292034911525734f;
constexpr float GELU_C = 2.423681954311584f;
constexpr float HSCALE = 1.0f / (2.0f * KAPPA);
__device__ __forceinline__ uint32_t acc_exp(float z) { return max(__float_as_uint(z) >> 23, 10u); }
__device__ __forceinline__ void sched_break(int zero) {
    asm volatile("{\n.reg .pred p;\nsetp.ne.s32 p, %0, 0;\nSB_LOOP:\n@p nanosleep.u32 1;\n@p bra SB_LOOP;\n}\n" ::"r"(zero));
}

#define ACCR8(d, o) "+r"(d[o + 0]), "+r"(d[o + 1]), "+r"(d[o + 2]), "+r"(d[o + 3]), "+r"(d[o + 4]), "+r"(d[o + 5]), "+r"(d[o + 6]), "+r"(d[o + 7])
__device__ __forceinline__ void mma_rs_n128(uint32_t (&d)[32], const uint32_t (&a)[4], uint64_t desc, int scale_d) {
    asm volatile(
        "{\n.reg .pred p;\nsetp.ne.b32 p, %37, 0;\n"
        "wgmma.mma_async.sync.aligned.m64n128k16.f16.f16.f16 "
        "{%0,%1,%2,%3,%4,%5,%6,%7,%8,%9,%10,%11,%12,%13,%14,%15,"
        "%16,%17,%18,%19,%20,%21,%22,%23,%24,%25,%26,%27,%28,%29,%30,%31},"
        "{%32,%33,%34,%35}, %36, p, 1, 1, 0;\n}\n"
        : ACCR8(d, 0), ACCR8(d, 8), ACCR8(d, 16), ACCR8(d, 24)
        : "r"(a[0]), "r"(a[1]), "r"(a[2]), "r"(a[3]), "l"(desc), "r"(scale_d));
}
__device__ __forceinline__ void mma_ss_n128(uint32_t (&d)[32], uint64_t da, uint64_t db) {
    asm volatile(
        "{\n.reg .pred p;\nsetp.ne.b32 p, %34, 0;\n"
        "wgmma.mma_async.sync.aligned.m64n128k16.f16.f16.f16 "
        "{%0,%1,%2,%3,%4,%5,%6,%7,%8,%9,%10,%11,%12,%13,%14,%15,"
        "%16,%17,%18,%19,%20,%21,%22,%23,%24,%25,%26,%27,%28,%29,%30,%31},"
        "%32, %33, p, 1, 1, 0, 0;\n}\n"
        : ACCR8(d, 0), ACCR8(d, 8), ACCR8(d, 16), ACCR8(d, 24)
        : "l"(da), "l"(db), "r"(1));
}
__device__ __forceinline__ uint32_t bf2_as_h2(uint32_t v) { return (v & 0x0fff0fffu) * 7u + v; }
__device__ __forceinline__ float h_lo(uint32_t v) {
    float r;
    asm("{\n.reg .b16 l, h;\nmov.b32 {l, h}, %1;\ncvt.f32.f16 %0, l;\n}\n" : "=f"(r) : "r"(v));
    return r;
}
__device__ __forceinline__ float h_hi(uint32_t v) {
    float r;
    asm("{\n.reg .b16 l, h;\nmov.b32 {l, h}, %1;\ncvt.f32.f16 %0, h;\n}\n" : "=f"(r) : "r"(v));
    return r;
}

__device__ __forceinline__ void mma_rs_n192(uint32_t (&d)[48], const uint4& a, uint64_t db, int scale_d) {
    asm volatile(
        "{\n.reg .pred p;\nsetp.ne.b32 p, %53, 0;\n"
        "wgmma.mma_async.sync.aligned.m64n192k16.f16.f16.f16 "
        "{%0,%1,%2,%3,%4,%5,%6,%7,%8,%9,%10,%11,%12,%13,%14,%15,"
        "%16,%17,%18,%19,%20,%21,%22,%23,%24,%25,%26,%27,%28,%29,%30,%31,"
        "%32,%33,%34,%35,%36,%37,%38,%39,%40,%41,%42,%43,%44,%45,%46,%47},"
        "{%48,%49,%50,%51}, %52, p, 1, 1, 0;\n}\n"
        : ACCR8(d, 0), ACCR8(d, 8), ACCR8(d, 16), ACCR8(d, 24), ACCR8(d, 32), ACCR8(d, 40)
        : "r"(a.x), "r"(a.y), "r"(a.z), "r"(a.w), "l"(db), "r"(scale_d));
}

__device__ __forceinline__ uint32_t pack_f16(float lo, float hi) {
    uint32_t r;
    asm("cvt.rn.f16x2.f32 %0, %1, %2;\n" : "=r"(r) : "f"(hi), "f"(lo));
    return r;
}

constexpr int P1_IMG = 900;
constexpr int P1_SLOT = LN_TILE / 2, P1_NST = 4;
constexpr int P1_X = 16 * C_DIM * 2;
constexpr int P1_OFF_A = P1_SLOT * P1_NST;
constexpr int P1_OFF_DW = P1_OFF_A + 3 * 2048;
constexpr int P1_OFF_X = P1_OFF_DW + C_DIM * 2;
constexpr int P1_OFF_BAR = P1_OFF_X + 2 * P1_X;
constexpr int P1_OFF_TILE = P1_OFF_BAR + (2 * P1_NST + 3 + 2 + 3 + 2) * 8;
constexpr int P1_SMEM = P1_OFF_TILE + 64;

__device__ __forceinline__ float rsqrt_fast(float x) {
    float r;
    asm("rsqrt.approx.ftz.f32 %0, %1;\n" : "=f"(r) : "f"(x));
    return r;
}
__device__ __forceinline__ float sum8(const uint32_t (&c)[4]) {
    const uint32_t u = bf2_add(bf2_add(c[0], c[1]), bf2_add(c[2], c[3]));
    return bf_lo(u) + bf_hi(u);
}
__device__ __forceinline__ void lds128(uint32_t (&v)[4], uint32_t a) {
    asm volatile("ld.shared.v4.u32 {%0,%1,%2,%3}, [%4];\n" : "=r"(v[0]), "=r"(v[1]), "=r"(v[2]), "=r"(v[3]) : "r"(a) : "memory");
}
template <class F>
__device__ __forceinline__ void ln_row(uint32_t (&v)[6][4], uint32_t sdw, F after_loads) {
    uint32_t c[4], s[4], d[4], nm;
#pragma unroll
    for (int i = 0; i < 6; i++) {
        lds128(d, sdw + i * 128);
        if (i == 0) {
#pragma unroll
            for (int k = 0; k < 4; k++) c[k] = bf2_mul(v[0][k], d[k]);
            const float p = sum8(c) * -0.125f;
            nm = pack_bf16(p, p);
        }
#pragma unroll
        for (int k = 0; k < 4; k++) {
            v[i][k] = bf2_fma(v[i][k], d[k], nm);
            s[k] = i ? bf2_add(v[i][k], s[k]) : v[i][k];
            c[k] = i ? bf2_fma(v[i][k], v[i][k], c[k]) : bf2_mul(v[i][k], v[i][k]);
        }
    }
    after_loads(c[0]);
    float m = fmaf(sum8(s), 1.0f / 48, -bf_lo(nm));
    float q = fmaf(-bf_lo(nm), fmaf(2.f, m, bf_lo(nm)), sum8(c) * (1.0f / 48));
#pragma unroll
    for (int o = 1; o < 8; o <<= 1) {
        m += __shfl_xor_sync(0xffffffffu, m, o);
        q += __shfl_xor_sync(0xffffffffu, q, o);
    }
    m *= 0.125f;
    const float r = KAPPA * rsqrt_fast(fmaxf(fmaf(-m, m, q * 0.125f), 0.f) + 1e-5f);
    const float e = (-bf_lo(nm) - m) * r * 0x1p-112f;
    const bool two = __any_sync(0xffffffffu, r < 0x1p-14f);
    const float r1 = r * (two ? 0x1p-56f : 0x1p-112f);
    uint32_t mul = pack_bf16(r1, r1), add = two ? 0u : pack_bf16(e, e);
#pragma unroll 1
    for (int it = !two; it < 2; it++) {
#pragma unroll
        for (int i = 0; i < 6; i++)
#pragma unroll
            for (int k = 0; k < 4; k++) v[i][k] = bf2_fma(v[i][k], mul, add);
        mul = 0x23802380u;
        add = pack_bf16(e, e);
    }
#pragma unroll
    for (int i = 0; i < 6; i++)
#pragma unroll
        for (int k = 0; k < 4; k++) v[i][k] = bf2_as_h2(v[i][k]);
}

__device__ __forceinline__ float gelu_s(float y) {
    float u = y * fmaf(y, y, GELU_C);
    float t;
    asm volatile("tanh.approx.f32 %0, %1;\n" : "=f"(t) : "f"(u));
    return fmaf(y, t, y);
}
__device__ __forceinline__ void p1_pack(int c, uint32_t (&p)[4], uint32_t (&dd)[4]) {
#pragma unroll
    for (int u = 0; u < 4; u++) {
        if ((c & 3) == 0) dd[u] = p[u];
        else {
            uint32_t n = dd[u];
            if ((c & 3) == 1) n = __byte_perm(n, 0, 0x2301);
            if ((c & 3) == 2) {
                dd[u] = __byte_perm(n >> 3, n >> 1, 0x6341);
                n = __byte_perm(n >> 3, n >> 1, 0x7250);
            }
            asm("lop3.b32 %0, %0, %1, 0x40074007, 0xd8;\n" : "+r"(p[u]) : "r"(n));
        }
    }
}
__device__ __forceinline__ void p1_store(int c, const uint32_t (&p)[4], uint8_t* hptr) {
    if (c & 3) stg128_cs(hptr + (c >> 2) * H_HALF + ((c & 3) - 1) * 512, p[0], p[1], p[2], p[3]);
}

template <bool GEN>
__device__ __forceinline__ void p1_epilogue(uint32_t (&acc)[32], float (&ssq)[2], uint32_t sc2, uint8_t* hp, int zero) {
    uint32_t sq[2], dd[4];
#pragma unroll
    for (int c = 0; c < 8; c++) {
        if (GEN) sched_break(zero);
        uint32_t p[4];
#pragma unroll
        for (int u = 0; u < 4; u++) {
            const uint32_t y = acc[8 * (c >> 1) + 2 * u + (c & 1)];
            if (GEN) {
                const float sc = c & 1 ? bf_hi(sc2) : bf_lo(sc2), fs = __uint_as_float(0x78000000u - __float_as_uint(sc));
                const float g0 = gelu_s(h_lo(y) * fs), g1 = gelu_s(h_hi(y) * fs);
                ssq[c & 1] = fmaf(g1, g1, fmaf(g0, g0, ssq[c & 1]));
                p[u] = pack_f16(g0 * sc, g1 * sc);
            } else {
                uint32_t g;
                asm("{\n.reg .b32 w;\n"
                    "fma.rn.f16x2 w, %1, %1, %2;\n"
                    "mul.rn.f16x2 w, w, %1;\n"
                    "tanh.approx.f16x2 w, w;\n"
                    "fma.rn.f16x2 %0, %1, w, %1;\n}\n" : "=r"(g) : "r"(y), "r"(0x40d940d9u));
                acc[8 * (c >> 1) + 2 * u + (c & 1)] = g;
                if (c < 2 && u == 0) asm("mul.rn.f16x2 %0, %1, %1;\n" : "=r"(sq[c & 1]) : "r"(g));
                else asm("fma.rn.f16x2 %0, %1, %1, %0;\n" : "+r"(sq[c & 1]) : "r"(g));
                if (c & 1) asm("{\n.reg .b16 l, h;\n.reg .b32 f;\nmov.b32 {l, h}, %2;\nmov.b32 f, {h, h};\nmul.rn.f16x2 %0, %1, f;\n}\n" : "=r"(p[u]) : "r"(g), "r"(sc2));
                else asm("{\n.reg .b16 l, h;\n.reg .b32 f;\nmov.b32 {l, h}, %2;\nmov.b32 f, {l, l};\nmul.rn.f16x2 %0, %1, f;\n}\n" : "=r"(p[u]) : "r"(g), "r"(sc2));
            }
        }
        p1_pack(c, p, dd);
        if (c & 3) {
#pragma unroll
            for (int u = 0; u < 4; u++) acc[4 * (c - 1 - (c >> 2)) + u] = p[u];
        }
        p1_store(c, p, hp);
    }
    if (!GEN) {
#pragma unroll
        for (int r = 0; r < 2; r++) ssq[r] += h_lo(sq[r]) + h_hi(sq[r]);
    }
}
template <int CS, int NWG>
__device__ __forceinline__ void p1_compute(uint32_t sbase, int cb0, int warp, int lane, int zero) {
    const uint32_t bar_full = sbase + P1_OFF_BAR, bar_empty = bar_full + P1_NST * 8, bar_w = bar_empty + P1_NST * 8;
    const int wg = warp >> 2, w = warp & 3, cb = cb0 + wg;
    const uint32_t slot_free = mapa(bar_empty, lane & (CS - 1)) + (lane / CS) * 8;
    if (lane < 4 * CS && lane / CS != 1 + wg && (NWG == 2 || wg || lane >= CS)) mbar_arrive_cluster(slot_free);
    if (wg == 1) bar_arrive(1, 256);
    uint32_t a[24][4], ex[2], gen = 0;
    const uint32_t wsrc = sbase + (1 + wg) * P1_SLOT + ((lane >> 4) * 8 + (lane & 7)) * 128 + (((2 * w + ((lane >> 3) & 1)) ^ (lane & 7)) << 4);
#pragma unroll 1
    for (int it = 0; it < 2; it++) {
        if (it) mbar_wait(bar_w + wg * 8, 0);
        TRACEW(110 + warp, 5);
        if (it || wg == 0) {
#pragma unroll
        for (int k = 0; k < 24; k++) ldsm4t(a[k], wsrc + k * 2048);
#pragma unroll
        for (int r = 0; r < 2; r++) {
            float t = 0.f;
#pragma unroll
            for (int j = 0; j < 6; j++) {
                uint32_t c = bf2_mul(a[4 * j][r], a[4 * j][r]);
#pragma unroll
                for (int k = 1; k < 8; k++) c = bf2_fma(a[4 * j + k / 2][r + (k & 1) * 2], a[4 * j + k / 2][r + (k & 1) * 2], c);
                t += bf_lo(c) + bf_hi(c);
            }
            t += __shfl_xor_sync(0xffffffffu, t, 1);
            t += __shfl_xor_sync(0xffffffffu, t, 2);
            asm("sqrt.approx.f32 %0, %0;\n" : "+f"(t));
            ex[r] = min(max(__float_as_uint(13.9f * t) >> 23, 72u), 198u);
        }
        asm volatile("{\n.reg .pred p;\nsetp.gt.u32 p, %1, 7;\nbar.red.or.pred p, %2, 128, p;\nselp.u32 %0, 1, 0, p;\n}\n"
                     : "=r"(gen) : "r"(max(ex[0] - 125u, ex[1] - 125u)), "r"(5 + wg) : "memory");
        gen = __shfl_sync(0xffffffffu, gen, 0) & it;
        if (it) {
            if ((lane & 3) < 2) g_ex[cb * 64 + w * 16 + (lane & 1) * 8 + (lane >> 2)] = lane & 1 ? ex[1] : ex[0];
            if (lane / CS == 1 + wg) mbar_arrive_cluster(slot_free);
            __syncwarp();
        }
        }
        if (gen) {
#pragma unroll
            for (int k = 0; k < 24; k++)
#pragma unroll
                for (int j = 0; j < 4; j++) a[k][j] = bf2_mul(a[k][j], (268u - ex[j & 1]) * 0x00800080u);
        }
        if (it || wg == 1) {
#pragma unroll
            for (int k = 0; k < 24; k++)
#pragma unroll
                for (int j = 0; j < 4; j++) {
                    a[k][j] = bf2_as_h2(bf2_mul(a[k][j], 0x07800780u));
                    asm volatile("" : "+r"(a[k][j]));
                }
        }
        TRACEW(110 + warp, 6);
    }
#pragma unroll
    for (int j = 0; j < 4; j++)
        asm volatile("st.shared.u32 [%0], %1;\n" ::"r"(sbase + P1_OFF_A + warp * 512 + (j & 1) * 256 + (j >> 1) * 128 + lane * 4), "r"(a[23][j]) : "memory");
    asm volatile("fence.proxy.async.shared::cta;\n" ::: "memory");
    TRACEW(110 + warp, 7);
    const uint32_t ex2 = ex[0] | ex[1] << 16;
    const uint32_t sc2 = gen ? 0x7f007f00u - (ex2 << 7) : (0x008e008eu - ex2) << 10;
    const uint32_t empty_remote = mapa(bar_empty, lane & (CS - 1));
    const int g = lane >> 2, q = lane & 3, turn = wg + 1 == NWG ? 1 : wg + 2;
    float ssq[2] = {0.f, 0.f};
    uint32_t acc[32] = {};
    TSTAMP(0, 1);
    STAMPT(128, 4);
    STAMPT(256, 5);

    uint8_t* hp = reinterpret_cast<uint8_t*>(g_h) + ((cb * 2 + (w >> 1)) * H_STEP + (w & 1) * 1536) + g * 64 + (q ^ (g >> 1)) * 16;
    const uint64_t desc_base = make_desc(sbase, 16, 1024) | (1ull << 62);
    const uint64_t da = make_desc(sbase + P1_OFF_A + wg * 2048, 128, 256);
#pragma unroll 1
    for (int i = 0;; i++) {
        const int s0 = (i & 1) * 16, par = (i >> 1) & 1;
        const uint64_t d0 = desc_base + (uint64_t)((i & 1) * (LN_TILE / 16));
        TRACE(wg, i, 0);
        mbar_wait(bar_full + s0, par);
        bar_sync(1 + wg, 256);
        TRACE(wg, i, 1);
        uint32_t step, more;
        wg_fence();
#pragma unroll
        for (int k = 0; k < 24; k++) {
            if (k == 12) mbar_wait(bar_full + s0 + 8, par);
            const uint64_t db = d0 + (uint64_t)((k >> 2) * 1024 + (k & 3) * 2);
            if (k < 23) mma_rs_n128(acc, a[k], db, k ? 1 : zero);
            else mma_ss_n128(acc, da, db);
            if (k == 23) bar_arrive(turn, 256);
            if (k % 12 == 11) wg_commit();
        }
        if (NWG == 2) {
            step = (i ? 11 : LN_STEP) * (2 * H_TILE);
            more = i + 1 < NSMALL;
        } else asm volatile("ld.shared.v2.u32 {%0, %1}, [%2];\n" : "=r"(step), "=r"(more) : "r"(sbase + P1_OFF_TILE + (i & 3) * 16) : "memory");
        TRACE(wg, i, 2);
        wg_wait<1>();
        if (lane < CS) mbar_arrive_cluster(empty_remote + s0);
        hp += step;
        TRACE(wg, i, 3);
        wg_wait<0>();
        TRACE(wg, i, 4);
        if (lane < CS) mbar_arrive_cluster(empty_remote + s0 + 8);
        if (gen) p1_epilogue<true>(acc, ssq, sc2, hp, zero);
        else p1_epilogue<false>(acc, ssq, sc2, hp, zero);
        if (!more) break;
    }
    TSTAMP(0, 21);
    if (wg == 0) bar_sync(1, 256);
    uint32_t par;
    if (NWG == 2) par = __ldcg(&g_epoch) & 1;
    else asm volatile("ld.shared.u32 %0, [%1];\n" : "=r"(par) : "r"(sbase + P1_OFF_TILE - 4) : "memory");
    float* sums = g_sums[par];
#pragma unroll
    for (int r = 0; r < 2; r++) {
        ssq[r] += __shfl_xor_sync(0xffffffffu, ssq[r], 1);
        ssq[r] += __shfl_xor_sync(0xffffffffu, ssq[r], 2);
        if (q == 0) atomicAdd(sums + cb * 64 + w * 16 + r * 8 + g, ssq[r]);
    }
    if (NWG == 2) {
        asm volatile("fence.proxy.async.global;\nfence.acq_rel.gpu;\n" ::: "memory");
        __syncwarp();
        if (lane == 0) asm volatile("red.relaxed.gpu.global.add.u32 [%0], 1;\n" ::"l"(&g_img[2]) : "memory");
    }
}

__device__ __forceinline__ void p1_w2(const __nv_bfloat16* __restrict__ w2, const __nv_bfloat16* __restrict__ grn_b, int w, int lane) {
    const int gw = blockIdx.x * 4 + w;
    float* sums = g_sums[__ldcg(&g_epoch) & 1] + HID;
    flag_wait<true>(&g_flag[40][1][0], 12);
    {
        const int col = gw % 6 * 64 + lane * 2;
        float bsum[2] = {0.f, 0.f}, asum[2] = {0.f, 0.f};
#pragma unroll 4
        for (int kk = 0; kk < 192; kk++) {
            const int k = gw / 6 * 192 + kk;
            const uint32_t v = *reinterpret_cast<const uint32_t*>(w2 + k * C_DIM + col);
            const float b = __bfloat162float(grn_b[k]), f = __uint_as_float(__ldcg(&g_ex[k]) << 23);
            bsum[0] = fmaf(b, bf_lo(v), bsum[0]);
            bsum[1] = fmaf(b, bf_hi(v), bsum[1]);
            asum[0] = fmaf(f, fabsf(bf_lo(v)), asum[0]);
            asum[1] = fmaf(f, fabsf(bf_hi(v)), asum[1]);
        }
#pragma unroll
        for (int j = 0; j < 2; j++) {
            atomicAdd(sums + col + j, bsum[j]);
            atomicAdd(sums + C_DIM + col + j, asum[j]);
        }
        __threadfence();
        __syncwarp();
        if (lane == 0) asm volatile("red.relaxed.gpu.global.add.u32 [%0], 1;\n" ::"l"(&g_flag[LN_RING + 2][0][0]) : "memory");
    }
    while (*(volatile unsigned*)&g_flag[P1_IMG % LN_RING][1][0] < 12 * (P1_IMG / LN_RING + 1)) {
        __nanosleep(2000);
        SAFE_BREAK
    }
    flag_wait<true>(&g_flag[LN_RING + 2][0][0], 48);
    float z = 0.f;
#pragma unroll
    for (int j = 0; j < C_DIM / 32; j++) z = fmaxf(z, __ldcg(sums + C_DIM + j * 32 + lane));
    const float sc = __uint_as_float((263u - acc_exp(__uint_as_float(__reduce_max_sync(0xffffffffu, __float_as_uint(z))))) << 23);
    const int np = gw % 6 * 64 + lane * 2;
#pragma unroll 2
    for (int cc = 0; cc < 24; cc++) {
        const int c = gw / 6 * 24 + cc;
        uint32_t v[8], o[2][4];
#pragma unroll
        for (int e = 0; e < 8; e++) v[e] = *reinterpret_cast<const uint32_t*>(w2 + (c * 8 + e) * C_DIM + perm32(np));
#pragma unroll
        for (int e = 0; e < 4; e++) {
            const uint2 t = __ldcg(reinterpret_cast<const uint2*>(g_ex) + c * 4 + e);
            const float f0 = __uint_as_float(t.x << 23), f1 = __uint_as_float(t.y << 23);
            o[0][e] = pack_f16(bf_lo(v[2 * e]) * f0 * sc, bf_lo(v[2 * e + 1]) * f1 * sc);
            o[1][e] = pack_f16(bf_hi(v[2 * e]) * f0 * sc, bf_hi(v[2 * e + 1]) * f1 * sc);
        }
#pragma unroll
        for (int j = 0; j < 2; j++)
            g_w2img[0][(((c >> 1) * 48 + (np >> 3)) * 2 + (c & 1)) * 8 + (np & 7) + j] = make_uint4(o[j][0], o[j][1], o[j][2], o[j][3]);
    }
    asm volatile("fence.proxy.async.global;\n" ::: "memory");
    __threadfence();
    __syncwarp();
    if (lane < 2) asm volatile("red.relaxed.gpu.global.add.u32 [%0], 1;\n" ::"l"(&g_img[lane * 2]) : "memory");
}

__device__ __forceinline__ void p1_load_w1(uint32_t sbase, const CUtensorMap* wmap, int cb0, int nwg) {
    const uint32_t bar_w = sbase + P1_OFF_BAR + 2 * P1_NST * 8;
    for (int i = 0; i < nwg; i++) {
        mbar_expect_tx(bar_w + i * 8, P1_SLOT);
        tma2(sbase + (1 + i) * P1_SLOT, wmap, (cb0 + i) * 64, 0, bar_w + i * 8);
        tma2(sbase + (1 + i) * P1_SLOT + P1_SLOT / 2, wmap, (cb0 + i) * 64, 192, bar_w + i * 8);
    }
}

template <int CS>
__global__ void __cluster_dims__(CS, 1, 1) __launch_bounds__(512, 1)
pass1_kernel(const __grid_constant__ CUtensorMap wmap, const __nv_bfloat16* __restrict__ x, const __nv_bfloat16* __restrict__ dw,
             const __nv_bfloat16* __restrict__ w1, int zero) {
    extern __shared__ __align__(1024) uint8_t smem[];
    const uint32_t sbase = smem_u32(smem);
    const uint32_t bar_full = sbase + P1_OFF_BAR, bar_empty = bar_full + P1_NST * 8, bar_w = bar_empty + P1_NST * 8;
    const uint32_t bar_xfull = bar_w + 24, bar_raw = bar_xfull + 16, bar_done = bar_raw + 16;
    const int tid = threadIdx.x;
    const int warp = __shfl_sync(0xffffffffu, tid >> 5, 0), lane = tid & 31;
    const uint32_t rank = cluster_rank();
    const int bid = blockIdx.x, cl = bid >> 1;
    uint8_t* const ring = reinterpret_cast<uint8_t*>(g_ln);
    const int ln0 = bid >> 2, items = (NT128 - 1 - ln0) / LN_STEP + 1;

    TSTAMP(0, 0);
    TRACEW(110 + warp, 0);

    if (warp >= 12) {
        reg_dec<56>();
        asm volatile("barrier.cluster.arrive.relaxed.aligned;\n" ::: "memory");
        asm volatile("barrier.cluster.wait.aligned;\n" ::: "memory");
        {
            auto ring_row = [&](int p) {
                const int n = (p & 8) * 8 + (lane >> 3) * 8 + (p & 3) * 2 + (p >> 2 & 1);
                return n * 128 + (((lane ^ n) & 7) << 4);
            };
            const uint8_t* xsrc = reinterpret_cast<const uint8_t*>(x) + (size_t)(LN_STEP * 8 + bid * 2 + (warp & 1)) * P1_X;
            const uint32_t xbar = bar_xfull + (warp & 1) * 8, xdst = sbase + P1_OFF_X + (warp & 1) * P1_X;
            const uint32_t sdw = sbase + P1_OFF_DW + (lane & 7) * 16;
            uint32_t src = xdst - P1_OFF_X + (lane >> 3) * (C_DIM * 2) + (lane & 7) * 16;
            int row0 = ring_row((bid & 7) * 2 + (warp & 1)) ^ 288, slot = bid >> 3, used = 0;
            auto next = [&]() {
                xsrc += (size_t)LN_STEP * 8 * P1_X;
                if (elect_one()) {
                    mbar_expect_tx(xbar, P1_X);
                    bulk_g2s(xdst, xsrc, P1_X, xbar);
                }
                __syncwarp();
            };
#pragma unroll 1
            for (int i = -1; i < items; i++) {
                if (warp == 14) TRACEW(128 + i, 0);
                const int place = p1_place(ln0 + i * LN_STEP, slot);
                const int last = i > 0 ? 3 : i ? 2 + (warp >> 1 & 1) : 1;
#pragma unroll 1
                for (int ps = i < 0 ? last - 4 : 0; ps <= last; ps += i < 0 ? 4 : 1) {
                    if (i < 0 && ps > 0) STAMPT(416, 6);
                    if (i < 0 && ps > 0) mbar_wait(bar_raw, 0);
                    if (i < 0 && ps > 0) STAMPT(416, 7);
                    if (ps == 0) {
                        if (used) flag_wait<false>(&g_flag[slot][1][0], used);
                        if (i && i + 1 < items && elect_one())
                            asm volatile("cp.async.bulk.prefetch.L2.global [%0], %1;\n" ::"l"(xsrc + (size_t)LN_STEP * 8 * P1_X), "r"(P1_X) : "memory");
                        if (i) mbar_wait(xbar, ~i & 1);
                        else mbar_wait(bar_raw + 8, 0);
                        if (warp == 14) TRACEW(128 + i, 1);
                    }
                    uint32_t v[6][4];
#pragma unroll
                    for (int j = 0; j < 6; j++) lds128(v[j], src + (ps & 3) * (4 * C_DIM * 2) + j * 128);
                    ln_row(v, sdw, [&](uint32_t dep) {
                        if (i == 0 && ps == 1 && lane < CS) mbar_arrive_cluster(mapa(bar_empty, lane) + (dep & zero));
                        if (ps == 3 && i > 0 && i + 1 < items && !__any_sync(0xffffffffu, dep & zero)) next();
                    });
                    uint8_t* dst = ring + (place * LN_TILE + (ps & 1) * 4096 + (row0 ^ (ps & 2) * 144));
#pragma unroll
                    for (int j = 0; j < 6; j++)
                        asm volatile("{\n.reg .pred p;\nsetp.ge.s32 p, %5, 0;\n@p st.global.v4.u32 [%0], {%1,%2,%3,%4};\n}\n"
                                     ::"l"(dst + j * 16384), "r"(v[j][0]), "r"(v[j][1]), "r"(v[j][2]), "r"(v[j][3]), "r"(ps) : "memory");
                }
                if (warp == 14) TRACEW(128 + i, 2);
                asm volatile("fence.proxy.async.global;\nfence.acq_rel.cta;\n" ::: "memory");
                if (i < 0) {
                    bar_sync(4, 128);
                    if (warp < 14) break;
                    row0 ^= 288;
                    slot += NGRP;
                } else {
                    if (i) mbar_wait(bar_done, ~i & 1);
                    else {
                        src += P1_OFF_X;
                        slot = ln0;
                        row0 = ring_row((bid & 3) * 4 + (warp & 1) * 2);
                    }
                    __syncwarp();
                    if (lane == 0) mbar_arrive(bar_done);
                    if ((slot += LN_STEP) >= LN_RING) { slot -= LN_RING; used += 12; }
                }
            }
            if (warp < 14 && lane < CS) mbar_arrive_cluster(mapa(bar_empty, lane));
        }
        if (warp == 12) {
            int prev = 0, t = cl >> 2, next = t + NGRP;
            const uint32_t rbase = mapa(sbase, lane & (CS - 1));
            int i = 0;
#pragma unroll 1
            for (; t < NT128; i++) {
                const int s0 = (i & 1) * 2, par = (i >> 1) & 1;
                const int round = t / LN_RING, slot = t - round * LN_RING;
                const uint8_t* src = ring + slot * LN_TILE + rank * (P1_SLOT / CS);
                int draw = 0;
                if (rank == 0 && lane == 0) draw = 2 * NGRP + atomicAdd(&g_flag[LN_RING + ((cl >> 1) & 1)][cl & 1][0], 1u);
                flag_wait<true>(&g_flag[slot][0][0], 8 * round + 8);
                TRACEW(i, 2);
                if (i == 0) STAMPT(384, 10);
                if (i == 2) STAMPT(384, 13);
                if (i == 3) STAMPT(384, 14);
                asm volatile("fence.proxy.async.global;\n" ::: "memory");
                draw = p1_tile(__shfl_sync(0xffffffffu, draw, 0));
#pragma unroll
                for (int h = 0; h < 2; h++) {
                    mbar_wait(bar_empty + (s0 + h) * 8, par);
                    TRACEW(i, 4 + h);
                    if (i == 0 && h == 1) STAMPT(384, 11);
                    if (elect_one()) {
                        mbar_expect_tx(bar_full + (s0 + h) * 8, P1_SLOT + 16 - 16 * h);
                        bulk_g2s_mc(sbase + (s0 + h) * P1_SLOT + rank * (P1_SLOT / CS), src + h * P1_SLOT, P1_SLOT / CS, bar_full + (s0 + h) * 8, (uint16_t)((1 << CS) - 1));
                    }
                    __syncwarp();
                    if (h == 0 && rank == 0 && lane < CS)
                        asm volatile("st.async.shared::cluster.mbarrier::complete_tx::bytes.v4.u32 [%0], {%1, %2, %3, %3}, [%4];\n"
                                     ::"r"(rbase + P1_OFF_TILE + (i & 3) * 16), "r"((t - prev) * (2 * H_TILE)), "r"((int)(next < NT128)), "r"(draw),
                                       "r"(rbase + P1_OFF_BAR + s0 * 8) : "memory");
                }
                prev = t;
                t = next;
                next = draw;
                if (rank != 0) {
                    mbar_wait(bar_full + s0 * 8, (i >> 1) & 1);
                    mbar_wait(bar_full + s0 * 8 + 8, (i >> 1) & 1);
                    if (lane == 0 && rank == 1) asm volatile("red.relaxed.gpu.global.add.u32 [%0], %1;\n" ::"l"(&g_flag[slot][1][0]), "r"(CS * 3 / 2) : "memory");
                    asm volatile("ld.shared.u32 %0, [%1];\n" : "=r"(next) : "r"(sbase + P1_OFF_TILE + (i & 3) * 16 + 8) : "memory");
                    TRACEW(i, 3);
                }
            }
#pragma unroll 1
            for (int j = 2 * i; j < 2 * i + 4; j++) mbar_wait(bar_empty + (j & 3) * 8, (j >> 2) & 1);
        } else if (warp == 13) {
            STAMPT(416, 8);
            if (lane == 0) asm volatile("red.release.gpu.global.add.u32 [%0], 1;\n" ::"l"(&g_flag[bid >> 3][0][0]) : "memory");
            __syncwarp();
            STAMPT(416, 9);
            const uint32_t ep = g_epoch & 1;
            asm volatile("st.shared.u32 [%0], %1;\n" ::"r"(sbase + P1_OFF_TILE - 4), "r"(ep) : "memory");
            if (bid < 18) reinterpret_cast<float4*>(g_sums[ep ^ 1])[bid * 32 + lane] = make_float4(0.f, 0.f, 0.f, 0.f);
#pragma unroll 1
            for (int i = 0; i < items; i++) {
                mbar_wait(bar_done, i & 1);
                asm volatile("fence.proxy.async.global;\n" ::: "memory");
                if (lane == 0) {
                    const int slot = i ? ln0 + (i & 1) * LN_STEP : NGRP + (bid >> 3), place = p1_place(ln0 + i * LN_STEP, slot);
                    mbar_arrive(bar_done);
                    asm volatile("red.release.gpu.global.add.u32 [%0], %1;\n" ::"l"(&g_flag[place][0][0]), "r"(i ? 2 : 1) : "memory");
                    if (place != slot) {
                        atomicAdd(&g_flag[slot][0][0], 2u);
                        atomicAdd(&g_flag[slot][1][0], 3u);
                    }
                }
                __syncwarp();
                TRACEW(128 + i, 3);
            }
        }
    } else {
        if (tid == 0) {
            mbar_init(bar_raw, 1);
            mbar_init(bar_raw + 8, 1);
            mbar_init(bar_xfull, 1);
            mbar_init(bar_xfull + 8, 1);
            for (int i = 0; i < 3; i++) mbar_init(bar_w + i * 8, 1);
            asm volatile("fence.mbarrier_init.release.cluster;\n" ::: "memory");
            {
                mbar_expect_tx(bar_raw, P1_X + C_DIM * 2);
                bulk_g2s(sbase + P1_OFF_DW, dw, C_DIM * 2, bar_raw);
                for (int i = 0; i < 2; i++) bulk_g2s(sbase + i * P1_X + P1_X / 2, x + (size_t)(bid * 16 + i * 8) * C_DIM, P1_X / 2, bar_raw);
                if (bid < 96) asm volatile("cp.async.bulk.prefetch.L2.global [%0], 12288;\n" ::"l"(w1 + bid * 6144) : "memory");
                mbar_expect_tx(bar_raw + 8, P1_X);
                for (int i = 0; i < 2; i++) bulk_g2s(sbase + i * P1_X, x + (size_t)(NGRP * 128 + bid * 16 + i * 8) * C_DIM, P1_X / 2, bar_raw + 8);
            }
            p1_load_w1(sbase, &wmap, (bid & 7) * 3, 3);
            for (int i = 0; i < 2; i++) {
                mbar_expect_tx(bar_xfull + i * 8, P1_X);
                bulk_g2s(sbase + P1_OFF_X + i * P1_X, x + (size_t)(LN_STEP * 128 + bid * 32 + i * 16) * C_DIM, P1_X, bar_xfull + i * 8);
            }
        }
        if (tid == 32) {
            mbar_init(bar_done, 3);
            mbar_arrive(bar_done);
            asm volatile("fence.mbarrier_init.release.cluster;\n" ::: "memory");
        }
        if (tid == 64) {
            for (int i = 0; i < P1_NST; i++) {
                mbar_init(bar_full + i * 8, 1);
                mbar_init(bar_empty + i * 8, 12 * CS);
            }
            asm volatile("fence.mbarrier_init.release.cluster;\n" ::: "memory");
            if (bid < 64) (&g_half[0][0])[bid] = 0;
            else if (bid < 67) g_img[bid - 64] = 0;
        }
        __syncwarp();
        asm volatile("barrier.cluster.arrive.relaxed.aligned;\n" ::: "memory");
        reg_inc<152>();
        TRACEW(110 + warp, 1);
        gdc_launch();
        asm volatile("barrier.cluster.wait.aligned;\n" ::: "memory");
        p1_compute<CS, 3>(sbase, (bid & 7) * 3, warp, lane, zero);
        TSTAMP(0, 30);
    }
}

constexpr int P2_B = 24576, P2_NB = 5;
constexpr int P2_A = 3072, P2_NA = 5;
constexpr int P2_XROW = C_DIM * 2;
constexpr int P2_OFF_A = P2_B * P2_NB;
constexpr int P2_OFF_X = P2_OFF_A + 3 * P2_NA * P2_A;
constexpr int P2_XHALF = 32 * P2_XROW + 64;
constexpr int P2_OFF_BIAS = P2_OFF_X + 64 * P2_XROW + 64;
constexpr int P2_OFF_GRN = P2_OFF_BIAS + C_DIM * 4;
constexpr int P2_OFF_RED = P2_OFF_GRN + HID * 2;
constexpr int P2_OFF_BAR = P2_OFF_RED + 192;
static_assert(P2_OFF_BAR >= P1_OFF_DW && P2_OFF_BAR + (2 * P2_NB + 6 * P2_NA + 3) * 8 <= P1_OFF_BAR, "");
constexpr int P2_SMEM = P1_SMEM;
constexpr int P2_LAG = 17;
constexpr int P2_NCL = NUM_CTAS / 2, P2_ITEMS = NT128 / P2_NCL, P2_SHARED = NT128 - P2_ITEMS * P2_NCL;
constexpr int P2_POS = P2_LAG * (P2_ITEMS - 1) + 48;
__device__ __forceinline__ int p2_start(int n) { return n < 0 ? 0 : n == P2_ITEMS ? P2_POS - 24 : P2_LAG * n; }
constexpr int P2_FOLD = 17;
constexpr int P2_XC = 8 * P2_XROW;
__device__ __forceinline__ int p2_tile(int cl, int n) {
    return n == 0 ? NT128 - 1 - cl : n < 0 || n == P2_ITEMS ? NT128 - 1 - P2_NCL - (cl >> 1) : cl + P2_NCL * (n - 1);
}

constexpr int P2_EG = 2;
__device__ __forceinline__ void p2_init(uint32_t (&acc)[48], int c, uint32_t sb) {
#pragma unroll
    for (int i = 8 * (c % 6); i < 8 * (c % 6) + 8; i += 4)
        asm volatile("ld.shared.v4.u32 {%0,%1,%2,%3}, [%4];\n" : "=r"(acc[i]), "=r"(acc[i + 1]), "=r"(acc[i + 2]), "=r"(acc[i + 3])
                     : "r"(sb + c * 128 + i % 8 * 4) : "memory");
}
__device__ __forceinline__ void p2_epilogue(uint32_t (&acc0)[48], uint32_t (&acc1)[48], uint32_t sx, uint32_t sb, uint32_t up, int zero) {
    uint32_t v[2][P2_EG][4];
    auto load = [&](int c, uint32_t a) {
#pragma unroll
        for (int j = 0; j < P2_EG; j++) {
            const int u = c * P2_EG + j;
            asm volatile("ld.shared.v4.u32 {%0,%1,%2,%3}, [%4];\n" : "=r"(v[c & 1][j][0]), "=r"(v[c & 1][j][1]), "=r"(v[c & 1][j][2]), "=r"(v[c & 1][j][3])
                         : "r"(a + (u >> 1) * 64 + (u & 1) * 4 * P2_XROW) : "memory");
        }
    };
    load(0, sx);
#pragma unroll
    for (int c = 0; c < 24 / P2_EG; c++) {
        if (c + 1 < 24 / P2_EG) load(c + 1, sx + (v[c & 1][P2_EG - 1][0] & zero));
#pragma unroll
        for (int j = 0; j < P2_EG; j++) {
            const int u = c * P2_EG + j, i = 8 * ((u >> 1) % 6) + (u & 1);
            const uint32_t (&acc)[48] = u < 12 ? acc0 : acc1;
            uint32_t (&w)[4] = v[c & 1][j];
#pragma unroll
            for (int e = 0; e < 4; e++)
                w[e] = bf2_fma(pack_bf16(h_lo(acc[i + 2 * e]), h_hi(acc[i + 2 * e])), up, w[e]);
            asm volatile("st.shared.v4.u32 [%4], {%0,%1,%2,%3};\n" ::"r"(w[0]), "r"(w[1]), "r"(w[2]), "r"(w[3]),
                         "r"(sx + (u >> 1) * 64 + (u & 1) * 4 * P2_XROW) : "memory");
        }
        p2_init(c < 6 ? acc0 : acc1, c, sb + (v[c & 1][1][0] & zero));
    }
}

__device__ __forceinline__ void p2_unpack(uint4& u, uint32_t o1, uint32_t o2, uint32_t o3) {
    u.z = o1 & 0xbff8bff8u;
    u.y = o2 & 0xbff8bff8u;
    u.w = o3 & 0xbff8bff8u;
    u.x = (__byte_perm(o1, 0, 0x2301) & 0x07400740u) | ((__byte_perm(o2, o3, 0x6240) << 3) & 0x38383838u) | ((__byte_perm(o2, o3, 0x3715) << 1) & 0x80808080u);
}
__device__ __forceinline__ uint32_t h2_mul(uint32_t a, uint32_t b) {
    uint32_t r;
    asm("mul.rn.f16x2 %0, %1, %2;\n" : "=r"(r) : "r"(a), "r"(b));
    return r;
}
__device__ __forceinline__ void p2_epilogue_add(const uint32_t (&acc)[48], uint8_t* o, uint32_t up, int zero) {
#pragma unroll
    for (int t = 0; t < 12; t++) {
        uint32_t v[4];
#pragma unroll
        for (int e = 0; e < 4; e++) {
            v[e] = acc[8 * (t >> 1) + (t & 1) + 2 * e];
            asm volatile("" : "+r"(v[e]));
            v[e] = bf2_mul(pack_bf16(h_lo(v[e]), h_hi(v[e])), up);
        }
        asm volatile("red.global.add.noftz.v4.bf16x2 [%0], {%1,%2,%3,%4};\n" ::"l"(o + (t >> 1) * 64 + (t & 1) * 4 * P2_XROW),
                     "r"(v[0]), "r"(v[1]), "r"(v[2]), "r"(v[3]) : "memory");
        if (t % 3 == 2) sched_break(zero);
    }
}

__global__ void __cluster_dims__(2, 1, 1) __launch_bounds__(512, 1)
pass2_kernel(const __grid_constant__ CUtensorMap wmap, const __nv_bfloat16* __restrict__ x, const __nv_bfloat16* __restrict__ w2,
             const __nv_bfloat16* __restrict__ grn_g, const __nv_bfloat16* __restrict__ grn_b, __nv_bfloat16* __restrict__ out, int zero) {
    extern __shared__ __align__(1024) uint8_t smem[];
    const uint32_t sbase = smem_u32(smem);
    const uint32_t bar_bfull = sbase + P2_OFF_BAR, bar_bempty = bar_bfull + P2_NB * 8;
    const uint32_t bar_afull = bar_bempty + P2_NB * 8, bar_aempty = bar_afull + 3 * P2_NA * 8;
    const uint32_t bar_xfull = bar_aempty + 3 * P2_NA * 8, bar_oready = bar_xfull + 8, s_pos = bar_xfull + 16;
    int tid;
    asm volatile("mov.u32 %0, %%tid.x;\n" : "=r"(tid));
    const int warp = __shfl_sync(0xffffffffu, tid >> 5, 0), lane = tid & 31;
    const uint32_t rank = cluster_rank();
    const int cl = blockIdx.x >> 1, pair = cl >> 1;
    const int k0 = (4 * pair + (cl & 1) * (48 - P2_POS % 48)) % 48;
    const int head = pair < P2_SHARED && !(cl & 1), tail = pair < P2_SHARED && (cl & 1);

    const bool small = blockIdx.x < NUM_CTAS - 8 * NGRP;
    uint32_t par, gg[4];
    auto early = [&]() {
        asm volatile("ld.global.cg.u32 %0, [%1];\n" : "=r"(par) : "l"(&g_epoch) : "memory");
#pragma unroll
        for (int i = 0; i < 4; i++) asm volatile("ld.global.nc.u16 %0, [%1];\n" : "=r"(gg[i]) : "l"(grn_g + tid + 384 * i) : "memory");
    };
    if (warp < 12) early();
    if (small && tid == 0) {
        for (int i = 0; i < 2 * P1_NST + 2; i++) mbar_init(sbase + P1_OFF_BAR + i * 8, (i & 12) == 4 ? 16 : 1);
        asm volatile("fence.mbarrier_init.release.cluster;\n" ::: "memory");
        p1_load_w1(sbase, &wmap, blockIdx.x * 2, 2);
    }
    if (small) TSTAMP(0, 0);
    TSTAMP(1, 0);
    if (tid == 384) {
        for (int i = 0; i < P2_NB; i++) {
            mbar_init(bar_bfull + i * 8, 1);
            mbar_init(bar_bempty + i * 8, 24);
        }
        mbar_init(bar_xfull, 1);
        mbar_init(bar_oready, 4);
        asm volatile("st.shared.u32 [%0], 0;\nfence.mbarrier_init.release.cluster;\nfence.acq_rel.cta;\n" ::"r"(s_pos) : "memory");
    }
    if (warp > 12 && lane == 0) {
        for (int i = 0; i < P2_NA; i++) {
            mbar_init(bar_afull + ((warp - 13) * P2_NA + i) * 8, 1);
            mbar_init(bar_aempty + ((warp - 13) * P2_NA + i) * 8, 4);
        }
        asm volatile("fence.mbarrier_init.release.cluster;\n" ::: "memory");
    }
    __syncwarp();
    asm volatile("barrier.cluster.arrive.relaxed.aligned;\n" ::: "memory");

    if (warp >= 12) {
        reg_dec<32>();
        if (small) par = 0;
        else asm volatile("ld.acquire.gpu.global.u32 %0, [%1];\n" : "=r"(par) : "l"(&g_img[(warp & 1) * 2]) : "memory");
        asm volatile("barrier.cluster.wait.aligned;\n" ::: "memory");
        if (small) {
#pragma unroll 1
            for (int j = 0; warp == 12 && j < 2 * NSMALL; j++) {
                const uint32_t bar = sbase + P1_OFF_BAR + (j & 3) * 8;
                if (!(j & 1)) {
                    flag_wait<true>(&g_flag[LN_RING + 3 + (j >> 1)][0][0], 8);
                    asm volatile("fence.proxy.async.global;\n" ::: "memory");
                }
                mbar_wait(bar + P1_NST * 8, (j >> 2) & 1);
                if (elect_one()) {
                    mbar_expect_tx(bar, P1_SLOT);
                    bulk_g2s_mc(sbase + (j & 3) * P1_SLOT + rank * (P1_SLOT / 2),
                                reinterpret_cast<const uint8_t*>(g_ln) + (size_t)(2 * (LN_RING + 3) + j) * P1_SLOT + rank * (P1_SLOT / 2), P1_SLOT / 2, bar, (uint16_t)3);
                }
                __syncwarp();
            }
            asm volatile("barrier.cluster.arrive.aligned;\nbarrier.cluster.wait.aligned;\n" ::: "memory");
        }
        if (warp == 12) {
            const uint8_t* wsrc = reinterpret_cast<const uint8_t*>(g_w2img) + rank * (P2_B / 2);
            int st = 0, ph = 1, kb = k0, m = 0, r = 0;
            const int busy = head ? 0 : tail ? P2_POS - 24 : P2_POS;
#pragma unroll 1
            for (int p = 0; p < P2_POS; p++) {
                if (p == 0 || p == P2_FOLD) {
                    if (p || par < 48) flag_wait<true>(&g_img[p != 0], p ? 96 * 4 : 48);
                    asm volatile("fence.proxy.async.global;\n" ::: "memory");
                    if (p) wsrc += sizeof(g_w2img[0]);
                }
                mbar_wait(bar_bempty + st * 8, ph);
                TR2P(p, 0);
                if (elect_one()) {
                    mbar_expect_tx(bar_bfull + st * 8, P2_B);
                    bulk_g2s_mc(sbase + st * P2_B + rank * (P2_B / 2), wsrc + kb * P2_B, P2_B / 2, bar_bfull + st * 8, (uint16_t)3);
                    asm volatile("st.volatile.shared.u32 [%0], %1;\n" ::"r"(s_pos), "r"(p) : "memory");
                    const int idle = 2 - min(m, P2_ITEMS - 1) + max(m - 2 + (r >= 48 - 2 * P2_LAG), 0) - ((unsigned)(p - busy) < 24);
                    if (idle) asm volatile("mbarrier.arrive.shared::cta.b64 _, [%0], %1;\n" ::"r"(bar_bempty + st * 8), "r"(idle * 8) : "memory");
                }
                __syncwarp();
                if (++st == P2_NB) { st = 0; ph ^= 1; }
                if (++kb == 48) kb = 0;
                if (++r == P2_LAG) { r = 0; m++; }
            }
            mbar_wait(bar_bempty + st * 8, ph);
            if (lane == 0) mbar_arrive(bar_bfull + st * 8);
#pragma unroll 1
            for (int p = 1; p < P2_NB; p++) {
                if (++st == P2_NB) { st = 0; ph ^= 1; }
                mbar_wait(bar_bempty + st * 8, ph);
            }
        } else if (warp == 13) {
            const uint8_t* src[3];
            int n[3], left[3], wrap[3];
            uint32_t st[3];
            auto item = [&](int w) {
                const int u = (k0 + p2_start(n[w])) % 48;
                left[w] = n[w] < 0 || n[w] == P2_ITEMS ? 24 : 48;
                wrap[w] = left[w] - (48 - u);
                src[w] = reinterpret_cast<const uint8_t*>(g_h) + (size_t)p2_tile(cl, n[w]) * (2 * H_TILE) + rank * H_HALF + u * H_STEP;
            };
#pragma unroll
            for (int w = 0; w < 3; w++) {
                n[w] = w == 2 && head ? -1 : w;
                st[w] = 0x80000000u;
                item(w);
            }
            if (par < (NUM_CTAS - 8 * NGRP) * 12) flag_wait<true>(&g_img[2], (NUM_CTAS - 8 * NGRP) * 12);
            bar_arrive(3, 416);
            gdc_wait();
            asm volatile("fence.proxy.async.global;\n" ::: "memory");
#pragma unroll 1
            for (int fin = 0; fin < 3;) {
                bool idle = true;
#pragma unroll
                for (int w = 0; w < 3; w++) {
                    const uint32_t o = (st[w] & 0xff) + w * P2_NA * 8;
                    if (left[w] >= 0 && mbar_test(bar_aempty + o, st[w] >> 31)) {
                        idle = false;
                        if (left[w] == 0) {
                            if (lane == 0) mbar_arrive(bar_afull + o);
                            left[w] = -1;
                            fin++;
                        } else {
                            if (elect_one()) {
                                mbar_expect_tx(bar_afull + o, P2_A);
                                bulk_g2s(sbase + P2_OFF_A + o * (P2_A / 8), src[w], P2_A, bar_afull + o);
                            }
                            __syncwarp();
                            src[w] += H_STEP;
                            st[w] += 8;
                            if ((st[w] & 0xff) == P2_NA * 8) st[w] ^= 0x80000000u | (P2_NA * 8);
                            if (--left[w] == wrap[w]) src[w] -= 48 * H_STEP;
                            if (left[w] == 0 && (n[w] += 3) < P2_ITEMS + tail) item(w);
                        }
                    }
                }
                if (idle) __nanosleep(64);
                SAFE_BREAK
            }
        } else if (warp == 14) {
            const uint32_t sx = sbase + P2_OFF_X;
            size_t o = 0;
            auto pace = [&](int target) {
                int v;
                while (true) {
                    asm volatile("ld.volatile.shared.u32 %0, [%1];\n" : "=r"(v) : "r"(s_pos) : "memory");
                    if (v * 16 >= target) break;
                    __nanosleep(100);
                    SAFE_BREAK
                }
            };
#pragma unroll 1
            for (int n = -head; n <= P2_ITEMS; n++) {
                const size_t on = (size_t)(2 * p2_tile(cl, n) + rank) * (64 * C_DIM * 2);
                const bool st = n + head > 0, ld = n < P2_ITEMS;
                if (st) mbar_wait(bar_oready, (n - 1 + head) & 1);
                TR2P(n + 1, 1);
                if (lane == 0) {
                    if (n == 1 && head) {
                        asm volatile("cp.async.bulk.wait_group 0;\nfence.proxy.async.global;\n" ::: "memory");
                        asm volatile("st.release.gpu.global.u32 [%0], 1;\n" ::"l"(&g_half[pair][rank]) : "memory");
                    }
                    if (ld) mbar_expect_tx(bar_xfull, 64 * C_DIM * 2);
                    const bool paced = st && n < P2_ITEMS - 1;
                    int t = (P2_LAG * (n - 1) + 52) * 16;
#pragma unroll 1
                    for (int c = 0; st && c < 64 * P2_XROW; c += P2_XC) {
                        if (paced) pace(t += 11);
                        bulk_s2g(reinterpret_cast<uint8_t*>(out) + o + c, sx + c + (c >= 32 * P2_XROW ? 64 : 0), P2_XC);
                        asm volatile("cp.async.bulk.commit_group;\n" ::: "memory");
                    }
#pragma unroll 1
                    for (int c = 0; ld && c < 64 * P2_XROW; c += P2_XC) {
                        if (c == 0) asm volatile("cp.async.bulk.wait_group.read 4;\n" ::: "memory");
                        if (c == 32 * P2_XROW) asm volatile("cp.async.bulk.wait_group.read 0;\n" ::: "memory");
                        if (paced) pace(t += 11);
                        bulk_g2s(sx + c + (c >= 32 * P2_XROW ? 64 : 0), reinterpret_cast<const uint8_t*>(x) + on + c, P2_XC, bar_xfull);
                    }
                    TR2P(n + 1, 2);
                    TR2P(n + 1, 3);
                }
                __syncwarp();
                o = on;
            }
            asm volatile("cp.async.bulk.wait_group 0;\n" ::: "memory");
            TR2P(30, 1);
        }
    } else {
        reg_inc<160>();
        asm volatile("barrier.cluster.wait.aligned;\n" ::: "memory");
        if (small) {
            if (warp < 8) p1_compute<2, 2>(sbase, blockIdx.x * 2, warp, lane, zero);
            else p1_w2(w2, grn_b, warp & 3, lane);
            asm volatile("barrier.cluster.arrive.aligned;\nbarrier.cluster.wait.aligned;\n" ::: "memory");
            TSTAMP(0, 30);
            early();
        }
        const int wg = warp >> 2, w = warp & 3, g = lane >> 2, q = lane & 3;
        const uint32_t sx = sbase + P2_OFF_X + (g & 1) * P2_XHALF + (w * 8 + (g >> 1)) * P2_XROW + q * 16;
        const uint32_t af = bar_afull + wg * P2_NA * 8;
        const uint32_t s_a = sbase + P2_OFF_A + wg * P2_NA * P2_A + (lane >> 3) * 512 + (lane & 7) * 64 +
                             ((w ^ ((lane & 7) >> 1)) << 4);
        uint32_t acc0[48], acc1[48];
        uint32_t up;
        uint4 a0[2], a1[2];
        uint32_t st = 0, ph = 0;

        {
            float4* s_red = reinterpret_cast<float4*>(smem + P2_OFF_RED);
            const float* sums = g_sums[par & 1];
            float gx[4], part = 0.f, mx = 0.f;
            asm volatile("prefetch.global.L2 [%0];\n" ::"l"(sums + HID + tid * 2) : "memory");
            TSTAMP(1, 27);
            bar_sync(3, 416);
            gdc_wait();
            TSTAMP(1, 1);
#pragma unroll
            for (int i = 0; i < 4; i++) gx[i] = __ldcg(sums + tid + 384 * i);
            const float bias = __ldcg(sums + HID + tid), asum = __ldcg(sums + HID + C_DIM + tid);
            float z = __uint_as_float(__reduce_max_sync(0xffffffffu, __float_as_uint(asum)));
            uint32_t bm = __reduce_max_sync(0xffffffffu, __float_as_uint(fabsf(bias)));
#pragma unroll
            for (int i = 0; i < 4; i++) {
                asm("sqrt.approx.f32 %0, %1;\n" : "=f"(gx[i]) : "f"(fmaf(gx[i], HSCALE * HSCALE, 1e-6f)));
                part += gx[i];
                gx[i] *= bf_lo(gg[i]);
                mx = fmaxf(mx, fabsf(gx[i]));
            }
#pragma unroll
            for (int o = 16; o > 0; o >>= 1) part += __shfl_xor_sync(0xffffffffu, part, o);
            mx = __uint_as_float(__reduce_max_sync(0xffffffffu, __float_as_uint(mx)));
            TSTAMP(1, 26);
            if (lane == 0) s_red[warp] = make_float4(part, mx, z, __uint_as_float(bm));
            bar_sync(1, 384);
            float tot = 0.f;
            {
                const float4 t = s_red[min(lane & 15, 11)];
                tot = (lane & 15) < 12 ? t.x : 0.f;
#pragma unroll
                for (int o = 8; o > 0; o >>= 1) tot += __shfl_xor_sync(0xffffffffu, tot, o);
                mx = __uint_as_float(__reduce_max_sync(0xffffffffu, __float_as_uint(t.y)));
                z = __uint_as_float(__reduce_max_sync(0xffffffffu, __float_as_uint(t.z)));
                bm = __reduce_max_sync(0xffffffffu, __float_as_uint(t.w));
            }
            const float inv = __fdividef(1.0f, fmaf(tot, 1.0f / HID, 1e-6f));
            const uint32_t e0 = acc_exp(z) - 9u;
            const uint32_t j = min(max(max(__float_as_uint(fmaf(mx, inv, 1.0f) * 1.01f) >> 23, 130u) - 130u, max(bm >> 23, e0 + 12u) - (e0 + 12u)), 126u);
            const float dn = __uint_as_float((127u - j) << 23) * (HSCALE * 1.00235f);
#pragma unroll
            for (int i = 0; i < 4; i++)
                *reinterpret_cast<uint16_t*>(smem + P2_OFF_GRN + (tid + 384 * i) * 2) = pack_f16(fmaf(gx[i], inv, 1.0f) * dn, 0.f);
            const uint32_t e = min(e0 + j, 253u);
            up = e * 0x00800080u;
#pragma unroll
            for (int i = 0; i < 2; i++)
                *reinterpret_cast<uint16_t*>(smem + P2_OFF_BIAS + (tid >> 1) * 8 + i * 4 + (tid & 1) * 2) = pack_f16(bias * __uint_as_float((254u - e) << 23), 0.f);
            TSTAMP(1, 25);
            bar_sync(1, 384);
            if (wg == 1 && blockIdx.x < 96) {
                const uint4* src = g_w2img[0] + blockIdx.x * 768 + tid - 128;
                const uint4 fk = *reinterpret_cast<const uint4*>(smem + P2_OFF_GRN + blockIdx.x * 32 + (tid & 8) * 2);
                uint4 v[6];
#pragma unroll
                for (int i = 0; i < 6; i++) v[i] = __ldcg(src + i * 128);
                auto fold = [&](uint32_t b, uint32_t f) { return (h2_mul(b, f) + 0x00040004u) & 0xfff8fff8u; };
#pragma unroll
                for (int i = 0; i < 6; i++)
                    g_w2img[1][blockIdx.x * 768 + tid - 128 + i * 128] = make_uint4(fold(v[i].x, fk.x), fold(v[i].y, fk.y), fold(v[i].z, fk.z), fold(v[i].w, fk.w));
                asm volatile("fence.proxy.async.global;\n" ::: "memory");
                __threadfence();
                __syncwarp();
                if (lane == 0) asm volatile("red.release.gpu.global.add.u32 [%0], 1;\n" ::"l"(&g_img[1]) : "memory");
            }
        }
        TSTAMP(1, 28);
        int kt = k0, pos;
        const uint32_t be = lane < 2 ? mapa(bar_bempty, lane) : 0, be0 = mapa(bar_bempty, 0);
        uint32_t prev = 0, sa = 0, pa = 0;
        auto release_b = [&](uint32_t p, bool on) {
            asm volatile("{\n.reg .pred p, q;\nsetp.ne.u32 q, %2, 0;\nsetp.ne.and.u32 p, %1, 0, q;\n@p mbarrier.arrive.shared::cluster.b64 _, [%0];\n}\n"
                         ::"r"(be + p), "r"(be), "r"((uint32_t)on) : "memory");
        };
        auto arrive1 = [&](uint32_t bar) {
            asm volatile("{\n.reg .pred p;\nsetp.eq.u32 p, %1, %2;\n@p mbarrier.arrive.shared::cta.b64 _, [%0];\n}\n" ::"r"(bar), "r"(be), "r"(be0) : "memory");
        };
        auto seek = [&](int p) {
            pos = p;
            st = p % P2_NB * 8;
            ph = p / P2_NB & 1;
            int v;
            while (true) {
                asm volatile("ld.volatile.shared.u32 %0, [%1];\n" : "=r"(v) : "r"(s_pos) : "memory");
                if (__all_sync(0xffffffffu, v >= p)) break;
                __nanosleep(200);
                SAFE_BREAK
            }
        };
        bool ok_a = false;
        auto fetch = [&](uint4 (&a)[2], uint32_t done, bool rel, bool early, bool wait = true) {
            if (!ok_a) mbar_wait(af + sa, pa);
            uint32_t o[6];
            const uint32_t src = s_a + sa * (P2_A / 8);
            asm volatile("ldmatrix.sync.aligned.m8n8.x4.trans.shared.b16 {%0,%1,%2,%3}, [%4];\n"
                         : "=r"(o[0]), "=r"(o[1]), "=r"(o[2]), "=r"(o[3]) : "r"(src) : "memory");
            asm volatile("ldmatrix.sync.aligned.m8n8.x2.trans.shared.b16 {%0,%1}, [%2];\n"
                         : "=r"(o[4]), "=r"(o[5]) : "r"(src + 2048) : "memory");
            if ((sa += 8) == P2_NA * 8) { sa = 0; pa ^= 1; }
            if (wait) wg_wait<1>();
            asm volatile("" ::"r"(a[0].x), "r"(a[0].y), "r"(a[0].z), "r"(a[0].w), "r"(a[1].x), "r"(a[1].y), "r"(a[1].z), "r"(a[1].w));
            release_b(done, rel);
            ok_a = mbar_test(af + sa, pa);
            const bool ok_b = mbar_test(bar_bfull + st, ph);
            p2_unpack(a[0], o[0], o[1], o[2]);
            p2_unpack(a[1], o[3], o[4], o[5]);
            if (early) {
                const uint32_t* t = reinterpret_cast<const uint32_t*>(smem + P2_OFF_GRN) + kt * 16 + q;
#pragma unroll
                for (int i = 0; i < 2; i++)
                    a[i] = make_uint4(h2_mul(a[i].x, t[8 * i]), h2_mul(a[i].y, t[8 * i]), h2_mul(a[i].z, t[8 * i + 4]), h2_mul(a[i].w, t[8 * i + 4]));
                if (++kt == 48) kt = 0;
            }
            if (!ok_b) mbar_wait(bar_bfull + st, ph);
        };
        const uint64_t db0 = make_desc(sbase, 128, 256);
        auto step = [&](const uint4 (&a)[2], uint4 (&an)[2], bool cont, bool add, bool early) {
            TR2(0);
            const uint64_t db = db0 + st * (P2_B / 128);
            wg_fence();
            mma_rs_n192(acc0, a[0], db, add);
            mma_rs_n192(acc1, a[0], db + 384, add);
            mma_rs_n192(acc0, a[1], db + 768, 1);
            mma_rs_n192(acc1, a[1], db + 768 + 384, 1);
            wg_commit();
            arrive1(af + 3 * P2_NA * 8 - 8 + (sa ? sa : P2_NA * 8));
            const uint32_t done = prev;
            prev = st;
            if ((st += 8) == P2_NB * 8) { st = 0; ph ^= 1; }
            fetch(an, done, cont, early);
            pos++;
        };
        int n = wg == 2 && head ? -1 : wg;
#pragma unroll
        for (int c = 0; c < 12; c++) p2_init(c < 6 ? acc0 : acc1, c, sbase + P2_OFF_BIAS + q * 32);
        a0[0] = a0[1] = a1[0] = a1[1] = make_uint4(zero, zero, zero, zero);
        seek(p2_start(n));
        fetch(a0, 0, false, n <= 0, false);
#pragma unroll 1
        for (;; n += 3) {
            TSTAMP(1, 2 + n);
            const int p0 = n < 0 || n == P2_ITEMS ? 12 : 0, pe = n <= 0 ? p0 + P2_FOLD / 2 : 0;
            const bool more = n + 3 < P2_ITEMS + tail;
#pragma unroll 1
            for (int p = p0; p < 24; p++) {
                step(a0, a1, p != p0, p != p0 || n != P2_ITEMS, p < pe);
                step(a1, a0, true, true, p < pe);
            }
            if (n == P2_ITEMS) {
                flag_wait<true>(&g_half[pair][rank], 1);
                TR2(1);
                wg_wait<0>();
                TR2(2);
                release_b(prev, true);
                uint8_t* o = reinterpret_cast<uint8_t*>(out) + (size_t)((2 * p2_tile(cl, -1) + rank) * 64 + (g & 1) * 32 + w * 8 + (g >> 1)) * P2_XROW + q * 16;
                p2_epilogue_add(acc0, o, up, zero);
                p2_epilogue_add(acc1, o + 384, up, zero);
                TR2(3);
                break;
            }
            mbar_wait(bar_xfull, (n + head) & 1);
            TR2(1);
            wg_wait<0>();
            TR2(2);
            release_b(prev, true);
            p2_epilogue(acc0, acc1, sx, sbase + P2_OFF_BIAS + q * 32, up, zero);
            TR2(3);
            asm volatile("fence.proxy.async.shared::cta;\n" ::: "memory");
            __syncwarp();
            arrive1(bar_oready);
            if (!more) break;
            ok_a = false;
            seek(p2_start(n + 3));
            mbar_wait(bar_bfull + st, ph);
        }
        if (blockIdx.x == 120 && threadIdx.x < (LN_RING + 3 + NSMALL) * 2) (&g_flag[0][0][0])[threadIdx.x * 8] = 0;
        if (blockIdx.x == 121 && threadIdx.x == 0) atomicAdd(&g_epoch, 1u);
        TSTAMP(1, 30);
    }
}

}

extern "C" void kernel_launch(void* const* d_in, const int* in_sizes, int n_in, void* d_out, int out_size) {
    const __nv_bfloat16* x = (const __nv_bfloat16*)d_in[0];
    const __nv_bfloat16* dw = (const __nv_bfloat16*)d_in[1];
    const __nv_bfloat16* w1 = (const __nv_bfloat16*)d_in[2];
    const __nv_bfloat16* w2 = (const __nv_bfloat16*)d_in[3];
    const __nv_bfloat16* grn_g = (const __nv_bfloat16*)d_in[4];
    const __nv_bfloat16* grn_b = (const __nv_bfloat16*)d_in[5];
    __nv_bfloat16* out = (__nv_bfloat16*)d_out;

    cudaFuncSetAttribute(pass1_kernel<2>, cudaFuncAttributeMaxDynamicSharedMemorySize, P1_SMEM);
    cudaFuncSetAttribute(pass1_kernel<8>, cudaFuncAttributeMaxDynamicSharedMemorySize, P1_SMEM);
    cudaFuncSetAttribute(pass2_kernel, cudaFuncAttributeMaxDynamicSharedMemorySize, P2_SMEM);

    typedef CUresult (*EncodeFn)(CUtensorMap*, CUtensorMapDataType, cuuint32_t, void*, const cuuint64_t*, const cuuint64_t*,
                                 const cuuint32_t*, const cuuint32_t*, CUtensorMapInterleave, CUtensorMapSwizzle,
                                 CUtensorMapL2promotion, CUtensorMapFloatOOBfill);
    static EncodeFn encode = nullptr;
    if (!encode) {
        cudaDriverEntryPointQueryResult qres;
        cudaGetDriverEntryPoint("cuTensorMapEncodeTiled", (void**)&encode, cudaEnableDefault, &qres);
    }
    CUtensorMap wmap;
    const cuuint64_t gdim[2] = {HID, C_DIM};
    const cuuint64_t gstr[1] = {HID * 2};
    const cuuint32_t box[2] = {64, 192}, estr[2] = {1, 1};
    CUresult er = encode(&wmap, CU_TENSOR_MAP_DATA_TYPE_BFLOAT16, 2, (void*)w1, gdim, gstr, box, estr, CU_TENSOR_MAP_INTERLEAVE_NONE,
           CU_TENSOR_MAP_SWIZZLE_128B, CU_TENSOR_MAP_L2_PROMOTION_L2_128B, CU_TENSOR_MAP_FLOAT_OOB_FILL_NONE);
    if (er != CUDA_SUCCESS) printf("tensor map encode failed %d\n", (int)er);

    cudaLaunchAttribute attr[1];
    attr[0].id = cudaLaunchAttributeProgrammaticStreamSerialization;
    attr[0].val.programmaticStreamSerializationAllowed = 1;
    cudaLaunchConfig_t cfg = {};
    cfg.stream = 0;
    cfg.blockDim = dim3(512);
    cfg.dynamicSmemBytes = P1_SMEM;
    static int wide = -1;
    if (wide < 0) {
        int n = 0;
        cfg.gridDim = dim3(8 * NGRP);
        wide = cudaOccupancyMaxActiveClusters(&n, pass1_kernel<8>, &cfg) == cudaSuccess && n >= NGRP;
    }
    if (wide) pass1_kernel<8><<<8 * NGRP, 512, P1_SMEM>>>(wmap, x, dw, w1, 0);
    else pass1_kernel<2><<<8 * NGRP, 512, P1_SMEM>>>(wmap, x, dw, w1, 0);
    cfg.attrs = attr;
    cfg.numAttrs = 1;
    cfg.gridDim = dim3(NUM_CTAS);
    cfg.dynamicSmemBytes = P2_SMEM;
    cudaLaunchKernelEx(&cfg, pass2_kernel, wmap, x, w2, grn_g, grn_b, out, 0);
}
```

```cpp
#include <cuda.h>
#include <cuda_runtime.h>
#include <cuda_bf16.h>
#include <stdint.h>
#include <stdio.h>

namespace {

constexpr int M_TOTAL = 384 * 384;
constexpr int C_DIM   = 384;
constexpr int HID     = 1536;
constexpr int NT128   = M_TOTAL / 128;
constexpr int NUM_CTAS = 132;

constexpr int NGRP = 15, NSMALL = 100;
constexpr int LN_STEP = 2 * NGRP, LN_RING = 2 * LN_STEP;
__device__ __forceinline__ int p1_tile(int t) { return t < LN_STEP ? t : t + min((t - LN_STEP) / 10 + 1, NSMALL); }
__device__ __forceinline__ int p1_place(int tile, int slot) {
    const int i = (tile + 3) / 11;
    return i * 11 == tile + 3 && (unsigned)(i - 3) < NSMALL ? LN_RING + i : slot;
}
constexpr int LN_TILE = 128 * C_DIM * 2;
constexpr int H_TILE = 64 * HID * 3 / 2;
constexpr int H_HALF = 3072, H_STEP = 6144;

__device__ __align__(1024) uint4 g_h[(size_t)M_TOTAL * HID * 3 / 32];
__device__ __align__(1024) uint4 g_ln[(LN_RING + 3 + NSMALL) * LN_TILE / 16];
__device__ __align__(1024) uint4 g_w2img[2][HID * C_DIM * 2 / 16];
__device__ __align__(16) float g_sums[2][HID + 2 * C_DIM];
__device__ __align__(16) unsigned g_ex[HID];
__device__ unsigned g_epoch;
__device__ __align__(128) unsigned g_img[3];
__device__ __align__(128) unsigned g_half[32][2];
__device__ unsigned g_flag[LN_RING + 3 + NSMALL][2][8];
#define TSTAMP(k, i)
#define STAMPT(t, i)
#define TRACE(wg, pos, i)
#define TRACEW(pos, i)

#define TR2(i)
#define TR2P(pos, i)
__host__ __device__ __forceinline__ int perm32(int n) {
    return (n & ~31) | (((n >> 1) & 3) << 3) | (((n >> 3) & 3) << 1) | (n & 1);
}

__device__ __forceinline__ uint32_t smem_u32(const void* p) { return (uint32_t)__cvta_generic_to_shared(p); }

__device__ __forceinline__ void mbar_init(uint32_t bar, uint32_t count) {
    asm volatile("mbarrier.init.shared::cta.b64 [%0], %1;\n" ::"r"(bar), "r"(count) : "memory");
}
__device__ __forceinline__ void mbar_expect_tx(uint32_t bar, uint32_t bytes) {
    asm volatile("mbarrier.arrive.expect_tx.shared::cta.b64 _, [%0], %1;\n" ::"r"(bar), "r"(bytes) : "memory");
}
__device__ __forceinline__ void mbar_arrive(uint32_t bar) {
    asm volatile("mbarrier.arrive.shared::cta.b64 _, [%0];\n" ::"r"(bar) : "memory");
}
__device__ __forceinline__ void mbar_arrive_cluster(uint32_t bar_cluster_addr) {
    asm volatile("mbarrier.arrive.shared::cluster.b64 _, [%0];\n" ::"r"(bar_cluster_addr) : "memory");
}
#define SAFE_BREAK
__device__ __forceinline__ void mbar_wait(uint32_t bar, uint32_t parity) {
    asm volatile(
        "{\n"
        ".reg .pred p;\n"
        "LAB_WAIT:\n"
        "mbarrier.try_wait.parity.shared::cta.b64 p, [%0], %1;\n"
        "@!p bra LAB_WAIT;\n"
        "}\n" ::"r"(bar), "r"(parity) : "memory");
}
__device__ __forceinline__ bool mbar_test(uint32_t bar, uint32_t parity) {
    uint32_t ok;
    asm volatile("{\n.reg .pred p;\n"
                 "mbarrier.test_wait.parity.shared::cta.b64 p, [%1], %2;\n"
                 "selp.u32 %0, 1, 0, p;\n}\n" : "=r"(ok) : "r"(bar), "r"(parity) : "memory");
    return ok != 0;
}
__device__ __forceinline__ uint32_t mapa(uint32_t addr, uint32_t rank) {
    uint32_t r;
    asm volatile("mapa.shared::cluster.u32 %0, %1, %2;\n" : "=r"(r) : "r"(addr), "r"(rank));
    return r;
}
__device__ __forceinline__ void bulk_g2s(uint32_t dst, const void* src, uint32_t bytes, uint32_t bar) {
    asm volatile("cp.async.bulk.shared::cluster.global.mbarrier::complete_tx::bytes [%0], [%1], %2, [%3];\n"
                 ::"r"(dst), "l"(src), "r"(bytes), "r"(bar) : "memory");
}
__device__ __forceinline__ void bulk_g2s_mc(uint32_t dst, const void* src, uint32_t bytes, uint32_t bar, uint16_t mask) {
    asm volatile("cp.async.bulk.shared::cluster.global.mbarrier::complete_tx::bytes.multicast::cluster [%0], [%1], %2, [%3], %4;\n"
                 ::"r"(dst), "l"(src), "r"(bytes), "r"(bar), "h"(mask) : "memory");
}
__device__ __forceinline__ void tma2(uint32_t dst, const CUtensorMap* map, int c0, int c1, uint32_t bar) {
    asm volatile("cp.async.bulk.tensor.2d.shared::cluster.global.tile.mbarrier::complete_tx::bytes [%0], [%1, {%2, %3}], [%4];\n"
                 ::"r"(dst), "l"(map), "r"(c0), "r"(c1), "r"(bar) : "memory");
}
template <bool ACQ>
__device__ __forceinline__ uint32_t flag_wait(const unsigned* p, unsigned target) {
    unsigned v, n = 0;
    do {
        if (ACQ) asm volatile("ld.acquire.gpu.global.u32 %0, [%1];\n" : "=r"(v) : "l"(p) : "memory");
        else asm volatile("ld.relaxed.gpu.global.u32 %0, [%1];\n" : "=r"(v) : "l"(p) : "memory");
        n++;
    } while (v < target);
    return n == 1;
}
__device__ __forceinline__ void ldsm4t(uint32_t (&r)[4], uint32_t addr) {
    asm volatile("ldmatrix.sync.aligned.m8n8.x4.trans.shared.b16 {%0,%1,%2,%3}, [%4];\n"
                 : "=r"(r[0]), "=r"(r[1]), "=r"(r[2]), "=r"(r[3]) : "r"(addr) : "memory");
}
__device__ __forceinline__ void bulk_s2g(void* dst, uint32_t src, uint32_t bytes) {
    asm volatile("cp.async.bulk.global.shared::cta.bulk_group [%0], [%1], %2;\n" ::"l"(dst), "r"(src), "r"(bytes) : "memory");
}
__device__ __forceinline__ void gdc_wait() { asm volatile("griddepcontrol.wait;\n" ::: "memory"); }
__device__ __forceinline__ void gdc_launch() { asm volatile("griddepcontrol.launch_dependents;\n" ::: "memory"); }
__device__ __forceinline__ uint32_t cluster_rank() {
    uint32_t r;
    asm volatile("mov.u32 %0, %%cluster_ctarank;\n" : "=r"(r));
    return r;
}
__device__ __forceinline__ bool elect_one() {
    uint32_t pred;
    asm volatile("{\n.reg .pred p;\nelect.sync _|p, 0xffffffff;\nselp.u32 %0, 1, 0, p;\n}\n" : "=r"(pred));
    return pred != 0;
}
__device__ __forceinline__ void wg_fence() { asm volatile("wgmma.fence.sync.aligned;\n" ::: "memory"); }
__device__ __forceinline__ void wg_commit() { asm volatile("wgmma.commit_group.sync.aligned;\n" ::: "memory"); }
template <int N> __device__ __forceinline__ void wg_wait() {
    asm volatile("wgmma.wait_group.sync.aligned %0;\n" ::"n"(N) : "memory");
}
template <int R> __device__ __forceinline__ void reg_inc() { asm volatile("setmaxnreg.inc.sync.aligned.u32 %0;\n" ::"n"(R)); }
template <int R> __device__ __forceinline__ void reg_dec() { asm volatile("setmaxnreg.dec.sync.aligned.u32 %0;\n" ::"n"(R)); }
__device__ __forceinline__ void bar_sync(int id, int n) { asm volatile("bar.sync %0, %1;\n" ::"r"(id), "r"(n) : "memory"); }
__device__ __forceinline__ void bar_arrive(int id, int n) { asm volatile("bar.arrive %0, %1;\n" ::"r"(id), "r"(n) : "memory"); }

__device__ __forceinline__ uint64_t make_desc(uint32_t saddr, uint32_t lbo, uint32_t sbo) {
    return (uint64_t)((saddr & 0x3FFFF) >> 4) | ((uint64_t)(lbo >> 4) << 16) | ((uint64_t)(sbo >> 4) << 32);
}

__device__ __forceinline__ void stg128_cs(void* p, uint32_t a, uint32_t b, uint32_t c, uint32_t d) {
    asm volatile("st.global.cs.v4.u32 [%0], {%1,%2,%3,%4};\n" ::"l"(p), "r"(a), "r"(b), "r"(c), "r"(d) : "memory");
}
__device__ __forceinline__ uint32_t pack_bf16(float lo, float hi) {
    uint32_t r;
    asm("cvt.rn.bf16x2.f32 %0, %1, %2;\n" : "=r"(r) : "f"(hi), "f"(lo));
    return r;
}
__device__ __forceinline__ float bf_lo(uint32_t v) { return __uint_as_float(v << 16); }
__device__ __forceinline__ float bf_hi(uint32_t v) { return __uint_as_float(v & 0xffff0000u); }
__device__ __forceinline__ uint32_t bf2_mul(uint32_t a, uint32_t b) {
    uint32_t r;
    asm("mul.rn.bf16x2 %0, %1, %2;\n" : "=r"(r) : "r"(a), "r"(b));
    return r;
}
__device__ __forceinline__ uint32_t bf2_fma(uint32_t a, uint32_t b, uint32_t c) {
    uint32_t r;
    asm("fma.rn.bf16x2 %0, %1, %2, %3;\n" : "=r"(r) : "r"(a), "r"(b), "r"(c));
    return r;
}
__device__ __forceinline__ uint32_t bf2_add(uint32_t a, uint32_t b) {
    uint32_t r;
    asm("add.rn.bf16x2 %0, %1, %2;\n" : "=r"(r) : "r"(a), "r"(b));
    return r;
}
constexpr float KAPPA = 0.3292034911525734f;
constexpr float GELU_C = 2.423681954311584f;
constexpr float HSCALE = 1.0f / (2.0f * KAPPA);
__device__ __forceinline__ uint32_t acc_exp(float z) { return max(__float_as_uint(z) >> 23, 10u); }
__device__ __forceinline__ void sched_break(int zero) {
    asm volatile("{\n.reg .pred p;\nsetp.ne.s32 p, %0, 0;\nSB_LOOP:\n@p nanosleep.u32 1;\n@p bra SB_LOOP;\n}\n" ::"r"(zero));
}

#define ACCR8(d, o) "+r"(d[o + 0]), "+r"(d[o + 1]), "+r"(d[o + 2]), "+r"(d[o + 3]), "+r"(d[o + 4]), "+r"(d[o + 5]), "+r"(d[o + 6]), "+r"(d[o + 7])
__device__ __forceinline__ void mma_rs_n128(uint32_t (&d)[32], const uint32_t (&a)[4], uint64_t desc, int scale_d) {
    asm volatile(
        "{\n.reg .pred p;\nsetp.ne.b32 p, %37, 0;\n"
        "wgmma.mma_async.sync.aligned.m64n128k16.f16.f16.f16 "
        "{%0,%1,%2,%3,%4,%5,%6,%7,%8,%9,%10,%11,%12,%13,%14,%15,"
        "%16,%17,%18,%19,%20,%21,%22,%23,%24,%25,%26,%27,%28,%29,%30,%31},"
        "{%32,%33,%34,%35}, %36, p, 1, 1, 0;\n}\n"
        : ACCR8(d, 0), ACCR8(d, 8), ACCR8(d, 16), ACCR8(d, 24)
        : "r"(a[0]), "r"(a[1]), "r"(a[2]), "r"(a[3]), "l"(desc), "r"(scale_d));
}
__device__ __forceinline__ void mma_ss_n128(uint32_t (&d)[32], uint64_t da, uint64_t db) {
    asm volatile(
        "{\n.reg .pred p;\nsetp.ne.b32 p, %34, 0;\n"
        "wgmma.mma_async.sync.aligned.m64n128k16.f16.f16.f16 "
        "{%0,%1,%2,%3,%4,%5,%6,%7,%8,%9,%10,%11,%12,%13,%14,%15,"
        "%16,%17,%18,%19,%20,%21,%22,%23,%24,%25,%26,%27,%28,%29,%30,%31},"
        "%32, %33, p, 1, 1, 0, 0;\n}\n"
        : ACCR8(d, 0), ACCR8(d, 8), ACCR8(d, 16), ACCR8(d, 24)
        : "l"(da), "l"(db), "r"(1));
}
__device__ __forceinline__ uint32_t bf2_as_h2(uint32_t v) { return (v & 0x0fff0fffu) * 7u + v; }
__device__ __forceinline__ float h_lo(uint32_t v) {
    float r;
    asm("{\n.reg .b16 l, h;\nmov.b32 {l, h}, %1;\ncvt.f32.f16 %0, l;\n}\n" : "=f"(r) : "r"(v));
    return r;
}
__device__ __forceinline__ float h_hi(uint32_t v) {
    float r;
    asm("{\n.reg .b16 l, h;\nmov.b32 {l, h}, %1;\ncvt.f32.f16 %0, h;\n}\n" : "=f"(r) : "r"(v));
    return r;
}

__device__ __forceinline__ void mma_rs_n192(uint32_t (&d)[48], const uint4& a, uint64_t db, int scale_d) {
    asm volatile(
        "{\n.reg .pred p;\nsetp.ne.b32 p, %53, 0;\n"
        "wgmma.mma_async.sync.aligned.m64n192k16.f16.f16.f16 "
        "{%0,%1,%2,%3,%4,%5,%6,%7,%8,%9,%10,%11,%12,%13,%14,%15,"
        "%16,%17,%18,%19,%20,%21,%22,%23,%24,%25,%26,%27,%28,%29,%30,%31,"
        "%32,%33,%34,%35,%36,%37,%38,%39,%40,%41,%42,%43,%44,%45,%46,%47},"
        "{%48,%49,%50,%51}, %52, p, 1, 1, 0;\n}\n"
        : ACCR8(d, 0), ACCR8(d, 8), ACCR8(d, 16), ACCR8(d, 24), ACCR8(d, 32), ACCR8(d, 40)
        : "r"(a.x), "r"(a.y), "r"(a.z), "r"(a.w), "l"(db), "r"(scale_d));
}

__device__ __forceinline__ uint32_t pack_f16(float lo, float hi) {
    uint32_t r;
    asm("cvt.rn.f16x2.f32 %0, %1, %2;\n" : "=r"(r) : "f"(hi), "f"(lo));
    return r;
}

constexpr int P1_IMG = 900;
constexpr int P1_SLOT = LN_TILE / 2, P1_NST = 4;
constexpr int P1_X = 16 * C_DIM * 2;
constexpr int P1_OFF_A = P1_SLOT * P1_NST;
constexpr int P1_OFF_DW = P1_OFF_A + 3 * 2048;
constexpr int P1_OFF_X = P1_OFF_DW + C_DIM * 2;
constexpr int P1_OFF_BAR = P1_OFF_X + 2 * P1_X;
constexpr int P1_OFF_TILE = P1_OFF_BAR + (2 * P1_NST + 3 + 2 + 3 + 2) * 8;
constexpr int P1_SMEM = P1_OFF_TILE + 64;

__device__ __forceinline__ float rsqrt_fast(float x) {
    float r;
    asm("rsqrt.approx.ftz.f32 %0, %1;\n" : "=f"(r) : "f"(x));
    return r;
}
__device__ __forceinline__ float sum8(const uint32_t (&c)[4]) {
    const uint32_t u = bf2_add(bf2_add(c[0], c[1]), bf2_add(c[2], c[3]));
    return bf_lo(u) + bf_hi(u);
}
__device__ __forceinline__ void lds128(uint32_t (&v)[4], uint32_t a) {
    asm volatile("ld.shared.v4.u32 {%0,%1,%2,%3}, [%4];\n" : "=r"(v[0]), "=r"(v[1]), "=r"(v[2]), "=r"(v[3]) : "r"(a) : "memory");
}
template <class F>
__device__ __forceinline__ void ln_row(uint32_t (&v)[6][4], uint32_t sdw, F after_loads) {
    uint32_t c[4], s[4], d[4], nm;
    float np;
#pragma unroll
    for (int i = 0; i < 6; i++) {
        lds128(d, sdw + i * 128);
        if (i == 0) {
#pragma unroll
            for (int k = 0; k < 4; k++) c[k] = bf2_mul(v[0][k], d[k]);
            const float p = sum8(c) * -0.125f;
            nm = pack_bf16(p, p);
            np = bf_lo(nm) - bf_lo(__shfl_sync(0xffffffffu, nm, 0, 8));
        }
#pragma unroll
        for (int k = 0; k < 4; k++) {
            v[i][k] = bf2_fma(v[i][k], d[k], nm);
            s[k] = i ? bf2_add(v[i][k], s[k]) : v[i][k];
            c[k] = i ? bf2_fma(v[i][k], v[i][k], c[k]) : bf2_mul(v[i][k], v[i][k]);
        }
    }
    after_loads(c[0]);
    float m = fmaf(sum8(s), 1.0f / 48, -np);
    float q = fmaf(-np, fmaf(2.f, m, np), sum8(c) * (1.0f / 48));
#pragma unroll
    for (int o = 1; o < 8; o <<= 1) {
        m += __shfl_xor_sync(0xffffffffu, m, o);
        q += __shfl_xor_sync(0xffffffffu, q, o);
    }
    m *= 0.125f;
    const float r = KAPPA * rsqrt_fast(fmaxf(fmaf(-m, m, q * 0.125f), 0.f) + 1e-5f);
    const float e = (-np - m) * r * 0x1p-112f;
    const bool two = __any_sync(0xffffffffu, r < 0x1p-14f);
    const float r1 = r * (two ? 0x1p-56f : 0x1p-112f);
    uint32_t mul = pack_bf16(r1, r1), add = two ? 0u : pack_bf16(e, e);
#pragma unroll 1
    for (int it = !two; it < 2; it++) {
#pragma unroll
        for (int i = 0; i < 6; i++)
#pragma unroll
            for (int k = 0; k < 4; k++) v[i][k] = bf2_fma(v[i][k], mul, add);
        mul = 0x23802380u;
        add = pack_bf16(e, e);
    }
#pragma unroll
    for (int i = 0; i < 6; i++)
#pragma unroll
        for (int k = 0; k < 4; k++) v[i][k] = bf2_as_h2(v[i][k]);
}

__device__ __forceinline__ float gelu_s(float y) {
    float u = y * fmaf(y, y, GELU_C);
    float t;
    asm volatile("tanh.approx.f32 %0, %1;\n" : "=f"(t) : "f"(u));
    return fmaf(y, t, y);
}
__device__ __forceinline__ void p1_pack(int c, uint32_t (&p)[4], uint32_t (&dd)[4]) {
#pragma unroll
    for (int u = 0; u < 4; u++) {
        if ((c & 3) == 0) dd[u] = p[u];
        else {
            uint32_t n = dd[u];
            if ((c & 3) == 1) n = __byte_perm(n, 0, 0x2301);
            if ((c & 3) == 2) {
                dd[u] = __byte_perm(n >> 3, n >> 1, 0x6341);
                n = __byte_perm(n >> 3, n >> 1, 0x7250);
            }
            asm("lop3.b32 %0, %0, %1, 0x40074007, 0xd8;\n" : "+r"(p[u]) : "r"(n));
        }
    }
}
__device__ __forceinline__ void p1_store(int c, const uint32_t (&p)[4], uint8_t* hptr) {
    if (c & 3) stg128_cs(hptr + (c >> 2) * H_HALF + ((c & 3) - 1) * 512, p[0], p[1], p[2], p[3]);
}

template <bool GEN>
__device__ __forceinline__ void p1_epilogue(uint32_t (&acc)[32], float (&ssq)[2], uint32_t sc2, uint8_t* hp, int zero) {
    uint32_t sq[2], dd[4];
#pragma unroll
    for (int c = 0; c < 8; c++) {
        if (GEN) sched_break(zero);
        uint32_t p[4];
#pragma unroll
        for (int u = 0; u < 4; u++) {
            const uint32_t y = acc[8 * (c >> 1) + 2 * u + (c & 1)];
            if (GEN) {
                const float sc = c & 1 ? bf_hi(sc2) : bf_lo(sc2), fs = __uint_as_float(0x78000000u - __float_as_uint(sc));
                const float g0 = gelu_s(h_lo(y) * fs), g1 = gelu_s(h_hi(y) * fs);
                ssq[c & 1] = fmaf(g1, g1, fmaf(g0, g0, ssq[c & 1]));
                p[u] = pack_f16(g0 * sc, g1 * sc);
            } else {
                uint32_t g;
                asm("{\n.reg .b32 w;\n"
                    "fma.rn.f16x2 w, %1, %1, %2;\n"
                    "mul.rn.f16x2 w, w, %1;\n"
                    "tanh.approx.f16x2 w, w;\n"
                    "fma.rn.f16x2 %0, %1, w, %1;\n}\n" : "=r"(g) : "r"(y), "r"(0x40d940d9u));
                acc[8 * (c >> 1) + 2 * u + (c & 1)] = g;
                if (c < 2 && u == 0) asm("mul.rn.f16x2 %0, %1, %1;\n" : "=r"(sq[c & 1]) : "r"(g));
                else asm("fma.rn.f16x2 %0, %1, %1, %0;\n" : "+r"(sq[c & 1]) : "r"(g));
                if (c & 1) asm("{\n.reg .b16 l, h;\n.reg .b32 f;\nmov.b32 {l, h}, %2;\nmov.b32 f, {h, h};\nmul.rn.f16x2 %0, %1, f;\n}\n" : "=r"(p[u]) : "r"(g), "r"(sc2));
                else asm("{\n.reg .b16 l, h;\n.reg .b32 f;\nmov.b32 {l, h}, %2;\nmov.b32 f, {l, l};\nmul.rn.f16x2 %0, %1, f;\n}\n" : "=r"(p[u]) : "r"(g), "r"(sc2));
            }
        }
        p1_pack(c, p, dd);
        if (c & 3) {
#pragma unroll
            for (int u = 0; u < 4; u++) acc[4 * (c - 1 - (c >> 2)) + u] = p[u];
        }
        p1_store(c, p, hp);
    }
    if (!GEN) {
#pragma unroll
        for (int r = 0; r < 2; r++) ssq[r] += h_lo(sq[r]) + h_hi(sq[r]);
    }
}
template <int CS, int NWG>
__device__ __forceinline__ void p1_compute(uint32_t sbase, int cb0, int warp, int lane, int zero) {
    const uint32_t bar_full = sbase + P1_OFF_BAR, bar_empty = bar_full + P1_NST * 8, bar_w = bar_empty + P1_NST * 8;
    const int wg = warp >> 2, w = warp & 3, cb = cb0 + wg;
    const uint32_t slot_free = mapa(bar_empty, lane & (CS - 1)) + (lane / CS) * 8;
    if (lane < 4 * CS && lane / CS != 1 + wg && (NWG == 2 || wg || lane >= CS)) mbar_arrive_cluster(slot_free);
    if (wg == 1) bar_arrive(1, 256);
    uint32_t a[24][4], ex[2], gen = 0;
    const uint32_t wsrc = sbase + (1 + wg) * P1_SLOT + ((lane >> 4) * 8 + (lane & 7)) * 128 + (((2 * w + ((lane >> 3) & 1)) ^ (lane & 7)) << 4);
#pragma unroll 1
    for (int it = 0; it < 2; it++) {
        if (it) mbar_wait(bar_w + wg * 8, 0);
        TRACEW(110 + warp, 5);
        if (it || wg == 0) {
#pragma unroll
        for (int k = 0; k < 24; k++) ldsm4t(a[k], wsrc + k * 2048);
#pragma unroll
        for (int r = 0; r < 2; r++) {
            float t = 0.f;
#pragma unroll
            for (int j = 0; j < 6; j++) {
                uint32_t c = bf2_mul(a[4 * j][r], a[4 * j][r]);
#pragma unroll
                for (int k = 1; k < 8; k++) c = bf2_fma(a[4 * j + k / 2][r + (k & 1) * 2], a[4 * j + k / 2][r + (k & 1) * 2], c);
                t += bf_lo(c) + bf_hi(c);
            }
            t += __shfl_xor_sync(0xffffffffu, t, 1);
            t += __shfl_xor_sync(0xffffffffu, t, 2);
            asm("sqrt.approx.f32 %0, %0;\n" : "+f"(t));
            ex[r] = min(max(__float_as_uint(13.9f * t) >> 23, 72u), 198u);
        }
        asm volatile("{\n.reg .pred p;\nsetp.gt.u32 p, %1, 7;\nbar.red.or.pred p, %2, 128, p;\nselp.u32 %0, 1, 0, p;\n}\n"
                     : "=r"(gen) : "r"(max(ex[0] - 125u, ex[1] - 125u)), "r"(5 + wg) : "memory");
        gen = __shfl_sync(0xffffffffu, gen, 0) & it;
        if (it) {
            if ((lane & 3) < 2) g_ex[cb * 64 + w * 16 + (lane & 1) * 8 + (lane >> 2)] = lane & 1 ? ex[1] : ex[0];
            if (lane / CS == 1 + wg) mbar_arrive_cluster(slot_free);
            __syncwarp();
        }
        }
        if (gen) {
#pragma unroll
            for (int k = 0; k < 24; k++)
#pragma unroll
                for (int j = 0; j < 4; j++) a[k][j] = bf2_mul(a[k][j], (268u - ex[j & 1]) * 0x00800080u);
        }
        if (it || wg == 1) {
#pragma unroll
            for (int k = 0; k < 24; k++)
#pragma unroll
                for (int j = 0; j < 4; j++) {
                    a[k][j] = bf2_as_h2(bf2_mul(a[k][j], 0x07800780u));
                    asm volatile("" : "+r"(a[k][j]));
                }
        }
        TRACEW(110 + warp, 6);
    }
#pragma unroll
    for (int j = 0; j < 4; j++)
        asm volatile("st.shared.u32 [%0], %1;\n" ::"r"(sbase + P1_OFF_A + warp * 512 + (j & 1) * 256 + (j >> 1) * 128 + lane * 4), "r"(a[23][j]) : "memory");
    asm volatile("fence.proxy.async.shared::cta;\n" ::: "memory");
    TRACEW(110 + warp, 7);
    const uint32_t ex2 = ex[0] | ex[1] << 16;
    const uint32_t sc2 = gen ? 0x7f007f00u - (ex2 << 7) : (0x008e008eu - ex2) << 10;
    const uint32_t empty_remote = mapa(bar_empty, lane & (CS - 1));
    const int g = lane >> 2, q = lane & 3, turn = wg + 1 == NWG ? 1 : wg + 2;
    float ssq[2] = {0.f, 0.f};
    uint32_t acc[32] = {};
    TSTAMP(0, 1);
    STAMPT(128, 4);
    STAMPT(256, 5);

    uint8_t* hp = reinterpret_cast<uint8_t*>(g_h) + ((cb * 2 + (w >> 1)) * H_STEP + (w & 1) * 1536) + g * 64 + (q ^ (g >> 1)) * 16;
    const uint64_t desc_base = make_desc(sbase, 16, 1024) | (1ull << 62);
    const uint64_t da = make_desc(sbase + P1_OFF_A + wg * 2048, 128, 256);
#pragma unroll 1
    for (int i = 0;; i++) {
        const int s0 = (i & 1) * 16, par = (i >> 1) & 1;
        const uint64_t d0 = desc_base + (uint64_t)((i & 1) * (LN_TILE / 16));
        TRACE(wg, i, 0);
        mbar_wait(bar_full + s0, par);
        bar_sync(1 + wg, 256);
        TRACE(wg, i, 1);
        uint32_t step, more;
        wg_fence();
#pragma unroll
        for (int k = 0; k < 24; k++) {
            if (k == 12) mbar_wait(bar_full + s0 + 8, par);
            const uint64_t db = d0 + (uint64_t)((k >> 2) * 1024 + (k & 3) * 2);
            if (k < 23) mma_rs_n128(acc, a[k], db, k ? 1 : zero);
            else mma_ss_n128(acc, da, db);
            if (k == 23) bar_arrive(turn, 256);
            if (k % 12 == 11) wg_commit();
        }
        if (NWG == 2) {
            step = (i ? 11 : LN_STEP) * (2 * H_TILE);
            more = i + 1 < NSMALL;
        } else asm volatile("ld.shared.v2.u32 {%0, %1}, [%2];\n" : "=r"(step), "=r"(more) : "r"(sbase + P1_OFF_TILE + (i & 3) * 16) : "memory");
        TRACE(wg, i, 2);
        wg_wait<1>();
        if (lane < CS) mbar_arrive_cluster(empty_remote + s0);
        hp += step;
        TRACE(wg, i, 3);
        wg_wait<0>();
        TRACE(wg, i, 4);
        if (lane < CS) mbar_arrive_cluster(empty_remote + s0 + 8);
        if (gen) p1_epilogue<true>(acc, ssq, sc2, hp, zero);
        else p1_epilogue<false>(acc, ssq, sc2, hp, zero);
        if (!more) break;
    }
    TSTAMP(0, 21);
    if (wg == 0) bar_sync(1, 256);
    uint32_t par;
    if (NWG == 2) par = __ldcg(&g_epoch) & 1;
    else asm volatile("ld.shared.u32 %0, [%1];\n" : "=r"(par) : "r"(sbase + P1_OFF_TILE - 4) : "memory");
    float* sums = g_sums[par];
#pragma unroll
    for (int r = 0; r < 2; r++) {
        ssq[r] += __shfl_xor_sync(0xffffffffu, ssq[r], 1);
        ssq[r] += __shfl_xor_sync(0xffffffffu, ssq[r], 2);
        if (q == 0) atomicAdd(sums + cb * 64 + w * 16 + r * 8 + g, ssq[r]);
    }
    if (NWG == 2) {
        asm volatile("fence.proxy.async.global;\nfence.acq_rel.gpu;\n" ::: "memory");
        __syncwarp();
        if (lane == 0) asm volatile("red.relaxed.gpu.global.add.u32 [%0], 1;\n" ::"l"(&g_img[2]) : "memory");
    }
}

__device__ __forceinline__ void p1_w2(const __nv_bfloat16* __restrict__ w2, const __nv_bfloat16* __restrict__ grn_b, int w, int lane) {
    const int gw = blockIdx.x * 4 + w;
    float* sums = g_sums[__ldcg(&g_epoch) & 1] + HID;
    flag_wait<true>(&g_flag[40][1][0], 12);
    {
        const int col = gw % 6 * 64 + lane * 2;
        float bsum[2] = {0.f, 0.f}, asum[2] = {0.f, 0.f};
#pragma unroll 4
        for (int kk = 0; kk < 192; kk++) {
            const int k = gw / 6 * 192 + kk;
            const uint32_t v = *reinterpret_cast<const uint32_t*>(w2 + k * C_DIM + col);
            const float b = __bfloat162float(grn_b[k]), f = __uint_as_float(__ldcg(&g_ex[k]) << 23);
            bsum[0] = fmaf(b, bf_lo(v), bsum[0]);
            bsum[1] = fmaf(b, bf_hi(v), bsum[1]);
            asum[0] = fmaf(f, fabsf(bf_lo(v)), asum[0]);
            asum[1] = fmaf(f, fabsf(bf_hi(v)), asum[1]);
        }
#pragma unroll
        for (int j = 0; j < 2; j++) {
            atomicAdd(sums + col + j, bsum[j]);
            atomicAdd(sums + C_DIM + col + j, asum[j]);
        }
        __threadfence();
        __syncwarp();
        if (lane == 0) asm volatile("red.relaxed.gpu.global.add.u32 [%0], 1;\n" ::"l"(&g_flag[LN_RING + 2][0][0]) : "memory");
    }
    while (*(volatile unsigned*)&g_flag[P1_IMG % LN_RING][1][0] < 12 * (P1_IMG / LN_RING + 1)) {
        __nanosleep(2000);
        SAFE_BREAK
    }
    flag_wait<true>(&g_flag[LN_RING + 2][0][0], 48);
    float z = 0.f;
#pragma unroll
    for (int j = 0; j < C_DIM / 32; j++) z = fmaxf(z, __ldcg(sums + C_DIM + j * 32 + lane));
    const float sc = __uint_as_float((263u - acc_exp(__uint_as_float(__reduce_max_sync(0xffffffffu, __float_as_uint(z))))) << 23);
    const int np = gw % 6 * 64 + lane * 2;
#pragma unroll 2
    for (int cc = 0; cc < 24; cc++) {
        const int c = gw / 6 * 24 + cc;
        uint32_t v[8], o[2][4];
#pragma unroll
        for (int e = 0; e < 8; e++) v[e] = *reinterpret_cast<const uint32_t*>(w2 + (c * 8 + e) * C_DIM + perm32(np));
#pragma unroll
        for (int e = 0; e < 4; e++) {
            const uint2 t = __ldcg(reinterpret_cast<const uint2*>(g_ex) + c * 4 + e);
            const float f0 = __uint_as_float(t.x << 23), f1 = __uint_as_float(t.y << 23);
            o[0][e] = pack_f16(bf_lo(v[2 * e]) * f0 * sc, bf_lo(v[2 * e + 1]) * f1 * sc);
            o[1][e] = pack_f16(bf_hi(v[2 * e]) * f0 * sc, bf_hi(v[2 * e + 1]) * f1 * sc);
        }
#pragma unroll
        for (int j = 0; j < 2; j++)
            g_w2img[0][(((c >> 1) * 48 + (np >> 3)) * 2 + (c & 1)) * 8 + (np & 7) + j] = make_uint4(o[j][0], o[j][1], o[j][2], o[j][3]);
    }
    asm volatile("fence.proxy.async.global;\n" ::: "memory");
    __threadfence();
    __syncwarp();
    if (lane < 2) asm volatile("red.relaxed.gpu.global.add.u32 [%0], 1;\n" ::"l"(&g_img[lane * 2]) : "memory");
}

__device__ __forceinline__ void p1_load_w1(uint32_t sbase, const CUtensorMap* wmap, int cb0, int nwg) {
    const uint32_t bar_w = sbase + P1_OFF_BAR + 2 * P1_NST * 8;
    for (int i = 0; i < nwg; i++) {
        mbar_expect_tx(bar_w + i * 8, P1_SLOT);
        tma2(sbase + (1 + i) * P1_SLOT, wmap, (cb0 + i) * 64, 0, bar_w + i * 8);
        tma2(sbase + (1 + i) * P1_SLOT + P1_SLOT / 2, wmap, (cb0 + i) * 64, 192, bar_w + i * 8);
    }
}

template <int CS>
__global__ void __cluster_dims__(CS, 1, 1) __launch_bounds__(512, 1)
pass1_kernel(const __grid_constant__ CUtensorMap wmap, const __nv_bfloat16* __restrict__ x, const __nv_bfloat16* __restrict__ dw,
             const __nv_bfloat16* __restrict__ w1, int zero) {
    extern __shared__ __align__(1024) uint8_t smem[];
    const uint32_t sbase = smem_u32(smem);
    const uint32_t bar_full = sbase + P1_OFF_BAR, bar_empty = bar_full + P1_NST * 8, bar_w = bar_empty + P1_NST * 8;
    const uint32_t bar_xfull = bar_w + 24, bar_raw = bar_xfull + 16, bar_done = bar_raw + 16;
    const int tid = threadIdx.x;
    const int warp = __shfl_sync(0xffffffffu, tid >> 5, 0), lane = tid & 31;
    const uint32_t rank = cluster_rank();
    const int bid = blockIdx.x, cl = bid >> 1;
    uint8_t* const ring = reinterpret_cast<uint8_t*>(g_ln);
    const int ln0 = bid >> 2, items = (NT128 - 1 - ln0) / LN_STEP + 1;

    TSTAMP(0, 0);
    TRACEW(110 + warp, 0);

    if (warp >= 12) {
        reg_dec<56>();
        asm volatile("barrier.cluster.arrive.relaxed.aligned;\n" ::: "memory");
        asm volatile("barrier.cluster.wait.aligned;\n" ::: "memory");
        {
            auto ring_row = [&](int p) {
                const int n = (p & 8) * 8 + (lane >> 3) * 8 + (p & 3) * 2 + (p >> 2 & 1);
                return n * 128 + (((lane ^ n) & 7) << 4);
            };
            const uint8_t* xsrc = reinterpret_cast<const uint8_t*>(x) + (size_t)(LN_STEP * 8 + bid * 2 + (warp & 1)) * P1_X;
            const uint32_t xbar = bar_xfull + (warp & 1) * 8, xdst = sbase + P1_OFF_X + (warp & 1) * P1_X;
            const uint32_t sdw = sbase + P1_OFF_DW + (lane & 7) * 16;
            uint32_t src = xdst - P1_OFF_X + (lane >> 3) * (C_DIM * 2) + (lane & 7) * 16;
            int row0 = ring_row((bid & 7) * 2 + (warp & 1)) ^ 288, slot = bid >> 3, used = 0;
            auto next = [&]() {
                xsrc += (size_t)LN_STEP * 8 * P1_X;
                if (elect_one()) {
                    mbar_expect_tx(xbar, P1_X);
                    bulk_g2s(xdst, xsrc, P1_X, xbar);
                }
                __syncwarp();
            };
#pragma unroll 1
            for (int i = -1; i < items; i++) {
                if (warp == 14) TRACEW(128 + i, 0);
                const int place = p1_place(ln0 + i * LN_STEP, slot);
                const int last = i > 0 ? 3 : i ? 2 + (warp >> 1 & 1) : 1;
#pragma unroll 1
                for (int ps = i < 0 ? last - 4 : 0; ps <= last; ps += i < 0 ? 4 : 1) {
                    if (i < 0 && ps > 0) STAMPT(416, 6);
                    if (i < 0 && ps > 0) mbar_wait(bar_raw, 0);
                    if (i < 0 && ps > 0) STAMPT(416, 7);
                    if (ps == 0) {
                        if (used) flag_wait<false>(&g_flag[slot][1][0], used);
                        if (i && i + 1 < items && elect_one())
                            asm volatile("cp.async.bulk.prefetch.L2.global [%0], %1;\n" ::"l"(xsrc + (size_t)LN_STEP * 8 * P1_X), "r"(P1_X) : "memory");
                        if (i) mbar_wait(xbar, ~i & 1);
                        else mbar_wait(bar_raw + 8, 0);
                        if (warp == 14) TRACEW(128 + i, 1);
                    }
                    uint32_t v[6][4];
#pragma unroll
                    for (int j = 0; j < 6; j++) lds128(v[j], src + (ps & 3) * (4 * C_DIM * 2) + j * 128);
                    ln_row(v, sdw, [&](uint32_t dep) {
                        if (i == 0 && ps == 1 && lane < CS) mbar_arrive_cluster(mapa(bar_empty, lane) + (dep & zero));
                        if (ps == 3 && i > 0 && i + 1 < items && !__any_sync(0xffffffffu, dep & zero)) next();
                    });
                    uint8_t* dst = ring + (place * LN_TILE + (ps & 1) * 4096 + (row0 ^ (ps & 2) * 144));
#pragma unroll
                    for (int j = 0; j < 6; j++)
                        asm volatile("{\n.reg .pred p;\nsetp.ge.s32 p, %5, 0;\n@p st.global.v4.u32 [%0], {%1,%2,%3,%4};\n}\n"
                                     ::"l"(dst + j * 16384), "r"(v[j][0]), "r"(v[j][1]), "r"(v[j][2]), "r"(v[j][3]), "r"(ps) : "memory");
                }
                if (warp == 14) TRACEW(128 + i, 2);
                asm volatile("fence.proxy.async.global;\nfence.acq_rel.cta;\n" ::: "memory");
                if (i < 0) {
                    bar_sync(4, 128);
                    if (warp < 14) break;
                    row0 ^= 288;
                    slot += NGRP;
                } else {
                    if (i) mbar_wait(bar_done, ~i & 1);
                    else {
                        src += P1_OFF_X;
                        slot = ln0;
                        row0 = ring_row((bid & 3) * 4 + (warp & 1) * 2);
                    }
                    __syncwarp();
                    if (lane == 0) mbar_arrive(bar_done);
                    if ((slot += LN_STEP) >= LN_RING) { slot -= LN_RING; used += 12; }
                }
            }
            if (warp < 14 && lane < CS) mbar_arrive_cluster(mapa(bar_empty, lane));
        }
        if (warp == 12) {
            int prev = 0, t = cl >> 2, next = t + NGRP;
            const uint32_t rbase = mapa(sbase, lane & (CS - 1));
            int i = 0;
#pragma unroll 1
            for (; t < NT128; i++) {
                const int s0 = (i & 1) * 2, par = (i >> 1) & 1;
                const int round = t / LN_RING, slot = t - round * LN_RING;
                const uint8_t* src = ring + slot * LN_TILE + rank * (P1_SLOT / CS);
                int draw = 0;
                if (rank == 0 && lane == 0) draw = 2 * NGRP + atomicAdd(&g_flag[LN_RING + ((cl >> 1) & 1)][cl & 1][0], 1u);
                flag_wait<true>(&g_flag[slot][0][0], 8 * round + 8);
                TRACEW(i, 2);
                if (i == 0) STAMPT(384, 10);
                if (i == 2) STAMPT(384, 13);
                if (i == 3) STAMPT(384, 14);
                asm volatile("fence.proxy.async.global;\n" ::: "memory");
                draw = p1_tile(__shfl_sync(0xffffffffu, draw, 0));
#pragma unroll
                for (int h = 0; h < 2; h++) {
                    mbar_wait(bar_empty + (s0 + h) * 8, par);
                    TRACEW(i, 4 + h);
                    if (i == 0 && h == 1) STAMPT(384, 11);
                    if (elect_one()) {
                        mbar_expect_tx(bar_full + (s0 + h) * 8, P1_SLOT + 16 - 16 * h);
                        bulk_g2s_mc(sbase + (s0 + h) * P1_SLOT + rank * (P1_SLOT / CS), src + h * P1_SLOT, P1_SLOT / CS, bar_full + (s0 + h) * 8, (uint16_t)((1 << CS) - 1));
                    }
                    __syncwarp();
                    if (h == 0 && rank == 0 && lane < CS)
                        asm volatile("st.async.shared::cluster.mbarrier::complete_tx::bytes.v4.u32 [%0], {%1, %2, %3, %3}, [%4];\n"
                                     ::"r"(rbase + P1_OFF_TILE + (i & 3) * 16), "r"((t - prev) * (2 * H_TILE)), "r"((int)(next < NT128)), "r"(draw),
                                       "r"(rbase + P1_OFF_BAR + s0 * 8) : "memory");
                }
                prev = t;
                t = next;
                next = draw;
                if (rank != 0) {
                    mbar_wait(bar_full + s0 * 8, (i >> 1) & 1);
                    mbar_wait(bar_full + s0 * 8 + 8, (i >> 1) & 1);
                    if (lane == 0 && rank == 1) asm volatile("red.relaxed.gpu.global.add.u32 [%0], %1;\n" ::"l"(&g_flag[slot][1][0]), "r"(CS * 3 / 2) : "memory");
                    asm volatile("ld.shared.u32 %0, [%1];\n" : "=r"(next) : "r"(sbase + P1_OFF_TILE + (i & 3) * 16 + 8) : "memory");
                    TRACEW(i, 3);
                }
            }
#pragma unroll 1
            for (int j = 2 * i; j < 2 * i + 4; j++) mbar_wait(bar_empty + (j & 3) * 8, (j >> 2) & 1);
        } else if (warp == 13) {
            STAMPT(416, 8);
            if (lane == 0) asm volatile("red.release.gpu.global.add.u32 [%0], 1;\n" ::"l"(&g_flag[bid >> 3][0][0]) : "memory");
            __syncwarp();
            STAMPT(416, 9);
            const uint32_t ep = g_epoch & 1;
            asm volatile("st.shared.u32 [%0], %1;\n" ::"r"(sbase + P1_OFF_TILE - 4), "r"(ep) : "memory");
            if (bid < 18) reinterpret_cast<float4*>(g_sums[ep ^ 1])[bid * 32 + lane] = make_float4(0.f, 0.f, 0.f, 0.f);
#pragma unroll 1
            for (int i = 0; i < items; i++) {
                mbar_wait(bar_done, i & 1);
                asm volatile("fence.proxy.async.global;\n" ::: "memory");
                if (lane == 0) {
                    const int slot = i ? ln0 + (i & 1) * LN_STEP : NGRP + (bid >> 3), place = p1_place(ln0 + i * LN_STEP, slot);
                    mbar_arrive(bar_done);
                    asm volatile("red.release.gpu.global.add.u32 [%0], %1;\n" ::"l"(&g_flag[place][0][0]), "r"(i ? 2 : 1) : "memory");
                    if (place != slot) {
                        atomicAdd(&g_flag[slot][0][0], 2u);
                        atomicAdd(&g_flag[slot][1][0], 3u);
                    }
                }
                __syncwarp();
                TRACEW(128 + i, 3);
            }
        }
    } else {
        if (tid == 0) {
            mbar_init(bar_raw, 1);
            mbar_init(bar_raw + 8, 1);
            mbar_init(bar_xfull, 1);
            mbar_init(bar_xfull + 8, 1);
            for (int i = 0; i < 3; i++) mbar_init(bar_w + i * 8, 1);
            asm volatile("fence.mbarrier_init.release.cluster;\n" ::: "memory");
            {
                mbar_expect_tx(bar_raw, P1_X + C_DIM * 2);
                bulk_g2s(sbase + P1_OFF_DW, dw, C_DIM * 2, bar_raw);
                for (int i = 0; i < 2; i++) bulk_g2s(sbase + i * P1_X + P1_X / 2, x + (size_t)(bid * 16 + i * 8) * C_DIM, P1_X / 2, bar_raw);
                if (bid < 96) asm volatile("cp.async.bulk.prefetch.L2.global [%0], 12288;\n" ::"l"(w1 + bid * 6144) : "memory");
                mbar_expect_tx(bar_raw + 8, P1_X);
                for (int i = 0; i < 2; i++) bulk_g2s(sbase + i * P1_X, x + (size_t)(NGRP * 128 + bid * 16 + i * 8) * C_DIM, P1_X / 2, bar_raw + 8);
            }
            p1_load_w1(sbase, &wmap, (bid & 7) * 3, 3);
            for (int i = 0; i < 2; i++) {
                mbar_expect_tx(bar_xfull + i * 8, P1_X);
                bulk_g2s(sbase + P1_OFF_X + i * P1_X, x + (size_t)(LN_STEP * 128 + bid * 32 + i * 16) * C_DIM, P1_X, bar_xfull + i * 8);
            }
        }
        if (tid == 32) {
            mbar_init(bar_done, 3);
            mbar_arrive(bar_done);
            asm volatile("fence.mbarrier_init.release.cluster;\n" ::: "memory");
        }
        if (tid == 64) {
            for (int i = 0; i < P1_NST; i++) {
                mbar_init(bar_full + i * 8, 1);
                mbar_init(bar_empty + i * 8, 12 * CS);
            }
            asm volatile("fence.mbarrier_init.release.cluster;\n" ::: "memory");
            if (bid < 64) (&g_half[0][0])[bid] = 0;
            else if (bid < 67) g_img[bid - 64] = 0;
        }
        __syncwarp();
        asm volatile("barrier.cluster.arrive.relaxed.aligned;\n" ::: "memory");
        reg_inc<152>();
        TRACEW(110 + warp, 1);
        gdc_launch();
        asm volatile("barrier.cluster.wait.aligned;\n" ::: "memory");
        p1_compute<CS, 3>(sbase, (bid & 7) * 3, warp, lane, zero);
        TSTAMP(0, 30);
    }
}

constexpr int P2_B = 24576, P2_NB = 5;
constexpr int P2_A = 3072, P2_NA = 5;
constexpr int P2_XROW = C_DIM * 2;
constexpr int P2_OFF_A = P2_B * P2_NB;
constexpr int P2_OFF_X = P2_OFF_A + 3 * P2_NA * P2_A;
constexpr int P2_XHALF = 32 * P2_XROW + 64;
constexpr int P2_OFF_BIAS = P2_OFF_X + 64 * P2_XROW + 64;
constexpr int P2_OFF_GRN = P2_OFF_BIAS + C_DIM * 4;
constexpr int P2_OFF_RED = P2_OFF_GRN + HID * 2;
constexpr int P2_OFF_BAR = P2_OFF_RED + 192;
static_assert(P2_OFF_BAR >= P1_OFF_DW && P2_OFF_BAR + (2 * P2_NB + 6 * P2_NA + 3) * 8 <= P1_OFF_BAR, "");
constexpr int P2_SMEM = P1_SMEM;
constexpr int P2_LAG = 17;
constexpr int P2_NCL = NUM_CTAS / 2, P2_ITEMS = NT128 / P2_NCL, P2_SHARED = NT128 - P2_ITEMS * P2_NCL;
constexpr int P2_POS = P2_LAG * (P2_ITEMS - 1) + 48;
__device__ __forceinline__ int p2_start(int n) { return n < 0 ? 0 : n == P2_ITEMS ? P2_POS - 24 : P2_LAG * n; }
constexpr int P2_FOLD = 17;
constexpr int P2_XC = 8 * P2_XROW;
__device__ __forceinline__ int p2_tile(int cl, int n) {
    return n == 0 ? NT128 - 1 - cl : n < 0 || n == P2_ITEMS ? NT128 - 1 - P2_NCL - (cl >> 1) : cl + P2_NCL * (n - 1);
}

constexpr int P2_EG = 2;
__device__ __forceinline__ void p2_init(uint32_t (&acc)[48], int c, uint32_t sb) {
#pragma unroll
    for (int i = 8 * (c % 6); i < 8 * (c % 6) + 8; i += 4)
        asm volatile("ld.shared.v4.u32 {%0,%1,%2,%3}, [%4];\n" : "=r"(acc[i]), "=r"(acc[i + 1]), "=r"(acc[i + 2]), "=r"(acc[i + 3])
                     : "r"(sb + c * 128 + i % 8 * 4) : "memory");
}
__device__ __forceinline__ void p2_epilogue(uint32_t (&acc0)[48], uint32_t (&acc1)[48], uint32_t sx, uint32_t sb, uint32_t up, int zero) {
    uint32_t v[2][P2_EG][4];
    auto load = [&](int c, uint32_t a) {
#pragma unroll
        for (int j = 0; j < P2_EG; j++) {
            const int u = c * P2_EG + j;
            asm volatile("ld.shared.v4.u32 {%0,%1,%2,%3}, [%4];\n" : "=r"(v[c & 1][j][0]), "=r"(v[c & 1][j][1]), "=r"(v[c & 1][j][2]), "=r"(v[c & 1][j][3])
                         : "r"(a + (u >> 1) * 64 + (u & 1) * 4 * P2_XROW) : "memory");
        }
    };
    load(0, sx);
#pragma unroll
    for (int c = 0; c < 24 / P2_EG; c++) {
        if (c + 1 < 24 / P2_EG) load(c + 1, sx + (v[c & 1][P2_EG - 1][0] & zero));
#pragma unroll
        for (int j = 0; j < P2_EG; j++) {
            const int u = c * P2_EG + j, i = 8 * ((u >> 1) % 6) + (u & 1);
            const uint32_t (&acc)[48] = u < 12 ? acc0 : acc1;
            uint32_t (&w)[4] = v[c & 1][j];
#pragma unroll
            for (int e = 0; e < 4; e++)
                w[e] = bf2_fma(pack_bf16(h_lo(acc[i + 2 * e]), h_hi(acc[i + 2 * e])), up, w[e]);
            asm volatile("st.shared.v4.u32 [%4], {%0,%1,%2,%3};\n" ::"r"(w[0]), "r"(w[1]), "r"(w[2]), "r"(w[3]),
                         "r"(sx + (u >> 1) * 64 + (u & 1) * 4 * P2_XROW) : "memory");
        }
        p2_init(c < 6 ? acc0 : acc1, c, sb + (v[c & 1][1][0] & zero));
    }
}

__device__ __forceinline__ void p2_unpack(uint4& u, uint32_t o1, uint32_t o2, uint32_t o3) {
    u.z = o1 & 0xbff8bff8u;
    u.y = o2 & 0xbff8bff8u;
    u.w = o3 & 0xbff8bff8u;
    u.x = (__byte_perm(o1, 0, 0x2301) & 0x07400740u) | ((__byte_perm(o2, o3, 0x6240) << 3) & 0x38383838u) | ((__byte_perm(o2, o3, 0x3715) << 1) & 0x80808080u);
}
__device__ __forceinline__ uint32_t h2_mul(uint32_t a, uint32_t b) {
    uint32_t r;
    asm("mul.rn.f16x2 %0, %1, %2;\n" : "=r"(r) : "r"(a), "r"(b));
    return r;
}
__device__ __forceinline__ void p2_epilogue_add(const uint32_t (&acc)[48], uint8_t* o, uint32_t up, int zero) {
#pragma unroll
    for (int t = 0; t < 12; t++) {
        uint32_t v[4];
#pragma unroll
        for (int e = 0; e < 4; e++) {
            v[e] = acc[8 * (t >> 1) + (t & 1) + 2 * e];
            asm volatile("" : "+r"(v[e]));
            v[e] = bf2_mul(pack_bf16(h_lo(v[e]), h_hi(v[e])), up);
        }
        asm volatile("red.global.add.noftz.v4.bf16x2 [%0], {%1,%2,%3,%4};\n" ::"l"(o + (t >> 1) * 64 + (t & 1) * 4 * P2_XROW),
                     "r"(v[0]), "r"(v[1]), "r"(v[2]), "r"(v[3]) : "memory");
        if (t % 3 == 2) sched_break(zero);
    }
}

__global__ void __cluster_dims__(2, 1, 1) __launch_bounds__(512, 1)
pass2_kernel(const __grid_constant__ CUtensorMap wmap, const __nv_bfloat16* __restrict__ x, const __nv_bfloat16* __restrict__ w2,
             const __nv_bfloat16* __restrict__ grn_g, const __nv_bfloat16* __restrict__ grn_b, __nv_bfloat16* __restrict__ out, int zero) {
    extern __shared__ __align__(1024) uint8_t smem[];
    const uint32_t sbase = smem_u32(smem);
    const uint32_t bar_bfull = sbase + P2_OFF_BAR, bar_bempty = bar_bfull + P2_NB * 8;
    const uint32_t bar_afull = bar_bempty + P2_NB * 8, bar_aempty = bar_afull + 3 * P2_NA * 8;
    const uint32_t bar_xfull = bar_aempty + 3 * P2_NA * 8, bar_oready = bar_xfull + 8, s_pos = bar_xfull + 16;
    int tid;
    asm volatile("mov.u32 %0, %%tid.x;\n" : "=r"(tid));
    const int warp = __shfl_sync(0xffffffffu, tid >> 5, 0), lane = tid & 31;
    const uint32_t rank = cluster_rank();
    const int cl = blockIdx.x >> 1, pair = cl >> 1;
    const int k0 = (4 * pair + (cl & 1) * (48 - P2_POS % 48)) % 48;
    const int head = pair < P2_SHARED && !(cl & 1), tail = pair < P2_SHARED && (cl & 1);

    const bool small = blockIdx.x < NUM_CTAS - 8 * NGRP;
    uint32_t par, gg[4];
    auto early = [&]() {
        asm volatile("ld.global.cg.u32 %0, [%1];\n" : "=r"(par) : "l"(&g_epoch) : "memory");
#pragma unroll
        for (int i = 0; i < 4; i++) asm volatile("ld.global.nc.u16 %0, [%1];\n" : "=r"(gg[i]) : "l"(grn_g + tid + 384 * i) : "memory");
    };
    if (warp < 12) early();
    if (small && tid == 0) {
        for (int i = 0; i < 2 * P1_NST + 2; i++) mbar_init(sbase + P1_OFF_BAR + i * 8, (i & 12) == 4 ? 16 : 1);
        asm volatile("fence.mbarrier_init.release.cluster;\n" ::: "memory");
        p1_load_w1(sbase, &wmap, blockIdx.x * 2, 2);
    }
    if (small) TSTAMP(0, 0);
    TSTAMP(1, 0);
    if (tid == 384) {
        for (int i = 0; i < P2_NB; i++) {
            mbar_init(bar_bfull + i * 8, 1);
            mbar_init(bar_bempty + i * 8, 24);
        }
        mbar_init(bar_xfull, 1);
        mbar_init(bar_oready, 4);
        asm volatile("st.shared.u32 [%0], 0;\nfence.mbarrier_init.release.cluster;\nfence.acq_rel.cta;\n" ::"r"(s_pos) : "memory");
    }
    if (warp > 12 && lane == 0) {
        for (int i = 0; i < P2_NA; i++) {
            mbar_init(bar_afull + ((warp - 13) * P2_NA + i) * 8, 1);
            mbar_init(bar_aempty + ((warp - 13) * P2_NA + i) * 8, 4);
        }
        asm volatile("fence.mbarrier_init.release.cluster;\n" ::: "memory");
    }
    __syncwarp();
    asm volatile("barrier.cluster.arrive.relaxed.aligned;\n" ::: "memory");

    if (warp >= 12) {
        reg_dec<32>();
        if (small) par = 0;
        else asm volatile("ld.acquire.gpu.global.u32 %0, [%1];\n" : "=r"(par) : "l"(&g_img[(warp & 1) * 2]) : "memory");
        asm volatile("barrier.cluster.wait.aligned;\n" ::: "memory");
        if (small) {
#pragma unroll 1
            for (int j = 0; warp == 12 && j < 2 * NSMALL; j++) {
                const uint32_t bar = sbase + P1_OFF_BAR + (j & 3) * 8;
                if (!(j & 1)) {
                    flag_wait<true>(&g_flag[LN_RING + 3 + (j >> 1)][0][0], 8);
                    asm volatile("fence.proxy.async.global;\n" ::: "memory");
                }
                mbar_wait(bar + P1_NST * 8, (j >> 2) & 1);
                if (elect_one()) {
                    mbar_expect_tx(bar, P1_SLOT);
                    bulk_g2s_mc(sbase + (j & 3) * P1_SLOT + rank * (P1_SLOT / 2),
                                reinterpret_cast<const uint8_t*>(g_ln) + (size_t)(2 * (LN_RING + 3) + j) * P1_SLOT + rank * (P1_SLOT / 2), P1_SLOT / 2, bar, (uint16_t)3);
                }
                __syncwarp();
            }
            asm volatile("barrier.cluster.arrive.aligned;\nbarrier.cluster.wait.aligned;\n" ::: "memory");
        }
        if (warp == 12) {
            const uint8_t* wsrc = reinterpret_cast<const uint8_t*>(g_w2img) + rank * (P2_B / 2);
            int st = 0, ph = 1, kb = k0, m = 0, r = 0;
            const int busy = head ? 0 : tail ? P2_POS - 24 : P2_POS;
#pragma unroll 1
            for (int p = 0; p < P2_POS; p++) {
                if (p == 0 || p == P2_FOLD) {
                    if (p || par < 48) flag_wait<true>(&g_img[p != 0], p ? 96 * 4 : 48);
                    asm volatile("fence.proxy.async.global;\n" ::: "memory");
                    if (p) wsrc += sizeof(g_w2img[0]);
                }
                mbar_wait(bar_bempty + st * 8, ph);
                TR2P(p, 0);
                if (elect_one()) {
                    mbar_expect_tx(bar_bfull + st * 8, P2_B);
                    bulk_g2s_mc(sbase + st * P2_B + rank * (P2_B / 2), wsrc + kb * P2_B, P2_B / 2, bar_bfull + st * 8, (uint16_t)3);
                    asm volatile("st.volatile.shared.u32 [%0], %1;\n" ::"r"(s_pos), "r"(p) : "memory");
                    const int idle = 2 - min(m, P2_ITEMS - 1) + max(m - 2 + (r >= 48 - 2 * P2_LAG), 0) - ((unsigned)(p - busy) < 24);
                    if (idle) asm volatile("mbarrier.arrive.shared::cta.b64 _, [%0], %1;\n" ::"r"(bar_bempty + st * 8), "r"(idle * 8) : "memory");
                }
                __syncwarp();
                if (++st == P2_NB) { st = 0; ph ^= 1; }
                if (++kb == 48) kb = 0;
                if (++r == P2_LAG) { r = 0; m++; }
            }
            mbar_wait(bar_bempty + st * 8, ph);
            if (lane == 0) mbar_arrive(bar_bfull + st * 8);
#pragma unroll 1
            for (int p = 1; p < P2_NB; p++) {
                if (++st == P2_NB) { st = 0; ph ^= 1; }
                mbar_wait(bar_bempty + st * 8, ph);
            }
        } else if (warp == 13) {
            const uint8_t* src[3];
            int n[3], left[3], wrap[3];
            uint32_t st[3];
            auto item = [&](int w) {
                const int u = (k0 + p2_start(n[w])) % 48;
                left[w] = n[w] < 0 || n[w] == P2_ITEMS ? 24 : 48;
                wrap[w] = left[w] - (48 - u);
                src[w] = reinterpret_cast<const uint8_t*>(g_h) + (size_t)p2_tile(cl, n[w]) * (2 * H_TILE) + rank * H_HALF + u * H_STEP;
            };
#pragma unroll
            for (int w = 0; w < 3; w++) {
                n[w] = w == 2 && head ? -1 : w;
                st[w] = 0x80000000u;
                item(w);
            }
            if (par < (NUM_CTAS - 8 * NGRP) * 12) flag_wait<true>(&g_img[2], (NUM_CTAS - 8 * NGRP) * 12);
            bar_arrive(3, 416);
            gdc_wait();
            asm volatile("fence.proxy.async.global;\n" ::: "memory");
#pragma unroll 1
            for (int fin = 0; fin < 3;) {
                bool idle = true;
#pragma unroll
                for (int w = 0; w < 3; w++) {
                    const uint32_t o = (st[w] & 0xff) + w * P2_NA * 8;
                    if (left[w] >= 0 && mbar_test(bar_aempty + o, st[w] >> 31)) {
                        idle = false;
                        if (left[w] == 0) {
                            if (lane == 0) mbar_arrive(bar_afull + o);
                            left[w] = -1;
                            fin++;
                        } else {
                            if (elect_one()) {
                                mbar_expect_tx(bar_afull + o, P2_A);
                                bulk_g2s(sbase + P2_OFF_A + o * (P2_A / 8), src[w], P2_A, bar_afull + o);
                            }
                            __syncwarp();
                            src[w] += H_STEP;
                            st[w] += 8;
                            if ((st[w] & 0xff) == P2_NA * 8) st[w] ^= 0x80000000u | (P2_NA * 8);
                            if (--left[w] == wrap[w]) src[w] -= 48 * H_STEP;
                            if (left[w] == 0 && (n[w] += 3) < P2_ITEMS + tail) item(w);
                        }
                    }
                }
                if (idle) __nanosleep(64);
                SAFE_BREAK
            }
        } else if (warp == 14) {
            const uint32_t sx = sbase + P2_OFF_X;
            size_t o = 0;
            auto pace = [&](int target) {
                int v;
                while (true) {
                    asm volatile("ld.volatile.shared.u32 %0, [%1];\n" : "=r"(v) : "r"(s_pos) : "memory");
                    if (v * 16 >= target) break;
                    __nanosleep(100);
                    SAFE_BREAK
                }
            };
#pragma unroll 1
            for (int n = -head; n <= P2_ITEMS; n++) {
                const size_t on = (size_t)(2 * p2_tile(cl, n) + rank) * (64 * C_DIM * 2);
                const bool st = n + head > 0, ld = n < P2_ITEMS;
                if (st) mbar_wait(bar_oready, (n - 1 + head) & 1);
                TR2P(n + 1, 1);
                if (lane == 0) {
                    if (n == 1 && head) {
                        asm volatile("cp.async.bulk.wait_group 0;\nfence.proxy.async.global;\n" ::: "memory");
                        asm volatile("st.release.gpu.global.u32 [%0], 1;\n" ::"l"(&g_half[pair][rank]) : "memory");
                    }
                    if (ld) mbar_expect_tx(bar_xfull, 64 * C_DIM * 2);
                    const bool paced = st && n < P2_ITEMS - 1;
                    int t = (P2_LAG * (n - 1) + 52) * 16;
#pragma unroll 1
                    for (int c = 0; st && c < 64 * P2_XROW; c += P2_XC) {
                        if (paced) pace(t += 11);
                        bulk_s2g(reinterpret_cast<uint8_t*>(out) + o + c, sx + c + (c >= 32 * P2_XROW ? 64 : 0), P2_XC);
                        asm volatile("cp.async.bulk.commit_group;\n" ::: "memory");
                    }
#pragma unroll 1
                    for (int c = 0; ld && c < 64 * P2_XROW; c += P2_XC) {
                        if (c == 0) asm volatile("cp.async.bulk.wait_group.read 4;\n" ::: "memory");
                        if (c == 32 * P2_XROW) asm volatile("cp.async.bulk.wait_group.read 0;\n" ::: "memory");
                        if (paced) pace(t += 11);
                        bulk_g2s(sx + c + (c >= 32 * P2_XROW ? 64 : 0), reinterpret_cast<const uint8_t*>(x) + on + c, P2_XC, bar_xfull);
                    }
                    TR2P(n + 1, 2);
                    TR2P(n + 1, 3);
                }
                __syncwarp();
                o = on;
            }
            asm volatile("cp.async.bulk.wait_group 0;\n" ::: "memory");
            TR2P(30, 1);
        }
    } else {
        reg_inc<160>();
        asm volatile("barrier.cluster.wait.aligned;\n" ::: "memory");
        if (small) {
            if (warp < 8) p1_compute<2, 2>(sbase, blockIdx.x * 2, warp, lane, zero);
            else p1_w2(w2, grn_b, warp & 3, lane);
            asm volatile("barrier.cluster.arrive.aligned;\nbarrier.cluster.wait.aligned;\n" ::: "memory");
            TSTAMP(0, 30);
            early();
        }
        const int wg = warp >> 2, w = warp & 3, g = lane >> 2, q = lane & 3;
        const uint32_t sx = sbase + P2_OFF_X + (g & 1) * P2_XHALF + (w * 8 + (g >> 1)) * P2_XROW + q * 16;
        const uint32_t af = bar_afull + wg * P2_NA * 8;
        const uint32_t s_a = sbase + P2_OFF_A + wg * P2_NA * P2_A + (lane >> 3) * 512 + (lane & 7) * 64 +
                             ((w ^ ((lane & 7) >> 1)) << 4);
        uint32_t acc0[48], acc1[48];
        uint32_t up;
        uint4 a0[2], a1[2];
        uint32_t st = 0, ph = 0;

        {
            float4* s_red = reinterpret_cast<float4*>(smem + P2_OFF_RED);
            const float* sums = g_sums[par & 1];
            float gx[4], part = 0.f, mx = 0.f;
            asm volatile("prefetch.global.L2 [%0];\n" ::"l"(sums + HID + tid * 2) : "memory");
            TSTAMP(1, 27);
            bar_sync(3, 416);
            gdc_wait();
            TSTAMP(1, 1);
#pragma unroll
            for (int i = 0; i < 4; i++) gx[i] = __ldcg(sums + tid + 384 * i);
            const float bias = __ldcg(sums + HID + tid), asum = __ldcg(sums + HID + C_DIM + tid);
            float z = __uint_as_float(__reduce_max_sync(0xffffffffu, __float_as_uint(asum)));
            uint32_t bm = __reduce_max_sync(0xffffffffu, __float_as_uint(fabsf(bias)));
#pragma unroll
            for (int i = 0; i < 4; i++) {
                asm("sqrt.approx.f32 %0, %1;\n" : "=f"(gx[i]) : "f"(fmaf(gx[i], HSCALE * HSCALE, 1e-6f)));
                part += gx[i];
                gx[i] *= bf_lo(gg[i]);
                mx = fmaxf(mx, fabsf(gx[i]));
            }
#pragma unroll
            for (int o = 16; o > 0; o >>= 1) part += __shfl_xor_sync(0xffffffffu, part, o);
            mx = __uint_as_float(__reduce_max_sync(0xffffffffu, __float_as_uint(mx)));
            TSTAMP(1, 26);
            if (lane == 0) s_red[warp] = make_float4(part, mx, z, __uint_as_float(bm));
            bar_sync(1, 384);
            float tot = 0.f;
            {
                const float4 t = s_red[min(lane & 15, 11)];
                tot = (lane & 15) < 12 ? t.x : 0.f;
#pragma unroll
                for (int o = 8; o > 0; o >>= 1) tot += __shfl_xor_sync(0xffffffffu, tot, o);
                mx = __uint_as_float(__reduce_max_sync(0xffffffffu, __float_as_uint(t.y)));
                z = __uint_as_float(__reduce_max_sync(0xffffffffu, __float_as_uint(t.z)));
                bm = __reduce_max_sync(0xffffffffu, __float_as_uint(t.w));
            }
            const float inv = __fdividef(1.0f, fmaf(tot, 1.0f / HID, 1e-6f));
            const uint32_t e0 = acc_exp(z) - 9u;
            const uint32_t j = min(max(max(__float_as_uint(fmaf(mx, inv, 1.0f) * 1.01f) >> 23, 130u) - 130u, max(bm >> 23, e0 + 12u) - (e0 + 12u)), 126u);
            const float dn = __uint_as_float((127u - j) << 23) * (HSCALE * 1.00235f);
#pragma unroll
            for (int i = 0; i < 4; i++)
                *reinterpret_cast<uint16_t*>(smem + P2_OFF_GRN + (tid + 384 * i) * 2) = pack_f16(fmaf(gx[i], inv, 1.0f) * dn, 0.f);
            const uint32_t e = min(e0 + j, 253u);
            up = e * 0x00800080u;
#pragma unroll
            for (int i = 0; i < 2; i++)
                *reinterpret_cast<uint16_t*>(smem + P2_OFF_BIAS + (tid >> 1) * 8 + i * 4 + (tid & 1) * 2) = pack_f16(bias * __uint_as_float((254u - e) << 23), 0.f);
            TSTAMP(1, 25);
            bar_sync(1, 384);
            if (wg == 1 && blockIdx.x < 96) {
                const uint4* src = g_w2img[0] + blockIdx.x * 768 + tid - 128;
                const uint4 fk = *reinterpret_cast<const uint4*>(smem + P2_OFF_GRN + blockIdx.x * 32 + (tid & 8) * 2);
                uint4 v[6];
#pragma unroll
                for (int i = 0; i < 6; i++) v[i] = __ldcg(src + i * 128);
                auto fold = [&](uint32_t b, uint32_t f) { return (h2_mul(b, f) + 0x00040004u) & 0xfff8fff8u; };
#pragma unroll
                for (int i = 0; i < 6; i++)
                    g_w2img[1][blockIdx.x * 768 + tid - 128 + i * 128] = make_uint4(fold(v[i].x, fk.x), fold(v[i].y, fk.y), fold(v[i].z, fk.z), fold(v[i].w, fk.w));
                asm volatile("fence.proxy.async.global;\n" ::: "memory");
                __threadfence();
                __syncwarp();
                if (lane == 0) asm volatile("red.release.gpu.global.add.u32 [%0], 1;\n" ::"l"(&g_img[1]) : "memory");
            }
        }
        TSTAMP(1, 28);
        int kt = k0, pos;
        const uint32_t be = lane < 2 ? mapa(bar_bempty, lane) : 0, be0 = mapa(bar_bempty, 0);
        uint32_t prev = 0, sa = 0, pa = 0;
        auto release_b = [&](uint32_t p, bool on) {
            asm volatile("{\n.reg .pred p, q;\nsetp.ne.u32 q, %2, 0;\nsetp.ne.and.u32 p, %1, 0, q;\n@p mbarrier.arrive.shared::cluster.b64 _, [%0];\n}\n"
                         ::"r"(be + p), "r"(be), "r"((uint32_t)on) : "memory");
        };
        auto arrive1 = [&](uint32_t bar) {
            asm volatile("{\n.reg .pred p;\nsetp.eq.u32 p, %1, %2;\n@p mbarrier.arrive.shared::cta.b64 _, [%0];\n}\n" ::"r"(bar), "r"(be), "r"(be0) : "memory");
        };
        auto seek = [&](int p) {
            pos = p;
            st = p % P2_NB * 8;
            ph = p / P2_NB & 1;
            int v;
            while (true) {
                asm volatile("ld.volatile.shared.u32 %0, [%1];\n" : "=r"(v) : "r"(s_pos) : "memory");
                if (__all_sync(0xffffffffu, v >= p)) break;
                __nanosleep(200);
                SAFE_BREAK
            }
        };
        bool ok_a = false;
        auto fetch = [&](uint4 (&a)[2], uint32_t done, bool rel, bool early, bool wait = true) {
            if (!ok_a) mbar_wait(af + sa, pa);
            uint32_t o[6];
            const uint32_t src = s_a + sa * (P2_A / 8);
            asm volatile("ldmatrix.sync.aligned.m8n8.x4.trans.shared.b16 {%0,%1,%2,%3}, [%4];\n"
                         : "=r"(o[0]), "=r"(o[1]), "=r"(o[2]), "=r"(o[3]) : "r"(src) : "memory");
            asm volatile("ldmatrix.sync.aligned.m8n8.x2.trans.shared.b16 {%0,%1}, [%2];\n"
                         : "=r"(o[4]), "=r"(o[5]) : "r"(src + 2048) : "memory");
            if ((sa += 8) == P2_NA * 8) { sa = 0; pa ^= 1; }
            if (wait) wg_wait<1>();
            asm volatile("" ::"r"(a[0].x), "r"(a[0].y), "r"(a[0].z), "r"(a[0].w), "r"(a[1].x), "r"(a[1].y), "r"(a[1].z), "r"(a[1].w));
            release_b(done, rel);
            ok_a = mbar_test(af + sa, pa);
            const bool ok_b = mbar_test(bar_bfull + st, ph);
            p2_unpack(a[0], o[0], o[1], o[2]);
            p2_unpack(a[1], o[3], o[4], o[5]);
            if (early) {
                const uint32_t* t = reinterpret_cast<const uint32_t*>(smem + P2_OFF_GRN) + kt * 16 + q;
#pragma unroll
                for (int i = 0; i < 2; i++)
                    a[i] = make_uint4(h2_mul(a[i].x, t[8 * i]), h2_mul(a[i].y, t[8 * i]), h2_mul(a[i].z, t[8 * i + 4]), h2_mul(a[i].w, t[8 * i + 4]));
                if (++kt == 48) kt = 0;
            }
            if (!ok_b) mbar_wait(bar_bfull + st, ph);
        };
        const uint64_t db0 = make_desc(sbase, 128, 256);
        auto step = [&](const uint4 (&a)[2], uint4 (&an)[2], bool cont, bool add, bool early) {
            TR2(0);
            const uint64_t db = db0 + st * (P2_B / 128);
            wg_fence();
            mma_rs_n192(acc0, a[0], db, add);
            mma_rs_n192(acc1, a[0], db + 384, add);
            mma_rs_n192(acc0, a[1], db + 768, 1);
            mma_rs_n192(acc1, a[1], db + 768 + 384, 1);
            wg_commit();
            arrive1(af + 3 * P2_NA * 8 - 8 + (sa ? sa : P2_NA * 8));
            const uint32_t done = prev;
            prev = st;
            if ((st += 8) == P2_NB * 8) { st = 0; ph ^= 1; }
            fetch(an, done, cont, early);
            pos++;
        };
        int n = wg == 2 && head ? -1 : wg;
#pragma unroll
        for (int c = 0; c < 12; c++) p2_init(c < 6 ? acc0 : acc1, c, sbase + P2_OFF_BIAS + q * 32);
        a0[0] = a0[1] = a1[0] = a1[1] = make_uint4(zero, zero, zero, zero);
        seek(p2_start(n));
        fetch(a0, 0, false, n <= 0, false);
#pragma unroll 1
        for (;; n += 3) {
            TSTAMP(1, 2 + n);
            const int p0 = n < 0 || n == P2_ITEMS ? 12 : 0, pe = n <= 0 ? p0 + P2_FOLD / 2 : 0;
            const bool more = n + 3 < P2_ITEMS + tail;
#pragma unroll 1
            for (int p = p0; p < 24; p++) {
                step(a0, a1, p != p0, p != p0 || n != P2_ITEMS, p < pe);
                step(a1, a0, true, true, p < pe);
            }
            if (n == P2_ITEMS) {
                flag_wait<true>(&g_half[pair][rank], 1);
                TR2(1);
                wg_wait<0>();
                TR2(2);
                release_b(prev, true);
                uint8_t* o = reinterpret_cast<uint8_t*>(out) + (size_t)((2 * p2_tile(cl, -1) + rank) * 64 + (g & 1) * 32 + w * 8 + (g >> 1)) * P2_XROW + q * 16;
                p2_epilogue_add(acc0, o, up, zero);
                p2_epilogue_add(acc1, o + 384, up, zero);
                TR2(3);
                break;
            }
            mbar_wait(bar_xfull, (n + head) & 1);
            TR2(1);
            wg_wait<0>();
            TR2(2);
            release_b(prev, true);
            p2_epilogue(acc0, acc1, sx, sbase + P2_OFF_BIAS + q * 32, up, zero);
            TR2(3);
            asm volatile("fence.proxy.async.shared::cta;\n" ::: "memory");
            __syncwarp();
            arrive1(bar_oready);
            if (!more) break;
            ok_a = false;
            seek(p2_start(n + 3));
            mbar_wait(bar_bfull + st, ph);
        }
        if (blockIdx.x == 120 && threadIdx.x < (LN_RING + 3 + NSMALL) * 2) (&g_flag[0][0][0])[threadIdx.x * 8] = 0;
        if (blockIdx.x == 121 && threadIdx.x == 0) atomicAdd(&g_epoch, 1u);
        TSTAMP(1, 30);
    }
}

}

extern "C" void kernel_launch(void* const* d_in, const int* in_sizes, int n_in, void* d_out, int out_size) {
    const __nv_bfloat16* x = (const __nv_bfloat16*)d_in[0];
    const __nv_bfloat16* dw = (const __nv_bfloat16*)d_in[1];
    const __nv_bfloat16* w1 = (const __nv_bfloat16*)d_in[2];
    const __nv_bfloat16* w2 = (const __nv_bfloat16*)d_in[3];
    const __nv_bfloat16* grn_g = (const __nv_bfloat16*)d_in[4];
    const __nv_bfloat16* grn_b = (const __nv_bfloat16*)d_in[5];
    __nv_bfloat16* out = (__nv_bfloat16*)d_out;

    cudaFuncSetAttribute(pass1_kernel<2>, cudaFuncAttributeMaxDynamicSharedMemorySize, P1_SMEM);
    cudaFuncSetAttribute(pass1_kernel<8>, cudaFuncAttributeMaxDynamicSharedMemorySize, P1_SMEM);
    cudaFuncSetAttribute(pass2_kernel, cudaFuncAttributeMaxDynamicSharedMemorySize, P2_SMEM);

    typedef CUresult (*EncodeFn)(CUtensorMap*, CUtensorMapDataType, cuuint32_t, void*, const cuuint64_t*, const cuuint64_t*,
                                 const cuuint32_t*, const cuuint32_t*, CUtensorMapInterleave, CUtensorMapSwizzle,
                                 CUtensorMapL2promotion, CUtensorMapFloatOOBfill);
    static EncodeFn encode = nullptr;
    if (!encode) {
        cudaDriverEntryPointQueryResult qres;
        cudaGetDriverEntryPoint("cuTensorMapEncodeTiled", (void**)&encode, cudaEnableDefault, &qres);
    }
    CUtensorMap wmap;
    const cuuint64_t gdim[2] = {HID, C_DIM};
    const cuuint64_t gstr[1] = {HID * 2};
    const cuuint32_t box[2] = {64, 192}, estr[2] = {1, 1};
    CUresult er = encode(&wmap, CU_TENSOR_MAP_DATA_TYPE_BFLOAT16, 2, (void*)w1, gdim, gstr, box, estr, CU_TENSOR_MAP_INTERLEAVE_NONE,
           CU_TENSOR_MAP_SWIZZLE_128B, CU_TENSOR_MAP_L2_PROMOTION_L2_128B, CU_TENSOR_MAP_FLOAT_OOB_FILL_NONE);
    if (er != CUDA_SUCCESS) printf("tensor map encode failed %d\n", (int)er);

    cudaLaunchAttribute attr[1];
    attr[0].id = cudaLaunchAttributeProgrammaticStreamSerialization;
    attr[0].val.programmaticStreamSerializationAllowed = 1;
    cudaLaunchConfig_t cfg = {};
    cfg.stream = 0;
    cfg.blockDim = dim3(512);
    cfg.dynamicSmemBytes = P1_SMEM;
    static int wide = -1;
    if (wide < 0) {
        int n = 0;
        cfg.gridDim = dim3(8 * NGRP);
        wide = cudaOccupancyMaxActiveClusters(&n, pass1_kernel<8>, &cfg) == cudaSuccess && n >= NGRP;
    }
    if (wide) pass1_kernel<8><<<8 * NGRP, 512, P1_SMEM>>>(wmap, x, dw, w1, 0);
    else pass1_kernel<2><<<8 * NGRP, 512, P1_SMEM>>>(wmap, x, dw, w1, 0);
    cfg.attrs = attr;
    cfg.numAttrs = 1;
    cfg.gridDim = dim3(NUM_CTAS);
    cfg.dynamicSmemBytes = P2_SMEM;
    cudaLaunchKernelEx(&cfg, pass2_kernel, wmap, x, w2, grn_g, grn_b, out, 0);
}
```
